```python
import torch

def _softmax(x, axis=-1):
    return torch.softmax(x, dim=axis)
def _gelu(x):
    return torch.nn.functional.gelu(x, approximate="tanh")
def _silu(x):
    return torch.nn.functional.silu(x)
def _sigmoid(x):
    return torch.sigmoid(x)
def _layernorm(x, axis=-1, eps=1e-5):
    m = x.mean(dim=axis, keepdim=True)
    v = x.var(dim=axis, keepdim=True, unbiased=False)
    return (x - m) / torch.sqrt(v + eps)
def _scatter_add(tgt, idx, src, axis=0):
    return tgt.clone().index_add_(axis, idx, src)
def _segment_sum(src, seg, n):
    out = torch.zeros((n,) + src.shape[1:], dtype=src.dtype)
    return out.index_add_(0, seg, src)
def _pad(x, pw):
    flat = tuple(v for pair in reversed(pw) for v in pair)
    return torch.nn.functional.pad(x, flat)

kernel_name = 'interleave_layers__linear_kernel_hedgehog__dense_activation_squared_relu__prompt'

def setup_inputs():

    _w = (lambda a: (lambda t: t.to(torch.bfloat16) if t.is_floating_point() else t)(torch.as_tensor(a)))
    def _A_setup():
        B, S, D, H = 1, 2048, 448, 16
        Dh = D // H
        return {
            "x": _w((lambda *s: torch.randn(*s, dtype=torch.bfloat16) * 0.05)(B, S, D)),
            "wqkv": _w((lambda *s: torch.randn(*s, dtype=torch.bfloat16) * 0.2)(D, 3 * D)),
            "w_phi": _w((lambda *s: torch.randn(*s, dtype=torch.bfloat16) * 0.2)(H, Dh, Dh) * (Dh ** -0.5)),
            "wo": _w((lambda *s: torch.randn(*s, dtype=torch.bfloat16) * 0.05)(D, D)),
        }
    _A_in = _A_setup()

    def _B_setup():
        B, S, D, F = 1, 2048, 448, 1792
        return {
            "x": _w((lambda *s: torch.randn(*s, dtype=torch.bfloat16) * 0.05)(B, S, D)),
            "w1": _w((lambda *s: torch.randn(*s, dtype=torch.bfloat16) * 0.05)(D, F)),
            "b1": _w((lambda *s: torch.randn(*s, dtype=torch.bfloat16) * 0.2)(F)),
            "w2": _w((lambda *s: torch.randn(*s, dtype=torch.bfloat16) * 0.05)(F, D)),
            "b2": _w((lambda *s: torch.randn(*s, dtype=torch.bfloat16) * 0.4)(D)),
        }
    _B_in = _B_setup()

    return {
        "A_x": _A_in["x"],
        "A_wqkv": _A_in["wqkv"],
        "A_w_phi": _A_in["w_phi"],
        "A_wo": _A_in["wo"],
        "B_x": _B_in["x"],
        "B_w1": _B_in["w1"],
        "B_b1": _B_in["b1"],
        "B_w2": _B_in["w2"],
        "B_b2": _B_in["b2"],
    }

def reference(A_x, A_wqkv, A_w_phi, A_wo, B_x, B_w1, B_b1, B_w2, B_b2):
    def _A_ref(x, wqkv, w_phi, wo):
        B, S, D = x.shape
        H = 16; Dh = D // H
        qkv = (lambda x, *d: x.permute(*d))((x @ wqkv).reshape(B, S, 3, H, Dh), 2, 0, 3, 1, 4)
        q, k, v = qkv[0], qkv[1], qkv[2]
        pq = torch.einsum("bhsd,hdf->bhsf", q, w_phi)
        pk = torch.einsum("bhsd,hdf->bhsf", k, w_phi)
        phi_q = torch.concatenate([_softmax(pq, axis=-1), _softmax(-pq, axis=-1)], axis=-1)
        phi_k = torch.concatenate([_softmax(pk, axis=-1), _softmax(-pk, axis=-1)], axis=-1)
        kv = torch.einsum("bhsf,bhsd->bhfd", phi_k, v)
        z  = torch.einsum("bhsf->bhf", phi_k)
        num = torch.einsum("bhqf,bhfd->bhqd", phi_q, kv)
        den = torch.einsum("bhqf,bhf->bhq", phi_q, z)[..., None] + 1e-6
        o = num / den
        return (lambda x, *d: x.permute(*d))(o, 0, 2, 1, 3).reshape(B, S, D) @ wo

    def _B_ref(x, w1, b1, w2, b2):
        h = torch.einsum("bsd,df->bsf", x, w1) + b1
        zero = torch.zeros_like(h)
        r = torch.where(h > zero, h, zero)
        h = r * r
        out = torch.einsum("bsf,fd->bsd", h, w2) + b2
        return out

    x = A_x
    x = x + _A_ref(_layernorm(x, axis=-1), A_wqkv, A_w_phi, A_wo)
    x = x + _B_ref(_layernorm(x, axis=-1), B_w1, B_b1, B_w2, B_b2)
    x = x + _A_ref(_layernorm(x, axis=-1), A_wqkv, A_w_phi, A_wo)
    x = x + _B_ref(_layernorm(x, axis=-1), B_w1, B_b1, B_w2, B_b2)
    return x
```

```cpp
#include <cuda_runtime.h>
#include <cuda_bf16.h>
#include <cuda.h>
#include <stdint.h>

namespace {

constexpr int DM = 448, NCTA = 128;
constexpr int ABYTES = 57344;
constexpr int SLOT = 14336, NSLOT = 7;
constexpr int OFF_RING = 2 * ABYTES;
constexpr int OFF_WPHI = OFF_RING + NSLOT * SLOT;
constexpr int OFF_B1 = OFF_WPHI + 8192;
constexpr int OFF_BAR = OFF_B1 + 896;
constexpr int SMEM_BYTES = OFF_BAR + 256 + 1024;
constexpr int TILES_PER_LAYER = 46;

__device__ __align__(1024) unsigned char gP[16 * 2 * 8 * 8 * 7168];
__device__ __align__(1024) unsigned char gXN[16 * 2 * ABYTES];
__device__ __align__(1024) float4 gKV[2 * 8 * 2 * 5 * 128];
__device__ __align__(128) unsigned gFlag[(4 * 16 * 2 * 5 + 32 + 1) * 32];
#define STAMP(i)

__device__ __forceinline__ uint32_t smem_u32(const void* p) { return (uint32_t)__cvta_generic_to_shared(p); }
__device__ __forceinline__ void mbar_init(uint32_t b, int c) { asm volatile("mbarrier.init.shared::cta.b64 [%0], %1;" ::"r"(b), "r"(c)); }
__device__ __forceinline__ void mbar_expect(uint32_t b, int bytes) { asm volatile("mbarrier.arrive.expect_tx.shared::cta.b64 _, [%0], %1;" ::"r"(b), "r"(bytes) : "memory"); }
__device__ __forceinline__ void mbar_arrive(uint32_t b) { asm volatile("mbarrier.arrive.shared::cta.b64 _, [%0];" ::"r"(b) : "memory"); }
__device__ __forceinline__ void mbar_wait(uint32_t b, int par) {
  uint32_t ok; int n = 0;
  while (true) {
    asm volatile("{.reg .pred p; mbarrier.try_wait.parity.shared::cta.b64 p, [%1], %2; selp.u32 %0,1,0,p;}" : "=r"(ok) : "r"(b), "r"(par) : "memory");
    if (ok) break;
    if (++n > (1 << 22)) break;
  }
}
__device__ __forceinline__ void flag_wait(const unsigned* f, unsigned target) {
  unsigned v; int n = 0;
  while (true) {
    asm volatile("ld.acquire.gpu.global.u32 %0, [%1];" : "=r"(v) : "l"(f) : "memory");
    if ((int)(v - target) >= 0) break;
    if (++n > (1 << 21)) break;
  }
}
__device__ __forceinline__ void flag_arrive(unsigned* f) { asm volatile("red.release.gpu.global.add.u32 [%0], 1;" ::"l"(f) : "memory"); }
__device__ __forceinline__ void fence_async() { asm volatile("fence.proxy.async;" ::: "memory"); }
__device__ __forceinline__ void fence_async_smem() { asm volatile("fence.proxy.async.shared::cta;" ::: "memory"); }
template <int ID, int N> __device__ __forceinline__ void bar_sync() { asm volatile("bar.sync %0, %1;" ::"n"(ID), "n"(N) : "memory"); }
__device__ __forceinline__ void bar_wg(int c) { if (c) bar_sync<2, 128>(); else bar_sync<1, 128>(); }
__device__ __forceinline__ void wg_fence() { asm volatile("wgmma.fence.sync.aligned;" ::: "memory"); }
__device__ __forceinline__ void wg_commit() { asm volatile("wgmma.commit_group.sync.aligned;" ::: "memory"); }
template <int N> __device__ __forceinline__ void wg_wait() { asm volatile("wgmma.wait_group.sync.aligned %0;" ::"n"(N) : "memory"); }
template <int N> __device__ __forceinline__ void reg_fence(float (&d)[N]) {
#pragma unroll
  for (int i = 0; i < N; i++) asm volatile("" : "+f"(d[i])::"memory");
}
__device__ __forceinline__ uint64_t mkdesc(uint32_t addr, uint32_t lbo, uint32_t sbo, uint64_t swz) {
  return (uint64_t)((addr & 0x3FFFF) >> 4) | ((uint64_t)(lbo >> 4) << 16) | ((uint64_t)(sbo >> 4) << 32) | (swz << 62);
}
__device__ __forceinline__ uint32_t pack(float a, float b) {
  uint32_t r; asm("cvt.rn.bf16x2.f32 %0, %1, %2;" : "=r"(r) : "f"(b), "f"(a)); return r;
}
__device__ __forceinline__ float lo(uint32_t u) { return __uint_as_float(u << 16); }
__device__ __forceinline__ float hi(uint32_t u) { return __uint_as_float(u & 0xFFFF0000u); }
__device__ __forceinline__ float ex2(float x) { float y; asm("ex2.approx.ftz.f32 %0, %1;" : "=f"(y) : "f"(x)); return y; }
__device__ __forceinline__ void stsm4(uint32_t a, uint32_t r0, uint32_t r1, uint32_t r2, uint32_t r3) {
  asm volatile("stmatrix.sync.aligned.m8n8.x4.shared.b16 [%0], {%1,%2,%3,%4};" ::"r"(a), "r"(r0), "r"(r1), "r"(r2), "r"(r3) : "memory");
}
__device__ __forceinline__ void tma3(uint32_t dst, const CUtensorMap* m, int c0, int c1, int c2, uint32_t bar) {
  asm volatile("cp.async.bulk.tensor.3d.shared::cluster.global.mbarrier::complete_tx::bytes [%0], [%1, {%3,%4,%5}], [%2];"
               ::"r"(dst), "l"(m), "r"(bar), "r"(c0), "r"(c1), "r"(c2) : "memory");
}
__device__ __forceinline__ void bulk_ld(uint32_t dst, const void* src, int bytes, uint32_t bar) {
  asm volatile("cp.async.bulk.shared::cluster.global.mbarrier::complete_tx::bytes [%0], [%1], %2, [%3];" ::"r"(dst), "l"(src), "r"(bytes), "r"(bar) : "memory");
}
__device__ __forceinline__ uint4 ldcg4(const void* p) {
  uint4 v; asm volatile("ld.global.cg.v4.u32 {%0,%1,%2,%3}, [%4];" : "=r"(v.x), "=r"(v.y), "=r"(v.z), "=r"(v.w) : "l"(p) : "memory"); return v;
}

__device__ __forceinline__ void mma_ss_184(float (&d)[92], uint64_t da, uint64_t db, int acc) {
  asm volatile("{.reg .pred p; setp.ne.b32 p, %94, 0;\n"
    "wgmma.mma_async.sync.aligned.m64n184k16.f32.bf16.bf16 {%0,%1,%2,%3,%4,%5,%6,%7,%8,%9,%10,%11,%12,%13,%14,%15,%16,%17,%18,%19,%20,%21,%22,%23,%24,%25,%26,%27,%28,%29,%30,%31,%32,%33,%34,%35,%36,%37,%38,%39,%40,%41,%42,%43,%44,%45,%46,%47,%48,%49,%50,%51,%52,%53,%54,%55,%56,%57,%58,%59,%60,%61,%62,%63,%64,%65,%66,%67,%68,%69,%70,%71,%72,%73,%74,%75,%76,%77,%78,%79,%80,%81,%82,%83,%84,%85,%86,%87,%88,%89,%90,%91}, %92, %93, p, 1, 1, 0, 1;}\n"
    : "+f"(d[0]),"+f"(d[1]),"+f"(d[2]),"+f"(d[3]),"+f"(d[4]),"+f"(d[5]),"+f"(d[6]),"+f"(d[7]),"+f"(d[8]),"+f"(d[9]),"+f"(d[10]),"+f"(d[11]),"+f"(d[12]),"+f"(d[13]),"+f"(d[14]),"+f"(d[15]),"+f"(d[16]),"+f"(d[17]),"+f"(d[18]),"+f"(d[19]),"+f"(d[20]),"+f"(d[21]),"+f"(d[22]),"+f"(d[23]),"+f"(d[24]),"+f"(d[25]),"+f"(d[26]),"+f"(d[27]),"+f"(d[28]),"+f"(d[29]),"+f"(d[30]),"+f"(d[31]),"+f"(d[32]),"+f"(d[33]),"+f"(d[34]),"+f"(d[35]),"+f"(d[36]),"+f"(d[37]),"+f"(d[38]),"+f"(d[39]),"+f"(d[40]),"+f"(d[41]),"+f"(d[42]),"+f"(d[43]),"+f"(d[44]),"+f"(d[45]),"+f"(d[46]),"+f"(d[47]),"+f"(d[48]),"+f"(d[49]),"+f"(d[50]),"+f"(d[51]),"+f"(d[52]),"+f"(d[53]),"+f"(d[54]),"+f"(d[55]),"+f"(d[56]),"+f"(d[57]),"+f"(d[58]),"+f"(d[59]),"+f"(d[60]),"+f"(d[61]),"+f"(d[62]),"+f"(d[63]),"+f"(d[64]),"+f"(d[65]),"+f"(d[66]),"+f"(d[67]),"+f"(d[68]),"+f"(d[69]),"+f"(d[70]),"+f"(d[71]),"+f"(d[72]),"+f"(d[73]),"+f"(d[74]),"+f"(d[75]),"+f"(d[76]),"+f"(d[77]),"+f"(d[78]),"+f"(d[79]),"+f"(d[80]),"+f"(d[81]),"+f"(d[82]),"+f"(d[83]),"+f"(d[84]),"+f"(d[85]),"+f"(d[86]),"+f"(d[87]),"+f"(d[88]),"+f"(d[89]),"+f"(d[90]),"+f"(d[91])
    : "l"(da), "l"(db), "r"(acc));
}
__device__ __forceinline__ void mma_ss_224(float (&d)[112], uint64_t da, uint64_t db, int acc) {
  asm volatile("{.reg .pred p; setp.ne.b32 p, %114, 0;\n"
    "wgmma.mma_async.sync.aligned.m64n224k16.f32.bf16.bf16 {%0,%1,%2,%3,%4,%5,%6,%7,%8,%9,%10,%11,%12,%13,%14,%15,%16,%17,%18,%19,%20,%21,%22,%23,%24,%25,%26,%27,%28,%29,%30,%31,%32,%33,%34,%35,%36,%37,%38,%39,%40,%41,%42,%43,%44,%45,%46,%47,%48,%49,%50,%51,%52,%53,%54,%55,%56,%57,%58,%59,%60,%61,%62,%63,%64,%65,%66,%67,%68,%69,%70,%71,%72,%73,%74,%75,%76,%77,%78,%79,%80,%81,%82,%83,%84,%85,%86,%87,%88,%89,%90,%91,%92,%93,%94,%95,%96,%97,%98,%99,%100,%101,%102,%103,%104,%105,%106,%107,%108,%109,%110,%111}, %112, %113, p, 1, 1, 0, 1;}\n"
    : "+f"(d[0]),"+f"(d[1]),"+f"(d[2]),"+f"(d[3]),"+f"(d[4]),"+f"(d[5]),"+f"(d[6]),"+f"(d[7]),"+f"(d[8]),"+f"(d[9]),"+f"(d[10]),"+f"(d[11]),"+f"(d[12]),"+f"(d[13]),"+f"(d[14]),"+f"(d[15]),"+f"(d[16]),"+f"(d[17]),"+f"(d[18]),"+f"(d[19]),"+f"(d[20]),"+f"(d[21]),"+f"(d[22]),"+f"(d[23]),"+f"(d[24]),"+f"(d[25]),"+f"(d[26]),"+f"(d[27]),"+f"(d[28]),"+f"(d[29]),"+f"(d[30]),"+f"(d[31]),"+f"(d[32]),"+f"(d[33]),"+f"(d[34]),"+f"(d[35]),"+f"(d[36]),"+f"(d[37]),"+f"(d[38]),"+f"(d[39]),"+f"(d[40]),"+f"(d[41]),"+f"(d[42]),"+f"(d[43]),"+f"(d[44]),"+f"(d[45]),"+f"(d[46]),"+f"(d[47]),"+f"(d[48]),"+f"(d[49]),"+f"(d[50]),"+f"(d[51]),"+f"(d[52]),"+f"(d[53]),"+f"(d[54]),"+f"(d[55]),"+f"(d[56]),"+f"(d[57]),"+f"(d[58]),"+f"(d[59]),"+f"(d[60]),"+f"(d[61]),"+f"(d[62]),"+f"(d[63]),"+f"(d[64]),"+f"(d[65]),"+f"(d[66]),"+f"(d[67]),"+f"(d[68]),"+f"(d[69]),"+f"(d[70]),"+f"(d[71]),"+f"(d[72]),"+f"(d[73]),"+f"(d[74]),"+f"(d[75]),"+f"(d[76]),"+f"(d[77]),"+f"(d[78]),"+f"(d[79]),"+f"(d[80]),"+f"(d[81]),"+f"(d[82]),"+f"(d[83]),"+f"(d[84]),"+f"(d[85]),"+f"(d[86]),"+f"(d[87]),"+f"(d[88]),"+f"(d[89]),"+f"(d[90]),"+f"(d[91]),"+f"(d[92]),"+f"(d[93]),"+f"(d[94]),"+f"(d[95]),"+f"(d[96]),"+f"(d[97]),"+f"(d[98]),"+f"(d[99]),"+f"(d[100]),"+f"(d[101]),"+f"(d[102]),"+f"(d[103]),"+f"(d[104]),"+f"(d[105]),"+f"(d[106]),"+f"(d[107]),"+f"(d[108]),"+f"(d[109]),"+f"(d[110]),"+f"(d[111])
    : "l"(da), "l"(db), "r"(acc));
}
__device__ __forceinline__ void mma_rs_224(float (&d)[112], uint32_t a0, uint32_t a1, uint32_t a2, uint32_t a3, uint64_t db, int acc) {
  asm volatile("{.reg .pred p; setp.ne.b32 p, %117, 0;\n"
    "wgmma.mma_async.sync.aligned.m64n224k16.f32.bf16.bf16 {%0,%1,%2,%3,%4,%5,%6,%7,%8,%9,%10,%11,%12,%13,%14,%15,%16,%17,%18,%19,%20,%21,%22,%23,%24,%25,%26,%27,%28,%29,%30,%31,%32,%33,%34,%35,%36,%37,%38,%39,%40,%41,%42,%43,%44,%45,%46,%47,%48,%49,%50,%51,%52,%53,%54,%55,%56,%57,%58,%59,%60,%61,%62,%63,%64,%65,%66,%67,%68,%69,%70,%71,%72,%73,%74,%75,%76,%77,%78,%79,%80,%81,%82,%83,%84,%85,%86,%87,%88,%89,%90,%91,%92,%93,%94,%95,%96,%97,%98,%99,%100,%101,%102,%103,%104,%105,%106,%107,%108,%109,%110,%111}, {%112,%113,%114,%115}, %116, p, 1, 1, 1;}\n"
    : "+f"(d[0]),"+f"(d[1]),"+f"(d[2]),"+f"(d[3]),"+f"(d[4]),"+f"(d[5]),"+f"(d[6]),"+f"(d[7]),"+f"(d[8]),"+f"(d[9]),"+f"(d[10]),"+f"(d[11]),"+f"(d[12]),"+f"(d[13]),"+f"(d[14]),"+f"(d[15]),"+f"(d[16]),"+f"(d[17]),"+f"(d[18]),"+f"(d[19]),"+f"(d[20]),"+f"(d[21]),"+f"(d[22]),"+f"(d[23]),"+f"(d[24]),"+f"(d[25]),"+f"(d[26]),"+f"(d[27]),"+f"(d[28]),"+f"(d[29]),"+f"(d[30]),"+f"(d[31]),"+f"(d[32]),"+f"(d[33]),"+f"(d[34]),"+f"(d[35]),"+f"(d[36]),"+f"(d[37]),"+f"(d[38]),"+f"(d[39]),"+f"(d[40]),"+f"(d[41]),"+f"(d[42]),"+f"(d[43]),"+f"(d[44]),"+f"(d[45]),"+f"(d[46]),"+f"(d[47]),"+f"(d[48]),"+f"(d[49]),"+f"(d[50]),"+f"(d[51]),"+f"(d[52]),"+f"(d[53]),"+f"(d[54]),"+f"(d[55]),"+f"(d[56]),"+f"(d[57]),"+f"(d[58]),"+f"(d[59]),"+f"(d[60]),"+f"(d[61]),"+f"(d[62]),"+f"(d[63]),"+f"(d[64]),"+f"(d[65]),"+f"(d[66]),"+f"(d[67]),"+f"(d[68]),"+f"(d[69]),"+f"(d[70]),"+f"(d[71]),"+f"(d[72]),"+f"(d[73]),"+f"(d[74]),"+f"(d[75]),"+f"(d[76]),"+f"(d[77]),"+f"(d[78]),"+f"(d[79]),"+f"(d[80]),"+f"(d[81]),"+f"(d[82]),"+f"(d[83]),"+f"(d[84]),"+f"(d[85]),"+f"(d[86]),"+f"(d[87]),"+f"(d[88]),"+f"(d[89]),"+f"(d[90]),"+f"(d[91]),"+f"(d[92]),"+f"(d[93]),"+f"(d[94]),"+f"(d[95]),"+f"(d[96]),"+f"(d[97]),"+f"(d[98]),"+f"(d[99]),"+f"(d[100]),"+f"(d[101]),"+f"(d[102]),"+f"(d[103]),"+f"(d[104]),"+f"(d[105]),"+f"(d[106]),"+f"(d[107]),"+f"(d[108]),"+f"(d[109]),"+f"(d[110]),"+f"(d[111])
    : "r"(a0), "r"(a1), "r"(a2), "r"(a3), "l"(db), "r"(acc));
}
__device__ __forceinline__ void mma_rs_56(float (&d)[28], uint32_t a0, uint32_t a1, uint32_t a2, uint32_t a3, uint64_t db, int acc) {
  asm volatile("{.reg .pred p; setp.ne.b32 p, %33, 0;\n"
    "wgmma.mma_async.sync.aligned.m64n56k16.f32.bf16.bf16 {%0,%1,%2,%3,%4,%5,%6,%7,%8,%9,%10,%11,%12,%13,%14,%15,%16,%17,%18,%19,%20,%21,%22,%23,%24,%25,%26,%27}, {%28,%29,%30,%31}, %32, p, 1, 1, 1;}\n"
    : "+f"(d[0]),"+f"(d[1]),"+f"(d[2]),"+f"(d[3]),"+f"(d[4]),"+f"(d[5]),"+f"(d[6]),"+f"(d[7]),"+f"(d[8]),"+f"(d[9]),"+f"(d[10]),"+f"(d[11]),"+f"(d[12]),"+f"(d[13]),"+f"(d[14]),"+f"(d[15]),"+f"(d[16]),"+f"(d[17]),"+f"(d[18]),"+f"(d[19]),"+f"(d[20]),"+f"(d[21]),"+f"(d[22]),"+f"(d[23]),"+f"(d[24]),"+f"(d[25]),"+f"(d[26]),"+f"(d[27])
    : "r"(a0), "r"(a1), "r"(a2), "r"(a3), "l"(db), "r"(acc));
}
__device__ __forceinline__ void mma_ss_64t(float (&d)[32], uint64_t da, uint64_t db, int acc) {
  asm volatile("{.reg .pred p; setp.ne.b32 p, %34, 0;\n"
    "wgmma.mma_async.sync.aligned.m64n64k16.f32.bf16.bf16 {%0,%1,%2,%3,%4,%5,%6,%7,%8,%9,%10,%11,%12,%13,%14,%15,%16,%17,%18,%19,%20,%21,%22,%23,%24,%25,%26,%27,%28,%29,%30,%31}, %32, %33, p, 1, 1, 1, 1;}\n"
    : "+f"(d[0]),"+f"(d[1]),"+f"(d[2]),"+f"(d[3]),"+f"(d[4]),"+f"(d[5]),"+f"(d[6]),"+f"(d[7]),"+f"(d[8]),"+f"(d[9]),"+f"(d[10]),"+f"(d[11]),"+f"(d[12]),"+f"(d[13]),"+f"(d[14]),"+f"(d[15]),"+f"(d[16]),"+f"(d[17]),"+f"(d[18]),"+f"(d[19]),"+f"(d[20]),"+f"(d[21]),"+f"(d[22]),"+f"(d[23]),"+f"(d[24]),"+f"(d[25]),"+f"(d[26]),"+f"(d[27]),"+f"(d[28]),"+f"(d[29]),"+f"(d[30]),"+f"(d[31])
    : "l"(da), "l"(db), "r"(acc));
}
__device__ __forceinline__ void mma_rs_64(float (&d)[32], uint32_t a0, uint32_t a1, uint32_t a2, uint32_t a3, uint64_t db, int acc) {
  asm volatile("{.reg .pred p; setp.ne.b32 p, %37, 0;\n"
    "wgmma.mma_async.sync.aligned.m64n64k16.f32.bf16.bf16 {%0,%1,%2,%3,%4,%5,%6,%7,%8,%9,%10,%11,%12,%13,%14,%15,%16,%17,%18,%19,%20,%21,%22,%23,%24,%25,%26,%27,%28,%29,%30,%31}, {%32,%33,%34,%35}, %36, p, 1, 1, 1;}\n"
    : "+f"(d[0]),"+f"(d[1]),"+f"(d[2]),"+f"(d[3]),"+f"(d[4]),"+f"(d[5]),"+f"(d[6]),"+f"(d[7]),"+f"(d[8]),"+f"(d[9]),"+f"(d[10]),"+f"(d[11]),"+f"(d[12]),"+f"(d[13]),"+f"(d[14]),"+f"(d[15]),"+f"(d[16]),"+f"(d[17]),"+f"(d[18]),"+f"(d[19]),"+f"(d[20]),"+f"(d[21]),"+f"(d[22]),"+f"(d[23]),"+f"(d[24]),"+f"(d[25]),"+f"(d[26]),"+f"(d[27]),"+f"(d[28]),"+f"(d[29]),"+f"(d[30]),"+f"(d[31])
    : "r"(a0), "r"(a1), "r"(a2), "r"(a3), "l"(db), "r"(acc));
}

__device__ __forceinline__ void dual_softmax(const float (&p)[28], uint32_t (&phi)[4][7]) {
  constexpr float L2E = 1.4426950408889634f;
#pragma unroll
  for (int i = 0; i < 4; i++) {
    float mx = p[i], mn = p[i];
#pragma unroll
    for (int j = 1; j < 7; j++) { mx = fmaxf(mx, p[4 * j + i]); mn = fminf(mn, p[4 * j + i]); }
    mx = fmaxf(mx, __shfl_xor_sync(~0u, mx, 1)); mn = fminf(mn, __shfl_xor_sync(~0u, mn, 1));
    mx = fmaxf(mx, __shfl_xor_sync(~0u, mx, 2)); mn = fminf(mn, __shfl_xor_sync(~0u, mn, 2));
    float a[7], b[7], sa = 0.f, sb = 0.f;
    const float mxl = mx * L2E, mnl = mn * L2E;
#pragma unroll
    for (int j = 0; j < 7; j++) {
      a[j] = ex2(fmaf(p[4 * j + i], L2E, -mxl)); b[j] = ex2(fmaf(p[4 * j + i], -L2E, mnl));
      sa += a[j]; sb += b[j];
    }
    sa += __shfl_xor_sync(~0u, sa, 1); sb += __shfl_xor_sync(~0u, sb, 1);
    sa += __shfl_xor_sync(~0u, sa, 2); sb += __shfl_xor_sync(~0u, sb, 2);
    const float ra = __fdividef(1.f, sa), rb = __fdividef(1.f, sb);
#pragma unroll
    for (int j = 0; j < 7; j++) phi[i][j] = pack(a[j] * ra, b[j] * rb);
  }
}

struct Ring {
  uint32_t full, empty, base; int slot, par;
  __device__ __forceinline__ uint32_t acquire() { mbar_wait(full + slot * 8, par); return base + slot * SLOT; }
  __device__ __forceinline__ int advance() { int s = slot; if (++slot == NSLOT) { slot = 0; par ^= 1; } return s; }
  __device__ __forceinline__ void release(int s, bool elect) { if (elect) mbar_arrive(empty + s * 8); }
};

__device__ __forceinline__ void store_partials(const float (&acc)[112], unsigned char* p0, int nh) {
#pragma unroll
  for (int q = 0; q < 7; q++) {
#pragma unroll
    for (int hh = 0; hh < 2; hh++) {
      uint4 v;
      v.x = pack(acc[16 * q + 2 * hh], acc[16 * q + 2 * hh + 1]);
      v.y = pack(acc[16 * q + 4 + 2 * hh], acc[16 * q + 5 + 2 * hh]);
      v.z = pack(acc[16 * q + 8 + 2 * hh], acc[16 * q + 9 + 2 * hh]);
      v.w = pack(acc[16 * q + 12 + 2 * hh], acc[16 * q + 13 + 2 * hh]);
      *reinterpret_cast<uint4*>(p0 + hh * (8 * 7168) + (nh * 7 + q) * 64) = v;
    }
  }
}

__global__ void __launch_bounds__(384, 1)
fused_kernel(const __grid_constant__ CUtensorMap mQKV, const __grid_constant__ CUtensorMap mWO,
             const __grid_constant__ CUtensorMap mW1, const __grid_constant__ CUtensorMap mW2,
             const __nv_bfloat16* __restrict__ x, const __nv_bfloat16* __restrict__ wphi,
             const __nv_bfloat16* __restrict__ b1, const __nv_bfloat16* __restrict__ b2,
             const __nv_bfloat16* __restrict__ wo, const __nv_bfloat16* __restrict__ w1,
             const __nv_bfloat16* __restrict__ w2, __nv_bfloat16* __restrict__ out) {
  extern __shared__ unsigned char smem_raw[];
  const uint32_t sb = (smem_u32(smem_raw) + 1023) & ~1023u;
  unsigned char* sg = smem_raw + (sb - smem_u32(smem_raw));
  const int tid = threadIdx.x, lane = tid & 31;
  const int G = blockIdx.x >> 3, r = blockIdx.x & 7;
  const uint32_t barFull = sb + OFF_BAR, barEmpty = barFull + 56, barA = barEmpty + 56;
  if (tid == 0) {
    for (int i = 0; i < NSLOT; i++) { mbar_init(barFull + i * 8, 1); mbar_init(barEmpty + i * 8, 2); }
    for (int i = 0; i < 14; i++) mbar_init(barA + i * 8, 1);
    asm volatile("fence.mbarrier_init.release.cluster;" ::: "memory");
  }
  __syncthreads();
  unsigned* const fDone = gFlag + (640 + 32) * 32;

  const int wgid = __shfl_sync(~0u, tid >> 7, 0);
  if (wgid == 2) {
    asm volatile("setmaxnreg.dec.sync.aligned.u32 24;");
    if (tid == 256) {
      int slot = 0, par = 1;
      for (int it = 0; it < 2 * TILES_PER_LAYER; it++) {
        const int i = it >= TILES_PER_LAYER ? it - TILES_PER_LAYER : it;
        mbar_wait(barEmpty + slot * 8, par);
        const uint32_t dst = sb + OFF_RING + slot * SLOT, fb = barFull + slot * 8;
        if (i < 14) { mbar_expect(fb, 12288); tma3(dst, &mQKV, 56 * r, 32 * i, 0, fb); }
        else if (i < 18) { mbar_expect(fb, SLOT); tma3(dst, &mWO, 0, 56 * r + 32 * ((i - 14) & 1), 7 * ((i - 14) >> 1), fb); }
        else if (i < 32) { mbar_expect(fb, SLOT); tma3(dst, &mW1, 0, 32 * (i - 18), 7 * r, fb); }
        else { const int j = i - 32, nh = j >= 7; mbar_expect(fb, SLOT); tma3(dst, &mW2, 0, 224 * r + 32 * (j - 7 * nh), 7 * nh, fb); }
        if (++slot == NSLOT) { slot = 0; par ^= 1; }
      }
    } else if (tid > 288 && tid <= 291) {
      const char* src = lane == 1 ? (const char*)wo + blockIdx.x * 3136 : (lane == 2 ? (const char*)w1 : (const char*)w2) + blockIdx.x * 12544;
      asm volatile("cp.async.bulk.prefetch.L2.global [%0], %1;" ::"l"(src), "r"(lane == 1 ? 3136 : 12544) : "memory");
    }
  } else {
  asm volatile("setmaxnreg.inc.sync.aligned.u32 240;");
  const int c = wgid, w = (tid >> 5) & 3, g = lane >> 2, t = lane & 3;
  const bool elect = (tid & 127) == 0;
  const uint32_t abuf = sb + c * ABYTES;
  unsigned epoch;
  asm volatile("ld.relaxed.gpu.global.u32 %0, [%1];" : "=r"(epoch) : "l"(fDone) : "memory");

  uint32_t xr[2][2][4];
  const int orow = G * 128 + c * 64 + r * 8 + w * 2;
  {
    uint4 v[4][7];
    const int u = lane & 7;
#pragma unroll
    for (int i = 0; i < 4; i++) {
      const uint4* src = reinterpret_cast<const uint4*>(x + (size_t)(G * 128 + c * 64 + w * 16 + i * 4 + (lane >> 3)) * DM) + u;
#pragma unroll
      for (int k = 0; k < 7; k++) v[i][k] = __ldg(src + k * 8);
    }
#pragma unroll
    for (int rr = 0; rr < 2; rr++)
#pragma unroll
      for (int m = 0; m < 2; m++)
#pragma unroll
        for (int jj = 0; jj < 4; jj++)
          xr[rr][m][jj] = lane < 28 ? __ldg(reinterpret_cast<const uint32_t*>(x + (size_t)(orow + rr) * DM + (g + 7 * m) * 32 + jj * 8 + 2 * t)) : 0u;
    for (int i = tid; i < 64 * 32; i += 256) {
      const int k = i >> 5, n2 = i & 31, j = n2 >> 2, tt = n2 & 3;
      uint32_t val = 0;
      if (k < 56 && j < 7) {
        const int e = k >= 28;
        const uint32_t wv = __bfloat16_as_ushort(wphi[(2 * r + e) * 784 + (k - 28 * e) * 28 + 4 * j + tt]);
        val = e ? wv << 16 : wv;
      }
      *reinterpret_cast<uint32_t*>(sg + OFF_WPHI + k * 128 + ((j ^ (k & 7)) << 4) + tt * 4) = val;
    }
    if (tid < 224) reinterpret_cast<float*>(sg + OFF_B1)[tid] = __bfloat162float(b1[224 * r + tid]);
    if (G == 0) {
      for (int i = tid; i < 2 * 1280; i += 256) gKV[((i >= 1280) * 8 + r) * 1280 + (i >= 1280 ? i - 1280 : i)] = make_float4(0.f, 0.f, 0.f, 0.f);
    }
#pragma unroll
    for (int i = 0; i < 4; i++) {
      float s = 0.f;
#pragma unroll
      for (int k = 0; k < 7; k++) s += (lo(v[i][k].x) + hi(v[i][k].x)) + (lo(v[i][k].y) + hi(v[i][k].y)) + (lo(v[i][k].z) + hi(v[i][k].z)) + (lo(v[i][k].w) + hi(v[i][k].w));
      s += __shfl_xor_sync(~0u, s, 1); s += __shfl_xor_sync(~0u, s, 2); s += __shfl_xor_sync(~0u, s, 4);
      const float mean = s * (1.f / DM);
      float q = 0.f;
#pragma unroll
      for (int k = 0; k < 7; k++) {
        const uint32_t e[4] = {v[i][k].x, v[i][k].y, v[i][k].z, v[i][k].w};
#pragma unroll
        for (int z = 0; z < 4; z++) { float a = lo(e[z]) - mean, b = hi(e[z]) - mean; q = fmaf(a, a, q); q = fmaf(b, b, q); }
      }
      q += __shfl_xor_sync(~0u, q, 1); q += __shfl_xor_sync(~0u, q, 2); q += __shfl_xor_sync(~0u, q, 4);
      const float rs = rsqrtf(q * (1.f / DM) + 1e-5f), mb = -mean * rs;
      const int row = w * 16 + i * 4 + (lane >> 3);
#pragma unroll
      for (int k = 0; k < 7; k++) {
        uint4 o;
        o.x = pack(fmaf(lo(v[i][k].x), rs, mb), fmaf(hi(v[i][k].x), rs, mb));
        o.y = pack(fmaf(lo(v[i][k].y), rs, mb), fmaf(hi(v[i][k].y), rs, mb));
        o.z = pack(fmaf(lo(v[i][k].z), rs, mb), fmaf(hi(v[i][k].z), rs, mb));
        o.w = pack(fmaf(lo(v[i][k].w), rs, mb), fmaf(hi(v[i][k].w), rs, mb));
        *reinterpret_cast<uint4*>(sg + c * ABYTES + k * 8192 + row * 128 + ((u ^ (row & 7)) << 4)) = o;
      }
    }
    fence_async_smem();
    bar_sync<3, 256>();
    epoch = epoch / NCTA + 1;
    if (G == 0 && tid == 0) { __threadfence(); flag_arrive(gFlag + (640 + 16 + r) * 32); }
  }
  STAMP(0);
  Ring ring{barFull, barEmpty, sb + OFF_RING, 0, 0};
  unsigned char* const pdst = gP + (size_t)(((G * 2 + c) * 8 + 2 * w) * 8 + r) * 7168 + (g * 56 + t) * 16;
  const unsigned char* const psrc = gP + (size_t)(((G * 2 + c) * 8 + r) * 8) * 7168 + (w * 2 * 56 + lane) * 16;
  unsigned char* const xn_img = gXN + (size_t)(G * 2 + c) * ABYTES;
  const uint32_t stsm_row = w * 16 + ((lane >> 3) & 1) * 8 + (lane & 7);
  const uint32_t stsm_hi = lane >> 4;

  auto exchange = [&](const int xi) {
    unsigned* fl = gFlag + ((xi * 16 + G) * 2 + c) * 5 * 32;
    __syncwarp();
    if (lane == 0) { __threadfence(); flag_arrive(fl + w * 32); flag_wait(fl + (r >> 1) * 32, epoch * 8); }
    __syncwarp();
    STAMP(4 + (xi >> 1) * 12 + (xi & 1) * 5);
    float y[2][2][8];
#pragma unroll
    for (int m = 0; m < 2; m++)
#pragma unroll
      for (int jj = 0; jj < 4; jj++) {
        uint32_t bb = 0;
        if ((xi & 1) && lane < 28) bb = __ldg(reinterpret_cast<const uint32_t*>(b2 + (g + 7 * m) * 32 + jj * 8 + 2 * t));
#pragma unroll
        for (int rr = 0; rr < 2; rr++) { y[rr][m][2 * jj] = lo(bb) + lo(xr[rr][m][jj]); y[rr][m][2 * jj + 1] = hi(bb) + hi(xr[rr][m][jj]); }
      }
    if (lane < 28) {
      uint4 pv[8][4];
#pragma unroll
      for (int s = 0; s < 8; s++)
#pragma unroll
        for (int i = 0; i < 4; i++) pv[s][i] = ldcg4(psrc + s * 7168 + i * 448);
#pragma unroll
      for (int s = 0; s < 8; s++)
#pragma unroll
        for (int i = 0; i < 4; i++) {
          float* yy = y[i >> 1][i & 1];
          yy[0] += lo(pv[s][i].x); yy[1] += hi(pv[s][i].x); yy[2] += lo(pv[s][i].y); yy[3] += hi(pv[s][i].y);
          yy[4] += lo(pv[s][i].z); yy[5] += hi(pv[s][i].z); yy[6] += lo(pv[s][i].w); yy[7] += hi(pv[s][i].w);
        }
    }
#pragma unroll
    for (int rr = 0; rr < 2; rr++)
#pragma unroll
      for (int m = 0; m < 2; m++)
#pragma unroll
        for (int jj = 0; jj < 4; jj++) xr[rr][m][jj] = pack(y[rr][m][2 * jj], y[rr][m][2 * jj + 1]);
    if (xi == 3) {
      if (lane < 28) {
#pragma unroll
        for (int rr = 0; rr < 2; rr++)
#pragma unroll
          for (int m = 0; m < 2; m++)
#pragma unroll
            for (int jj = 0; jj < 4; jj++)
              *reinterpret_cast<uint32_t*>(out + (size_t)(orow + rr) * DM + (g + 7 * m) * 32 + jj * 8 + 2 * t) = xr[rr][m][jj];
      }
      return;
    }
    float s0 = 0.f, s1 = 0.f;
#pragma unroll
    for (int m = 0; m < 2; m++)
#pragma unroll
      for (int jj = 0; jj < 4; jj++) { s0 += lo(xr[0][m][jj]) + hi(xr[0][m][jj]); s1 += lo(xr[1][m][jj]) + hi(xr[1][m][jj]); }
#pragma unroll
    for (int o = 16; o; o >>= 1) { s0 += __shfl_xor_sync(~0u, s0, o); s1 += __shfl_xor_sync(~0u, s1, o); }
    const float mean[2] = {s0 * (1.f / DM), s1 * (1.f / DM)};
    float q[2] = {0.f, 0.f};
    if (lane < 28) {
#pragma unroll
      for (int rr = 0; rr < 2; rr++)
#pragma unroll
        for (int m = 0; m < 2; m++)
#pragma unroll
          for (int jj = 0; jj < 4; jj++) { float a = lo(xr[rr][m][jj]) - mean[rr], b = hi(xr[rr][m][jj]) - mean[rr]; q[rr] = fmaf(a, a, q[rr]); q[rr] = fmaf(b, b, q[rr]); }
    }
#pragma unroll
    for (int o = 16; o; o >>= 1) { q[0] += __shfl_xor_sync(~0u, q[0], o); q[1] += __shfl_xor_sync(~0u, q[1], o); }
    if (lane < 28) {
#pragma unroll
      for (int rr = 0; rr < 2; rr++) {
        const float rs = rsqrtf(q[rr] * (1.f / DM) + 1e-5f), mb = -mean[rr] * rs;
        const int row = r * 8 + w * 2 + rr;
#pragma unroll
        for (int m = 0; m < 2; m++) {
          const int unit = g + 7 * m;
#pragma unroll
          for (int jj = 0; jj < 4; jj++)
            *reinterpret_cast<uint32_t*>(xn_img + (unit >> 1) * 8192 + row * 128 + ((((unit & 1) * 4 + jj) ^ (row & 7)) << 4) + t * 4) =
                pack(fmaf(lo(xr[rr][m][jj]), rs, mb), fmaf(hi(xr[rr][m][jj]), rs, mb));
        }
      }
    }
    fence_async();
    __syncwarp();
    if (lane == 0) { __threadfence(); flag_arrive(fl + 4 * 32); }
    STAMP(5 + (xi >> 1) * 12 + (xi & 1) * 5);
    if (elect) {
      flag_wait(fl + 4 * 32, epoch * 32);
      fence_async();
#pragma unroll
      for (int k = 0; k < 7; k++) { mbar_expect(barA + (c * 7 + k) * 8, 8192); bulk_ld(abuf + k * 8192, xn_img + k * 8192, 8192, barA + (c * 7 + k) * 8); }
    }
    __syncwarp();
    STAMP(6 + (xi >> 1) * 12 + (xi & 1) * 5);
  };

#pragma unroll 1
  for (int layer = 0; layer < 2; layer++) {
    uint32_t phiq[4][7];
    {
      float acc[92];
      int prev = -1;
#pragma unroll
      for (int st = 0; st < 14; st++) {
        if (layer == 1 && !(st & 1)) mbar_wait(barA + (c * 7 + (st >> 1)) * 8, 1);
        const uint32_t bs = ring.acquire();
        wg_fence();
#pragma unroll
        for (int s = 0; s < 2; s++)
          mma_ss_184(acc, mkdesc(abuf + (st >> 1) * 8192 + (st & 1) * 64 + s * 32, 16, 1024, 1), mkdesc(bs + s * 2048, 4096, 1024, 1), st + s);
        wg_commit();
        if (st > 0) { wg_wait<1>(); ring.release(prev, elect); }
        prev = ring.advance();
      }
      wg_wait<0>(); reg_fence(acc);
      ring.release(prev, elect);
      STAMP(1 + layer * 12);
      float pk[28], pq[28];
      const uint32_t wp = sb + OFF_WPHI;
      uint32_t qf[14], kf[14];
#pragma unroll
      for (int i = 0; i < 14; i++) { qf[i] = pack(acc[2 * i], acc[2 * i + 1]); kf[i] = pack(acc[32 + 2 * i], acc[33 + 2 * i]); }
      wg_fence();
#pragma unroll
      for (int s = 0; s < 4; s++)
        mma_rs_56(pk, kf[4 * s], kf[4 * s + 1], s < 3 ? kf[(4 * s + 2) % 14] : 0u, s < 3 ? kf[(4 * s + 3) % 14] : 0u, mkdesc(wp + s * 2048, 4096, 1024, 1), s);
      wg_commit();
#pragma unroll
      for (int s = 0; s < 4; s++)
        mma_rs_56(pq, qf[4 * s], qf[4 * s + 1], s < 3 ? qf[(4 * s + 2) % 14] : 0u, s < 3 ? qf[(4 * s + 3) % 14] : 0u, mkdesc(wp + s * 2048, 4096, 1024, 1), s);
      wg_commit();
      bar_wg(c);
      const uint32_t srow = abuf + stsm_row * 128;
#pragma unroll
      for (int jp = 0; jp < 4; jp++) {
        const int b = 64 + 8 * jp;
        const uint32_t ones = t == 0 ? 0x3F803F80u : 0u;
        stsm4(srow + 16384 + (((2 * jp + stsm_hi) ^ (lane & 7)) << 4), pack(acc[b], acc[b + 1]), pack(acc[b + 2], acc[b + 3]),
              jp < 3 ? pack(acc[(b + 4) % 92], acc[(b + 5) % 92]) : ones, jp < 3 ? pack(acc[(b + 6) % 92], acc[(b + 7) % 92]) : ones);
      }
      wg_wait<1>(); reg_fence(pk);
      uint32_t phik[4][7];
      dual_softmax(pk, phik);
#pragma unroll
      for (int e = 0; e < 2; e++)
#pragma unroll
        for (int jp = 0; jp < 4; jp++)
          stsm4(srow + e * 8192 + (((2 * jp + stsm_hi) ^ (lane & 7)) << 4), phik[e][2 * jp], phik[2 + e][2 * jp],
                jp < 3 ? phik[e][(2 * jp + 1) % 7] : 0u, jp < 3 ? phik[2 + e][(2 * jp + 1) % 7] : 0u);
      fence_async_smem();
      bar_sync<3, 256>();
      float kv[32];
      wg_fence();
#pragma unroll
      for (int s = 0; s < 8; s++) {
        const uint32_t o = sb + (s >> 2) * ABYTES + (s & 3) * 2048;
        mma_ss_64t(kv, mkdesc(o + c * 8192, 4096, 1024, 1), mkdesc(o + 16384, 4096, 1024, 1), s);
      }
      wg_commit();
      if (layer == 0 && lane == 0) flag_wait(gFlag + (640 + 16 + r) * 32, epoch);
      __syncwarp();
      wg_wait<0>(); reg_fence(kv); reg_fence(pq);
      float4* kvg = gKV + ((layer * 8 + r) * 2 + c) * 640 + (tid & 127);
#pragma unroll
      for (int i = 0; i < 5; i++) {
        float v0, v1, v2, v3;
        if (i == 4) { v0 = kv[28]; v1 = kv[29]; v2 = kv[30]; v3 = kv[31]; }
        else { v0 = c ? kv[12 + 4 * i] : kv[4 * i]; v1 = c ? kv[13 + 4 * i] : kv[1 + 4 * i]; v2 = c ? kv[14 + 4 * i] : kv[2 + 4 * i]; v3 = c ? kv[15 + 4 * i] : kv[3 + 4 * i]; }
        asm volatile("red.relaxed.gpu.global.add.v4.f32 [%0], {%1,%2,%3,%4};" ::"l"(kvg + i * 128), "f"(v0), "f"(v1), "f"(v2), "f"(v3) : "memory");
      }
      __syncwarp();
      if (lane == 0) { __threadfence(); flag_arrive(gFlag + (640 + layer * 8 + r) * 32); }
      STAMP(2 + layer * 12);
      dual_softmax(pq, phiq);
    }
    {
      if (lane == 0) flag_wait(gFlag + (640 + layer * 8 + r) * 32, epoch * 128);
      __syncwarp();
      STAMP(3 + layer * 12);
      const float4* kvg = gKV + (layer * 8 + r) * 1280 + (tid & 127);
      uint4 kk[2][5];
#pragma unroll
      for (int e = 0; e < 2; e++)
#pragma unroll
        for (int i = 0; i < 5; i++) kk[e][i] = ldcg4(kvg + e * 640 + i * 128);
      const uint32_t srow = abuf + 24576 + stsm_row * 128;
#pragma unroll
      for (int e = 0; e < 2; e++) {
        uint32_t f[8][2];
#pragma unroll
        for (int j = 0; j < 8; j++) { f[j][0] = 0u; f[j][1] = 0u; }
#pragma unroll
        for (int i = 0; i < 4; i++) {
          const int j = i + 3 * e;
          const bool keep = j != 3 || (e ? t >= 2 : t < 2);
          f[j][0] = keep ? pack(__uint_as_float(kk[e][i].x), __uint_as_float(kk[e][i].y)) : 0u;
          f[j][1] = keep ? pack(__uint_as_float(kk[e][i].z), __uint_as_float(kk[e][i].w)) : 0u;
        }
        if (t == 0) {
          f[7][0] = e ? pack(0.f, __uint_as_float(kk[e][4].y)) : pack(__uint_as_float(kk[e][4].x), 0.f);
          f[7][1] = e ? pack(0.f, __uint_as_float(kk[e][4].w)) : pack(__uint_as_float(kk[e][4].z), 0.f);
        }
#pragma unroll
        for (int jp = 0; jp < 4; jp++)
          stsm4(srow + e * 8192 + (((2 * jp + stsm_hi) ^ (lane & 7)) << 4), f[2 * jp][0], f[2 * jp][1], f[2 * jp + 1][0], f[2 * jp + 1][1]);
      }
      fence_async_smem();
      bar_wg(c);
      float num[32];
      wg_fence();
#pragma unroll
      for (int e = 0; e < 2; e++)
#pragma unroll
        for (int s = 0; s < 4; s++)
          mma_rs_64(num, phiq[e][2 * s], phiq[2 + e][2 * s], s < 3 ? phiq[e][(2 * s + 1) % 7] : 0u, s < 3 ? phiq[2 + e][(2 * s + 1) % 7] : 0u,
                    mkdesc(abuf + 24576 + e * 8192 + s * 2048, 4096, 1024, 1), e + s);
      wg_commit();
      wg_wait<0>(); reg_fence(num);
      float rd[4];
#pragma unroll
      for (int i = 0; i < 4; i++) rd[i] = __fdividef(1.f, __shfl_sync(~0u, num[28 + i], lane & ~3) + 1e-6f);
      uint32_t of[7][2];
#pragma unroll
      for (int j = 0; j < 7; j++) {
        const bool hb = j > 3 || (j == 3 && t >= 2);
        const float r0 = hb ? rd[1] : rd[0], r1 = hb ? rd[3] : rd[2];
        of[j][0] = pack(num[4 * j] * r0, num[4 * j + 1] * r0);
        of[j][1] = pack(num[4 * j + 2] * r1, num[4 * j + 3] * r1);
      }
#pragma unroll
      for (int nh = 0; nh < 2; nh++) {
        float acc[112];
        int sl[2];
#pragma unroll
        for (int st = 0; st < 2; st++) {
          const uint32_t bs = ring.acquire();
          wg_fence();
#pragma unroll
          for (int s = 0; s < 2; s++) {
            const int ks = st * 2 + s;
            mma_rs_224(acc, of[2 * ks][0], of[2 * ks][1], ks < 3 ? of[(2 * ks + 1) % 7][0] : 0u, ks < 3 ? of[(2 * ks + 1) % 7][1] : 0u,
                       mkdesc(bs + s * 1024, 2048, 512, 2), ks);
          }
          wg_commit();
          sl[st] = ring.advance();
        }
        wg_wait<0>(); reg_fence(acc);
        ring.release(sl[0], elect); ring.release(sl[1], elect);
        store_partials(acc, pdst, nh);
      }
    }
    exchange(layer * 2);
    {
      uint32_t hf[28][2];
      {
        float acc[112];
        int prev = -1;
#pragma unroll
        for (int st = 0; st < 14; st++) {
          if (!(st & 1)) mbar_wait(barA + (c * 7 + (st >> 1)) * 8, 0);
          const uint32_t bs = ring.acquire();
          wg_fence();
#pragma unroll
          for (int s = 0; s < 2; s++)
            mma_ss_224(acc, mkdesc(abuf + (st >> 1) * 8192 + (st & 1) * 64 + s * 32, 16, 1024, 1), mkdesc(bs + s * 1024, 2048, 512, 2), st + s);
          wg_commit();
          if (st > 0) { wg_wait<1>(); ring.release(prev, elect); }
          prev = ring.advance();
        }
        wg_wait<0>(); reg_fence(acc);
        ring.release(prev, elect);
        STAMP(7 + layer * 12);
        const float2* bs = reinterpret_cast<const float2*>(sg + OFF_B1) + t;
#pragma unroll
        for (int j = 0; j < 28; j++) {
          const float2 b = bs[4 * j];
          const float h0 = fmaxf(acc[4 * j] + b.x, 0.f), h1 = fmaxf(acc[4 * j + 1] + b.y, 0.f);
          const float h2 = fmaxf(acc[4 * j + 2] + b.x, 0.f), h3 = fmaxf(acc[4 * j + 3] + b.y, 0.f);
          hf[j][0] = pack(h0 * h0, h1 * h1); hf[j][1] = pack(h2 * h2, h3 * h3);
        }
      }
#pragma unroll
      for (int nh = 0; nh < 2; nh++) {
        float acc[112];
        int prev = -1;
#pragma unroll
        for (int st = 0; st < 7; st++) {
          const uint32_t bs = ring.acquire();
          wg_fence();
#pragma unroll
          for (int s = 0; s < 2; s++) {
            const int ks = st * 2 + s;
            mma_rs_224(acc, hf[2 * ks][0], hf[2 * ks][1], hf[2 * ks + 1][0], hf[2 * ks + 1][1], mkdesc(bs + s * 1024, 2048, 512, 2), ks);
          }
          wg_commit();
          if (st > 0) { wg_wait<1>(); ring.release(prev, elect); }
          prev = ring.advance();
        }
        wg_wait<0>(); reg_fence(acc);
        ring.release(prev, elect);
        store_partials(acc, pdst, nh);
      }
      STAMP(8 + layer * 12);
    }
    exchange(layer * 2 + 1);
  }
  STAMP(30);
  if (tid == 0) asm volatile("red.relaxed.gpu.global.add.u32 [%0], 1;" ::"l"(fDone) : "memory");
  }
}

typedef CUresult (*EncFn)(CUtensorMap*, CUtensorMapDataType, cuuint32_t, void*, const cuuint64_t*, const cuuint64_t*,
                          const cuuint32_t*, const cuuint32_t*, CUtensorMapInterleave, CUtensorMapSwizzle,
                          CUtensorMapL2promotion, CUtensorMapFloatOOBfill);

void make_map(EncFn enc, CUtensorMap* m, void* p, uint64_t d0, uint64_t d1, uint64_t d2, uint64_t s1, uint64_t s2,
              uint32_t b0, uint32_t b1, uint32_t b2, CUtensorMapSwizzle sw) {
  cuuint64_t dims[3] = {d0, d1, d2}, strides[2] = {s1, s2};
  cuuint32_t box[3] = {b0, b1, b2}, es[3] = {1, 1, 1};
  enc(m, CU_TENSOR_MAP_DATA_TYPE_BFLOAT16, 3, p, dims, strides, box, es, CU_TENSOR_MAP_INTERLEAVE_NONE, sw,
      CU_TENSOR_MAP_L2_PROMOTION_L2_256B, CU_TENSOR_MAP_FLOAT_OOB_FILL_NONE);
}

}

extern "C" void kernel_launch(void* const* d_in, const int* in_sizes, int n_in, void* d_out, int out_size) {
  static EncFn enc = nullptr;
  if (!enc) {
    cudaDriverEntryPointQueryResult st;
    void* fn = nullptr;
    cudaGetDriverEntryPoint("cuTensorMapEncodeTiled", &fn, cudaEnableDefault, &st);
    enc = (EncFn)fn;
    cudaFuncSetAttribute(fused_kernel, cudaFuncAttributeMaxDynamicSharedMemorySize, SMEM_BYTES);
  }
  CUtensorMap mQKV, mWO, mW1, mW2;
  make_map(enc, &mQKV, d_in[1], 448, 448, 3, 2688, 896, 64, 32, 3, CU_TENSOR_MAP_SWIZZLE_128B);
  make_map(enc, &mWO, d_in[3], 32, 448, 14, 896, 64, 32, 32, 7, CU_TENSOR_MAP_SWIZZLE_64B);
  make_map(enc, &mW1, d_in[5], 32, 448, 56, 3584, 64, 32, 32, 7, CU_TENSOR_MAP_SWIZZLE_64B);
  make_map(enc, &mW2, d_in[7], 32, 1792, 14, 896, 64, 32, 32, 7, CU_TENSOR_MAP_SWIZZLE_64B);
  fused_kernel<<<NCTA, 384, SMEM_BYTES, cudaStreamPerThread>>>(
      mQKV, mWO, mW1, mW2, (const __nv_bfloat16*)d_in[0], (const __nv_bfloat16*)d_in[2], (const __nv_bfloat16*)d_in[6],
      (const __nv_bfloat16*)d_in[8], (const __nv_bfloat16*)d_in[3], (const __nv_bfloat16*)d_in[5],
      (const __nv_bfloat16*)d_in[7], (__nv_bfloat16*)d_out);
}
```

```cpp
#include <cuda_runtime.h>
#include <cuda_bf16.h>
#include <cuda.h>
#include <stdint.h>

namespace {

constexpr int DM = 448, NCTA = 128;
constexpr int ABYTES = 57344;
constexpr int SLOT = 14336, NSLOT = 7;
constexpr int OFF_RING = 2 * ABYTES;
constexpr int OFF_WPHI = OFF_RING + NSLOT * SLOT;
constexpr int OFF_B1 = OFF_WPHI + 8192;
constexpr int OFF_BAR = OFF_B1 + 896;
constexpr int SMEM_BYTES = OFF_BAR + 256 + 1024;
constexpr int TILES_PER_LAYER = 46;

__device__ __align__(1024) unsigned char gP[16 * 2 * 8 * 8 * 7168];
__device__ __align__(1024) unsigned char gXN[16 * 2 * ABYTES];
__device__ __align__(1024) float4 gKV[2 * 8 * 2 * 5 * 128];
__device__ __align__(128) unsigned gFlag[(4 * 16 * 2 * 5 + 32 + 1) * 32];
#define STAMP(i)

__device__ __forceinline__ uint32_t smem_u32(const void* p) { return (uint32_t)__cvta_generic_to_shared(p); }
__device__ __forceinline__ void mbar_init(uint32_t b, int c) { asm volatile("mbarrier.init.shared::cta.b64 [%0], %1;" ::"r"(b), "r"(c)); }
__device__ __forceinline__ void mbar_expect(uint32_t b, int bytes) { asm volatile("mbarrier.arrive.expect_tx.shared::cta.b64 _, [%0], %1;" ::"r"(b), "r"(bytes) : "memory"); }
__device__ __forceinline__ void mbar_arrive(uint32_t b) { asm volatile("mbarrier.arrive.shared::cta.b64 _, [%0];" ::"r"(b) : "memory"); }
__device__ __forceinline__ void mbar_wait(uint32_t b, int par) {
  uint32_t ok; int n = 0;
  while (true) {
    asm volatile("{.reg .pred p; mbarrier.try_wait.parity.shared::cta.b64 p, [%1], %2; selp.u32 %0,1,0,p;}" : "=r"(ok) : "r"(b), "r"(par) : "memory");
    if (ok) break;
    if (++n > (1 << 22)) break;
  }
}
__device__ __forceinline__ void flag_wait(const unsigned* f, unsigned target) {
  unsigned v; int n = 0;
  while (true) {
    asm volatile("ld.acquire.gpu.global.u32 %0, [%1];" : "=r"(v) : "l"(f) : "memory");
    if ((int)(v - target) >= 0) break;
    if (++n > (1 << 21)) break;
  }
}
__device__ __forceinline__ void flag_arrive(unsigned* f) { asm volatile("red.release.gpu.global.add.u32 [%0], 1;" ::"l"(f) : "memory"); }
__device__ __forceinline__ void fence_async() { asm volatile("fence.proxy.async;" ::: "memory"); }
__device__ __forceinline__ void fence_async_smem() { asm volatile("fence.proxy.async.shared::cta;" ::: "memory"); }
template <int ID, int N> __device__ __forceinline__ void bar_sync() { asm volatile("bar.sync %0, %1;" ::"n"(ID), "n"(N) : "memory"); }
__device__ __forceinline__ void bar_wg(int c) { if (c) bar_sync<2, 128>(); else bar_sync<1, 128>(); }
__device__ __forceinline__ void wg_fence() { asm volatile("wgmma.fence.sync.aligned;" ::: "memory"); }
__device__ __forceinline__ void wg_commit() { asm volatile("wgmma.commit_group.sync.aligned;" ::: "memory"); }
template <int N> __device__ __forceinline__ void wg_wait() { asm volatile("wgmma.wait_group.sync.aligned %0;" ::"n"(N) : "memory"); }
template <int N> __device__ __forceinline__ void reg_fence(float (&d)[N]) {
#pragma unroll
  for (int i = 0; i < N; i++) asm volatile("" : "+f"(d[i])::"memory");
}
__device__ __forceinline__ uint64_t mkdesc(uint32_t addr, uint32_t lbo, uint32_t sbo, uint64_t swz) {
  return (uint64_t)((addr & 0x3FFFF) >> 4) | ((uint64_t)(lbo >> 4) << 16) | ((uint64_t)(sbo >> 4) << 32) | (swz << 62);
}
__device__ __forceinline__ uint32_t pack(float a, float b) {
  uint32_t r; asm("cvt.rn.bf16x2.f32 %0, %1, %2;" : "=r"(r) : "f"(b), "f"(a)); return r;
}
__device__ __forceinline__ float lo(uint32_t u) { return __uint_as_float(u << 16); }
__device__ __forceinline__ float hi(uint32_t u) { return __uint_as_float(u & 0xFFFF0000u); }
__device__ __forceinline__ float ex2(float x) { float y; asm("ex2.approx.ftz.f32 %0, %1;" : "=f"(y) : "f"(x)); return y; }
__device__ __forceinline__ void stsm4(uint32_t a, uint32_t r0, uint32_t r1, uint32_t r2, uint32_t r3) {
  asm volatile("stmatrix.sync.aligned.m8n8.x4.shared.b16 [%0], {%1,%2,%3,%4};" ::"r"(a), "r"(r0), "r"(r1), "r"(r2), "r"(r3) : "memory");
}
__device__ __forceinline__ void tma3(uint32_t dst, const CUtensorMap* m, int c0, int c1, int c2, uint32_t bar) {
  asm volatile("cp.async.bulk.tensor.3d.shared::cluster.global.mbarrier::complete_tx::bytes [%0], [%1, {%3,%4,%5}], [%2];"
               ::"r"(dst), "l"(m), "r"(bar), "r"(c0), "r"(c1), "r"(c2) : "memory");
}
__device__ __forceinline__ void bulk_ld(uint32_t dst, const void* src, int bytes, uint32_t bar) {
  asm volatile("cp.async.bulk.shared::cluster.global.mbarrier::complete_tx::bytes [%0], [%1], %2, [%3];" ::"r"(dst), "l"(src), "r"(bytes), "r"(bar) : "memory");
}
__device__ __forceinline__ uint4 ldcg4(const void* p) {
  uint4 v; asm volatile("ld.global.cg.v4.u32 {%0,%1,%2,%3}, [%4];" : "=r"(v.x), "=r"(v.y), "=r"(v.z), "=r"(v.w) : "l"(p) : "memory"); return v;
}

__device__ __forceinline__ void mma_ss_184(float (&d)[92], uint64_t da, uint64_t db, int acc) {
  asm volatile("{.reg .pred p; setp.ne.b32 p, %94, 0;\n"
    "wgmma.mma_async.sync.aligned.m64n184k16.f32.bf16.bf16 {%0,%1,%2,%3,%4,%5,%6,%7,%8,%9,%10,%11,%12,%13,%14,%15,%16,%17,%18,%19,%20,%21,%22,%23,%24,%25,%26,%27,%28,%29,%30,%31,%32,%33,%34,%35,%36,%37,%38,%39,%40,%41,%42,%43,%44,%45,%46,%47,%48,%49,%50,%51,%52,%53,%54,%55,%56,%57,%58,%59,%60,%61,%62,%63,%64,%65,%66,%67,%68,%69,%70,%71,%72,%73,%74,%75,%76,%77,%78,%79,%80,%81,%82,%83,%84,%85,%86,%87,%88,%89,%90,%91}, %92, %93, p, 1, 1, 0, 1;}\n"
    : "+f"(d[0]),"+f"(d[1]),"+f"(d[2]),"+f"(d[3]),"+f"(d[4]),"+f"(d[5]),"+f"(d[6]),"+f"(d[7]),"+f"(d[8]),"+f"(d[9]),"+f"(d[10]),"+f"(d[11]),"+f"(d[12]),"+f"(d[13]),"+f"(d[14]),"+f"(d[15]),"+f"(d[16]),"+f"(d[17]),"+f"(d[18]),"+f"(d[19]),"+f"(d[20]),"+f"(d[21]),"+f"(d[22]),"+f"(d[23]),"+f"(d[24]),"+f"(d[25]),"+f"(d[26]),"+f"(d[27]),"+f"(d[28]),"+f"(d[29]),"+f"(d[30]),"+f"(d[31]),"+f"(d[32]),"+f"(d[33]),"+f"(d[34]),"+f"(d[35]),"+f"(d[36]),"+f"(d[37]),"+f"(d[38]),"+f"(d[39]),"+f"(d[40]),"+f"(d[41]),"+f"(d[42]),"+f"(d[43]),"+f"(d[44]),"+f"(d[45]),"+f"(d[46]),"+f"(d[47]),"+f"(d[48]),"+f"(d[49]),"+f"(d[50]),"+f"(d[51]),"+f"(d[52]),"+f"(d[53]),"+f"(d[54]),"+f"(d[55]),"+f"(d[56]),"+f"(d[57]),"+f"(d[58]),"+f"(d[59]),"+f"(d[60]),"+f"(d[61]),"+f"(d[62]),"+f"(d[63]),"+f"(d[64]),"+f"(d[65]),"+f"(d[66]),"+f"(d[67]),"+f"(d[68]),"+f"(d[69]),"+f"(d[70]),"+f"(d[71]),"+f"(d[72]),"+f"(d[73]),"+f"(d[74]),"+f"(d[75]),"+f"(d[76]),"+f"(d[77]),"+f"(d[78]),"+f"(d[79]),"+f"(d[80]),"+f"(d[81]),"+f"(d[82]),"+f"(d[83]),"+f"(d[84]),"+f"(d[85]),"+f"(d[86]),"+f"(d[87]),"+f"(d[88]),"+f"(d[89]),"+f"(d[90]),"+f"(d[91])
    : "l"(da), "l"(db), "r"(acc));
}
__device__ __forceinline__ void mma_ss_224(float (&d)[112], uint64_t da, uint64_t db, int acc) {
  asm volatile("{.reg .pred p; setp.ne.b32 p, %114, 0;\n"
    "wgmma.mma_async.sync.aligned.m64n224k16.f32.bf16.bf16 {%0,%1,%2,%3,%4,%5,%6,%7,%8,%9,%10,%11,%12,%13,%14,%15,%16,%17,%18,%19,%20,%21,%22,%23,%24,%25,%26,%27,%28,%29,%30,%31,%32,%33,%34,%35,%36,%37,%38,%39,%40,%41,%42,%43,%44,%45,%46,%47,%48,%49,%50,%51,%52,%53,%54,%55,%56,%57,%58,%59,%60,%61,%62,%63,%64,%65,%66,%67,%68,%69,%70,%71,%72,%73,%74,%75,%76,%77,%78,%79,%80,%81,%82,%83,%84,%85,%86,%87,%88,%89,%90,%91,%92,%93,%94,%95,%96,%97,%98,%99,%100,%101,%102,%103,%104,%105,%106,%107,%108,%109,%110,%111}, %112, %113, p, 1, 1, 0, 1;}\n"
    : "+f"(d[0]),"+f"(d[1]),"+f"(d[2]),"+f"(d[3]),"+f"(d[4]),"+f"(d[5]),"+f"(d[6]),"+f"(d[7]),"+f"(d[8]),"+f"(d[9]),"+f"(d[10]),"+f"(d[11]),"+f"(d[12]),"+f"(d[13]),"+f"(d[14]),"+f"(d[15]),"+f"(d[16]),"+f"(d[17]),"+f"(d[18]),"+f"(d[19]),"+f"(d[20]),"+f"(d[21]),"+f"(d[22]),"+f"(d[23]),"+f"(d[24]),"+f"(d[25]),"+f"(d[26]),"+f"(d[27]),"+f"(d[28]),"+f"(d[29]),"+f"(d[30]),"+f"(d[31]),"+f"(d[32]),"+f"(d[33]),"+f"(d[34]),"+f"(d[35]),"+f"(d[36]),"+f"(d[37]),"+f"(d[38]),"+f"(d[39]),"+f"(d[40]),"+f"(d[41]),"+f"(d[42]),"+f"(d[43]),"+f"(d[44]),"+f"(d[45]),"+f"(d[46]),"+f"(d[47]),"+f"(d[48]),"+f"(d[49]),"+f"(d[50]),"+f"(d[51]),"+f"(d[52]),"+f"(d[53]),"+f"(d[54]),"+f"(d[55]),"+f"(d[56]),"+f"(d[57]),"+f"(d[58]),"+f"(d[59]),"+f"(d[60]),"+f"(d[61]),"+f"(d[62]),"+f"(d[63]),"+f"(d[64]),"+f"(d[65]),"+f"(d[66]),"+f"(d[67]),"+f"(d[68]),"+f"(d[69]),"+f"(d[70]),"+f"(d[71]),"+f"(d[72]),"+f"(d[73]),"+f"(d[74]),"+f"(d[75]),"+f"(d[76]),"+f"(d[77]),"+f"(d[78]),"+f"(d[79]),"+f"(d[80]),"+f"(d[81]),"+f"(d[82]),"+f"(d[83]),"+f"(d[84]),"+f"(d[85]),"+f"(d[86]),"+f"(d[87]),"+f"(d[88]),"+f"(d[89]),"+f"(d[90]),"+f"(d[91]),"+f"(d[92]),"+f"(d[93]),"+f"(d[94]),"+f"(d[95]),"+f"(d[96]),"+f"(d[97]),"+f"(d[98]),"+f"(d[99]),"+f"(d[100]),"+f"(d[101]),"+f"(d[102]),"+f"(d[103]),"+f"(d[104]),"+f"(d[105]),"+f"(d[106]),"+f"(d[107]),"+f"(d[108]),"+f"(d[109]),"+f"(d[110]),"+f"(d[111])
    : "l"(da), "l"(db), "r"(acc));
}
__device__ __forceinline__ void mma_rs_224(float (&d)[112], uint32_t a0, uint32_t a1, uint32_t a2, uint32_t a3, uint64_t db, int acc) {
  asm volatile("{.reg .pred p; setp.ne.b32 p, %117, 0;\n"
    "wgmma.mma_async.sync.aligned.m64n224k16.f32.bf16.bf16 {%0,%1,%2,%3,%4,%5,%6,%7,%8,%9,%10,%11,%12,%13,%14,%15,%16,%17,%18,%19,%20,%21,%22,%23,%24,%25,%26,%27,%28,%29,%30,%31,%32,%33,%34,%35,%36,%37,%38,%39,%40,%41,%42,%43,%44,%45,%46,%47,%48,%49,%50,%51,%52,%53,%54,%55,%56,%57,%58,%59,%60,%61,%62,%63,%64,%65,%66,%67,%68,%69,%70,%71,%72,%73,%74,%75,%76,%77,%78,%79,%80,%81,%82,%83,%84,%85,%86,%87,%88,%89,%90,%91,%92,%93,%94,%95,%96,%97,%98,%99,%100,%101,%102,%103,%104,%105,%106,%107,%108,%109,%110,%111}, {%112,%113,%114,%115}, %116, p, 1, 1, 1;}\n"
    : "+f"(d[0]),"+f"(d[1]),"+f"(d[2]),"+f"(d[3]),"+f"(d[4]),"+f"(d[5]),"+f"(d[6]),"+f"(d[7]),"+f"(d[8]),"+f"(d[9]),"+f"(d[10]),"+f"(d[11]),"+f"(d[12]),"+f"(d[13]),"+f"(d[14]),"+f"(d[15]),"+f"(d[16]),"+f"(d[17]),"+f"(d[18]),"+f"(d[19]),"+f"(d[20]),"+f"(d[21]),"+f"(d[22]),"+f"(d[23]),"+f"(d[24]),"+f"(d[25]),"+f"(d[26]),"+f"(d[27]),"+f"(d[28]),"+f"(d[29]),"+f"(d[30]),"+f"(d[31]),"+f"(d[32]),"+f"(d[33]),"+f"(d[34]),"+f"(d[35]),"+f"(d[36]),"+f"(d[37]),"+f"(d[38]),"+f"(d[39]),"+f"(d[40]),"+f"(d[41]),"+f"(d[42]),"+f"(d[43]),"+f"(d[44]),"+f"(d[45]),"+f"(d[46]),"+f"(d[47]),"+f"(d[48]),"+f"(d[49]),"+f"(d[50]),"+f"(d[51]),"+f"(d[52]),"+f"(d[53]),"+f"(d[54]),"+f"(d[55]),"+f"(d[56]),"+f"(d[57]),"+f"(d[58]),"+f"(d[59]),"+f"(d[60]),"+f"(d[61]),"+f"(d[62]),"+f"(d[63]),"+f"(d[64]),"+f"(d[65]),"+f"(d[66]),"+f"(d[67]),"+f"(d[68]),"+f"(d[69]),"+f"(d[70]),"+f"(d[71]),"+f"(d[72]),"+f"(d[73]),"+f"(d[74]),"+f"(d[75]),"+f"(d[76]),"+f"(d[77]),"+f"(d[78]),"+f"(d[79]),"+f"(d[80]),"+f"(d[81]),"+f"(d[82]),"+f"(d[83]),"+f"(d[84]),"+f"(d[85]),"+f"(d[86]),"+f"(d[87]),"+f"(d[88]),"+f"(d[89]),"+f"(d[90]),"+f"(d[91]),"+f"(d[92]),"+f"(d[93]),"+f"(d[94]),"+f"(d[95]),"+f"(d[96]),"+f"(d[97]),"+f"(d[98]),"+f"(d[99]),"+f"(d[100]),"+f"(d[101]),"+f"(d[102]),"+f"(d[103]),"+f"(d[104]),"+f"(d[105]),"+f"(d[106]),"+f"(d[107]),"+f"(d[108]),"+f"(d[109]),"+f"(d[110]),"+f"(d[111])
    : "r"(a0), "r"(a1), "r"(a2), "r"(a3), "l"(db), "r"(acc));
}
__device__ __forceinline__ void mma_rs_56(float (&d)[28], uint32_t a0, uint32_t a1, uint32_t a2, uint32_t a3, uint64_t db, int acc) {
  asm volatile("{.reg .pred p; setp.ne.b32 p, %33, 0;\n"
    "wgmma.mma_async.sync.aligned.m64n56k16.f32.bf16.bf16 {%0,%1,%2,%3,%4,%5,%6,%7,%8,%9,%10,%11,%12,%13,%14,%15,%16,%17,%18,%19,%20,%21,%22,%23,%24,%25,%26,%27}, {%28,%29,%30,%31}, %32, p, 1, 1, 1;}\n"
    : "+f"(d[0]),"+f"(d[1]),"+f"(d[2]),"+f"(d[3]),"+f"(d[4]),"+f"(d[5]),"+f"(d[6]),"+f"(d[7]),"+f"(d[8]),"+f"(d[9]),"+f"(d[10]),"+f"(d[11]),"+f"(d[12]),"+f"(d[13]),"+f"(d[14]),"+f"(d[15]),"+f"(d[16]),"+f"(d[17]),"+f"(d[18]),"+f"(d[19]),"+f"(d[20]),"+f"(d[21]),"+f"(d[22]),"+f"(d[23]),"+f"(d[24]),"+f"(d[25]),"+f"(d[26]),"+f"(d[27])
    : "r"(a0), "r"(a1), "r"(a2), "r"(a3), "l"(db), "r"(acc));
}
__device__ __forceinline__ void mma_ss_64t(float (&d)[32], uint64_t da, uint64_t db, int acc) {
  asm volatile("{.reg .pred p; setp.ne.b32 p, %34, 0;\n"
    "wgmma.mma_async.sync.aligned.m64n64k16.f32.bf16.bf16 {%0,%1,%2,%3,%4,%5,%6,%7,%8,%9,%10,%11,%12,%13,%14,%15,%16,%17,%18,%19,%20,%21,%22,%23,%24,%25,%26,%27,%28,%29,%30,%31}, %32, %33, p, 1, 1, 1, 1;}\n"
    : "+f"(d[0]),"+f"(d[1]),"+f"(d[2]),"+f"(d[3]),"+f"(d[4]),"+f"(d[5]),"+f"(d[6]),"+f"(d[7]),"+f"(d[8]),"+f"(d[9]),"+f"(d[10]),"+f"(d[11]),"+f"(d[12]),"+f"(d[13]),"+f"(d[14]),"+f"(d[15]),"+f"(d[16]),"+f"(d[17]),"+f"(d[18]),"+f"(d[19]),"+f"(d[20]),"+f"(d[21]),"+f"(d[22]),"+f"(d[23]),"+f"(d[24]),"+f"(d[25]),"+f"(d[26]),"+f"(d[27]),"+f"(d[28]),"+f"(d[29]),"+f"(d[30]),"+f"(d[31])
    : "l"(da), "l"(db), "r"(acc));
}
__device__ __forceinline__ void mma_rs_64(float (&d)[32], uint32_t a0, uint32_t a1, uint32_t a2, uint32_t a3, uint64_t db, int acc) {
  asm volatile("{.reg .pred p; setp.ne.b32 p, %37, 0;\n"
    "wgmma.mma_async.sync.aligned.m64n64k16.f32.bf16.bf16 {%0,%1,%2,%3,%4,%5,%6,%7,%8,%9,%10,%11,%12,%13,%14,%15,%16,%17,%18,%19,%20,%21,%22,%23,%24,%25,%26,%27,%28,%29,%30,%31}, {%32,%33,%34,%35}, %36, p, 1, 1, 1;}\n"
    : "+f"(d[0]),"+f"(d[1]),"+f"(d[2]),"+f"(d[3]),"+f"(d[4]),"+f"(d[5]),"+f"(d[6]),"+f"(d[7]),"+f"(d[8]),"+f"(d[9]),"+f"(d[10]),"+f"(d[11]),"+f"(d[12]),"+f"(d[13]),"+f"(d[14]),"+f"(d[15]),"+f"(d[16]),"+f"(d[17]),"+f"(d[18]),"+f"(d[19]),"+f"(d[20]),"+f"(d[21]),"+f"(d[22]),"+f"(d[23]),"+f"(d[24]),"+f"(d[25]),"+f"(d[26]),"+f"(d[27]),"+f"(d[28]),"+f"(d[29]),"+f"(d[30]),"+f"(d[31])
    : "r"(a0), "r"(a1), "r"(a2), "r"(a3), "l"(db), "r"(acc));
}

__device__ __forceinline__ void dual_softmax(const float (&p)[28], uint32_t (&phi)[4][7]) {
  constexpr float L2E = 1.4426950408889634f;
#pragma unroll
  for (int i = 0; i < 4; i++) {
    float mx = p[i], mn = p[i];
#pragma unroll
    for (int j = 1; j < 7; j++) { mx = fmaxf(mx, p[4 * j + i]); mn = fminf(mn, p[4 * j + i]); }
    mx = fmaxf(mx, __shfl_xor_sync(~0u, mx, 1)); mn = fminf(mn, __shfl_xor_sync(~0u, mn, 1));
    mx = fmaxf(mx, __shfl_xor_sync(~0u, mx, 2)); mn = fminf(mn, __shfl_xor_sync(~0u, mn, 2));
    float a[7], b[7], sa = 0.f, sb = 0.f;
    const float mxl = mx * L2E, mnl = mn * L2E;
#pragma unroll
    for (int j = 0; j < 7; j++) {
      a[j] = ex2(fmaf(p[4 * j + i], L2E, -mxl)); b[j] = ex2(fmaf(p[4 * j + i], -L2E, mnl));
      sa += a[j]; sb += b[j];
    }
    sa += __shfl_xor_sync(~0u, sa, 1); sb += __shfl_xor_sync(~0u, sb, 1);
    sa += __shfl_xor_sync(~0u, sa, 2); sb += __shfl_xor_sync(~0u, sb, 2);
    const float ra = __fdividef(1.f, sa), rb = __fdividef(1.f, sb);
#pragma unroll
    for (int j = 0; j < 7; j++) phi[i][j] = pack(a[j] * ra, b[j] * rb);
  }
}

struct Ring {
  uint32_t full, empty, base; int slot, par;
  __device__ __forceinline__ uint32_t acquire() { mbar_wait(full + slot * 8, par); return base + slot * SLOT; }
  __device__ __forceinline__ int advance() { int s = slot; if (++slot == NSLOT) { slot = 0; par ^= 1; } return s; }
  __device__ __forceinline__ void release(int s, bool elect) { if (elect) mbar_arrive(empty + s * 8); }
};

__device__ __forceinline__ void store_partials(const float (&acc)[112], unsigned char* p0, int nh) {
#pragma unroll
  for (int q = 0; q < 7; q++) {
#pragma unroll
    for (int hh = 0; hh < 2; hh++) {
      uint4 v;
      v.x = pack(acc[16 * q + 2 * hh], acc[16 * q + 2 * hh + 1]);
      v.y = pack(acc[16 * q + 4 + 2 * hh], acc[16 * q + 5 + 2 * hh]);
      v.z = pack(acc[16 * q + 8 + 2 * hh], acc[16 * q + 9 + 2 * hh]);
      v.w = pack(acc[16 * q + 12 + 2 * hh], acc[16 * q + 13 + 2 * hh]);
      *reinterpret_cast<uint4*>(p0 + hh * (8 * 7168) + (nh * 7 + q) * 64) = v;
    }
  }
}

__global__ void __launch_bounds__(384, 1)
fused_kernel(const __grid_constant__ CUtensorMap mQKV, const __grid_constant__ CUtensorMap mWO,
             const __grid_constant__ CUtensorMap mW1, const __grid_constant__ CUtensorMap mW2,
             const __nv_bfloat16* __restrict__ x, const __nv_bfloat16* __restrict__ wphi,
             const __nv_bfloat16* __restrict__ b1, const __nv_bfloat16* __restrict__ b2,
             const __nv_bfloat16* __restrict__ wo, const __nv_bfloat16* __restrict__ w1,
             const __nv_bfloat16* __restrict__ w2, __nv_bfloat16* __restrict__ out) {
  extern __shared__ unsigned char smem_raw[];
  const uint32_t sb = (smem_u32(smem_raw) + 1023) & ~1023u;
  unsigned char* sg = smem_raw + (sb - smem_u32(smem_raw));
  const int tid = threadIdx.x, lane = tid & 31;
  const int G = blockIdx.x >> 3, r = blockIdx.x & 7;
  const uint32_t barFull = sb + OFF_BAR, barEmpty = barFull + 56, barA = barEmpty + 56;
  if (tid == 0) {
    for (int i = 0; i < NSLOT; i++) { mbar_init(barFull + i * 8, 1); mbar_init(barEmpty + i * 8, 2); }
    for (int i = 0; i < 14; i++) mbar_init(barA + i * 8, 1);
    asm volatile("fence.mbarrier_init.release.cluster;" ::: "memory");
  }
  __syncthreads();
  unsigned* const fDone = gFlag + (640 + 32) * 32;

  const int wgid = __shfl_sync(~0u, tid >> 7, 0);
  if (wgid == 2) {
    asm volatile("setmaxnreg.dec.sync.aligned.u32 24;");
    if (tid == 256) {
      int slot = 0, par = 1;
      for (int it = 0; it < 2 * TILES_PER_LAYER; it++) {
        const int i = it >= TILES_PER_LAYER ? it - TILES_PER_LAYER : it;
        mbar_wait(barEmpty + slot * 8, par);
        const uint32_t dst = sb + OFF_RING + slot * SLOT, fb = barFull + slot * 8;
        if (i < 14) { mbar_expect(fb, 12288); tma3(dst, &mQKV, 56 * r, 32 * i, 0, fb); }
        else if (i < 18) { mbar_expect(fb, SLOT); tma3(dst, &mWO, 0, 56 * r + 32 * ((i - 14) & 1), 7 * ((i - 14) >> 1), fb); }
        else if (i < 32) { mbar_expect(fb, SLOT); tma3(dst, &mW1, 0, 32 * (i - 18), 7 * r, fb); }
        else { const int j = i - 32, nh = j >= 7; mbar_expect(fb, SLOT); tma3(dst, &mW2, 0, 224 * r + 32 * (j - 7 * nh), 7 * nh, fb); }
        if (++slot == NSLOT) { slot = 0; par ^= 1; }
      }
    } else if (tid > 288 && tid <= 291) {
      const char* src = lane == 1 ? (const char*)wo + blockIdx.x * 3136 : (lane == 2 ? (const char*)w1 : (const char*)w2) + blockIdx.x * 12544;
      asm volatile("cp.async.bulk.prefetch.L2.global [%0], %1;" ::"l"(src), "r"(lane == 1 ? 3136 : 12544) : "memory");
    }
  } else {
  asm volatile("setmaxnreg.inc.sync.aligned.u32 240;");
  const int c = wgid, w = (tid >> 5) & 3, g = lane >> 2, t = lane & 3;
  const bool elect = (tid & 127) == 0;
  const uint32_t abuf = sb + c * ABYTES;
  unsigned epoch;
  asm volatile("ld.relaxed.gpu.global.u32 %0, [%1];" : "=r"(epoch) : "l"(fDone) : "memory");

  uint32_t xr[2][2][4];
  const int orow = G * 128 + c * 64 + r * 8 + w * 2;
  {
    uint4 v[4][7];
    const int u = lane & 7;
#pragma unroll
    for (int i = 0; i < 4; i++) {
      const uint4* src = reinterpret_cast<const uint4*>(x + (size_t)(G * 128 + c * 64 + w * 16 + i * 4 + (lane >> 3)) * DM) + u;
#pragma unroll
      for (int k = 0; k < 7; k++) v[i][k] = __ldg(src + k * 8);
    }
#pragma unroll
    for (int rr = 0; rr < 2; rr++)
#pragma unroll
      for (int m = 0; m < 2; m++)
#pragma unroll
        for (int jj = 0; jj < 4; jj++)
          xr[rr][m][jj] = lane < 28 ? __ldg(reinterpret_cast<const uint32_t*>(x + (size_t)(orow + rr) * DM + (g + 7 * m) * 32 + jj * 8 + 2 * t)) : 0u;
    uint32_t wv[8];
#pragma unroll
    for (int i = 0; i < 8; i++) {
      const int k = i * 8 + (tid >> 5), e = k >= 28;
      wv[i] = (k < 56 && lane < 28) ? (uint32_t)__ldg(reinterpret_cast<const unsigned short*>(wphi) + (2 * r + e) * 784 + (k - 28 * e) * 28 + lane) << (16 * e) : 0u;
    }
#pragma unroll
    for (int i = 0; i < 8; i++) {
      const int k = i * 8 + (tid >> 5);
      *reinterpret_cast<uint32_t*>(sg + OFF_WPHI + k * 128 + ((g ^ (k & 7)) << 4) + t * 4) = wv[i];
    }
    if (tid < 224) reinterpret_cast<float*>(sg + OFF_B1)[tid] = __bfloat162float(b1[224 * r + tid]);
    if (G == 0) {
      for (int i = tid; i < 2 * 1280; i += 256) gKV[((i >= 1280) * 8 + r) * 1280 + (i >= 1280 ? i - 1280 : i)] = make_float4(0.f, 0.f, 0.f, 0.f);
    }
#pragma unroll
    for (int i = 0; i < 4; i++) {
      float s = 0.f;
#pragma unroll
      for (int k = 0; k < 7; k++) s += (lo(v[i][k].x) + hi(v[i][k].x)) + (lo(v[i][k].y) + hi(v[i][k].y)) + (lo(v[i][k].z) + hi(v[i][k].z)) + (lo(v[i][k].w) + hi(v[i][k].w));
      s += __shfl_xor_sync(~0u, s, 1); s += __shfl_xor_sync(~0u, s, 2); s += __shfl_xor_sync(~0u, s, 4);
      const float mean = s * (1.f / DM);
      float q = 0.f;
#pragma unroll
      for (int k = 0; k < 7; k++) {
        const uint32_t e[4] = {v[i][k].x, v[i][k].y, v[i][k].z, v[i][k].w};
#pragma unroll
        for (int z = 0; z < 4; z++) { float a = lo(e[z]) - mean, b = hi(e[z]) - mean; q = fmaf(a, a, q); q = fmaf(b, b, q); }
      }
      q += __shfl_xor_sync(~0u, q, 1); q += __shfl_xor_sync(~0u, q, 2); q += __shfl_xor_sync(~0u, q, 4);
      const float rs = rsqrtf(q * (1.f / DM) + 1e-5f), mb = -mean * rs;
      const int row = w * 16 + i * 4 + (lane >> 3);
#pragma unroll
      for (int k = 0; k < 7; k++) {
        uint4 o;
        o.x = pack(fmaf(lo(v[i][k].x), rs, mb), fmaf(hi(v[i][k].x), rs, mb));
        o.y = pack(fmaf(lo(v[i][k].y), rs, mb), fmaf(hi(v[i][k].y), rs, mb));
        o.z = pack(fmaf(lo(v[i][k].z), rs, mb), fmaf(hi(v[i][k].z), rs, mb));
        o.w = pack(fmaf(lo(v[i][k].w), rs, mb), fmaf(hi(v[i][k].w), rs, mb));
        *reinterpret_cast<uint4*>(sg + c * ABYTES + k * 8192 + row * 128 + ((u ^ (row & 7)) << 4)) = o;
      }
    }
    fence_async_smem();
    bar_sync<3, 256>();
    epoch = epoch / NCTA + 1;
    if (G == 0 && tid == 0) flag_arrive(gFlag + (640 + 16 + r) * 32);
  }
  STAMP(0);
  Ring ring{barFull, barEmpty, sb + OFF_RING, 0, 0};
  unsigned char* const pdst = gP + (size_t)(((G * 2 + c) * 8 + 2 * w) * 8 + r) * 7168 + (g * 56 + t) * 16;
  const unsigned char* const psrc = gP + (size_t)(((G * 2 + c) * 8 + r) * 8) * 7168 + (w * 2 * 56 + lane) * 16;
  unsigned char* const xn_img = gXN + (size_t)(G * 2 + c) * ABYTES;
  const uint32_t stsm_row = w * 16 + ((lane >> 3) & 1) * 8 + (lane & 7);
  const uint32_t stsm_hi = lane >> 4;

  auto exchange = [&](const int xi) {
    unsigned* fl = gFlag + ((xi * 16 + G) * 2 + c) * 5 * 32;
    __syncwarp();
    if (xi == 2) STAMP(24);
    if (lane == 0) { flag_arrive(fl + w * 32); if (xi == 2) STAMP(25); flag_wait(fl + (r >> 1) * 32, epoch * 8); }
    __syncwarp();
    STAMP(4 + (xi >> 1) * 12 + (xi & 1) * 5);
    float y[2][2][8];
#pragma unroll
    for (int m = 0; m < 2; m++)
#pragma unroll
      for (int jj = 0; jj < 4; jj++) {
        uint32_t bb = 0;
        if ((xi & 1) && lane < 28) bb = __ldg(reinterpret_cast<const uint32_t*>(b2 + (g + 7 * m) * 32 + jj * 8 + 2 * t));
#pragma unroll
        for (int rr = 0; rr < 2; rr++) { y[rr][m][2 * jj] = lo(bb) + lo(xr[rr][m][jj]); y[rr][m][2 * jj + 1] = hi(bb) + hi(xr[rr][m][jj]); }
      }
    if (lane < 28) {
      uint4 pv[8][4];
#pragma unroll
      for (int s = 0; s < 8; s++)
#pragma unroll
        for (int i = 0; i < 4; i++) pv[s][i] = ldcg4(psrc + s * 7168 + i * 448);
#pragma unroll
      for (int s = 0; s < 8; s++)
#pragma unroll
        for (int i = 0; i < 4; i++) {
          float* yy = y[i >> 1][i & 1];
          yy[0] += lo(pv[s][i].x); yy[1] += hi(pv[s][i].x); yy[2] += lo(pv[s][i].y); yy[3] += hi(pv[s][i].y);
          yy[4] += lo(pv[s][i].z); yy[5] += hi(pv[s][i].z); yy[6] += lo(pv[s][i].w); yy[7] += hi(pv[s][i].w);
        }
    }
#pragma unroll
    for (int rr = 0; rr < 2; rr++)
#pragma unroll
      for (int m = 0; m < 2; m++)
#pragma unroll
        for (int jj = 0; jj < 4; jj++) xr[rr][m][jj] = pack(y[rr][m][2 * jj], y[rr][m][2 * jj + 1]);
    if (xi == 2) STAMP(26);
    if (xi == 3) {
      if (lane < 28) {
#pragma unroll
        for (int rr = 0; rr < 2; rr++)
#pragma unroll
          for (int m = 0; m < 2; m++)
#pragma unroll
            for (int jj = 0; jj < 4; jj++)
              *reinterpret_cast<uint32_t*>(out + (size_t)(orow + rr) * DM + (g + 7 * m) * 32 + jj * 8 + 2 * t) = xr[rr][m][jj];
      }
      return;
    }
    float s0 = 0.f, s1 = 0.f;
#pragma unroll
    for (int m = 0; m < 2; m++)
#pragma unroll
      for (int jj = 0; jj < 4; jj++) { s0 += lo(xr[0][m][jj]) + hi(xr[0][m][jj]); s1 += lo(xr[1][m][jj]) + hi(xr[1][m][jj]); }
#pragma unroll
    for (int o = 16; o; o >>= 1) { s0 += __shfl_xor_sync(~0u, s0, o); s1 += __shfl_xor_sync(~0u, s1, o); }
    const float mean[2] = {s0 * (1.f / DM), s1 * (1.f / DM)};
    float q[2] = {0.f, 0.f};
    if (lane < 28) {
#pragma unroll
      for (int rr = 0; rr < 2; rr++)
#pragma unroll
        for (int m = 0; m < 2; m++)
#pragma unroll
          for (int jj = 0; jj < 4; jj++) { float a = lo(xr[rr][m][jj]) - mean[rr], b = hi(xr[rr][m][jj]) - mean[rr]; q[rr] = fmaf(a, a, q[rr]); q[rr] = fmaf(b, b, q[rr]); }
    }
#pragma unroll
    for (int o = 16; o; o >>= 1) { q[0] += __shfl_xor_sync(~0u, q[0], o); q[1] += __shfl_xor_sync(~0u, q[1], o); }
    if (lane < 28) {
#pragma unroll
      for (int rr = 0; rr < 2; rr++) {
        const float rs = rsqrtf(q[rr] * (1.f / DM) + 1e-5f), mb = -mean[rr] * rs;
        const int row = r * 8 + w * 2 + rr;
#pragma unroll
        for (int m = 0; m < 2; m++) {
          const int unit = g + 7 * m;
#pragma unroll
          for (int jj = 0; jj < 4; jj++)
            *reinterpret_cast<uint32_t*>(xn_img + (unit >> 1) * 8192 + row * 128 + ((((unit & 1) * 4 + jj) ^ (row & 7)) << 4) + t * 4) =
                pack(fmaf(lo(xr[rr][m][jj]), rs, mb), fmaf(hi(xr[rr][m][jj]), rs, mb));
        }
      }
    }
    if (xi == 2) STAMP(27);
    __syncwarp();
    if (lane == 0) flag_arrive(fl + 4 * 32);
    STAMP(5 + (xi >> 1) * 12 + (xi & 1) * 5);
    if (elect) {
      flag_wait(fl + 4 * 32, epoch * 32);
      fence_async();
#pragma unroll
      for (int k = 0; k < 7; k++) { mbar_expect(barA + (c * 7 + k) * 8, 8192); bulk_ld(abuf + k * 8192, xn_img + k * 8192, 8192, barA + (c * 7 + k) * 8); }
    }
    __syncwarp();
    STAMP(6 + (xi >> 1) * 12 + (xi & 1) * 5);
  };

#pragma unroll 1
  for (int layer = 0; layer < 2; layer++) {
    uint32_t phiq[4][7];
    {
      float acc[92];
      int prev = -1;
#pragma unroll
      for (int st = 0; st < 14; st++) {
        if (layer == 1 && !(st & 1)) mbar_wait(barA + (c * 7 + (st >> 1)) * 8, 1);
        const uint32_t bs = ring.acquire();
        wg_fence();
#pragma unroll
        for (int s = 0; s < 2; s++)
          mma_ss_184(acc, mkdesc(abuf + (st >> 1) * 8192 + (st & 1) * 64 + s * 32, 16, 1024, 1), mkdesc(bs + s * 2048, 4096, 1024, 1), st + s);
        wg_commit();
        if (st > 0) { wg_wait<1>(); ring.release(prev, elect); }
        prev = ring.advance();
      }
      wg_wait<0>(); reg_fence(acc);
      ring.release(prev, elect);
      STAMP(1 + layer * 12);
      float pk[28], pq[28];
      const uint32_t wp = sb + OFF_WPHI;
      uint32_t qf[14], kf[14];
#pragma unroll
      for (int i = 0; i < 14; i++) { qf[i] = pack(acc[2 * i], acc[2 * i + 1]); kf[i] = pack(acc[32 + 2 * i], acc[33 + 2 * i]); }
      wg_fence();
#pragma unroll
      for (int s = 0; s < 4; s++)
        mma_rs_56(pk, kf[4 * s], kf[4 * s + 1], s < 3 ? kf[(4 * s + 2) % 14] : 0u, s < 3 ? kf[(4 * s + 3) % 14] : 0u, mkdesc(wp + s * 2048, 4096, 1024, 1), s);
      wg_commit();
#pragma unroll
      for (int s = 0; s < 4; s++)
        mma_rs_56(pq, qf[4 * s], qf[4 * s + 1], s < 3 ? qf[(4 * s + 2) % 14] : 0u, s < 3 ? qf[(4 * s + 3) % 14] : 0u, mkdesc(wp + s * 2048, 4096, 1024, 1), s);
      wg_commit();
      bar_wg(c);
      const uint32_t srow = abuf + stsm_row * 128;
#pragma unroll
      for (int jp = 0; jp < 4; jp++) {
        const int b = 64 + 8 * jp;
        const uint32_t ones = t == 0 ? 0x3F803F80u : 0u;
        stsm4(srow + 16384 + (((2 * jp + stsm_hi) ^ (lane & 7)) << 4), pack(acc[b], acc[b + 1]), pack(acc[b + 2], acc[b + 3]),
              jp < 3 ? pack(acc[(b + 4) % 92], acc[(b + 5) % 92]) : ones, jp < 3 ? pack(acc[(b + 6) % 92], acc[(b + 7) % 92]) : ones);
      }
      wg_wait<1>(); reg_fence(pk);
      uint32_t phik[4][7];
      dual_softmax(pk, phik);
#pragma unroll
      for (int e = 0; e < 2; e++)
#pragma unroll
        for (int jp = 0; jp < 4; jp++)
          stsm4(srow + e * 8192 + (((2 * jp + stsm_hi) ^ (lane & 7)) << 4), phik[e][2 * jp], phik[2 + e][2 * jp],
                jp < 3 ? phik[e][(2 * jp + 1) % 7] : 0u, jp < 3 ? phik[2 + e][(2 * jp + 1) % 7] : 0u);
      fence_async_smem();
      bar_sync<3, 256>();
      float kv[32];
      wg_fence();
#pragma unroll
      for (int s = 0; s < 8; s++) {
        const uint32_t o = sb + (s >> 2) * ABYTES + (s & 3) * 2048;
        mma_ss_64t(kv, mkdesc(o + c * 8192, 4096, 1024, 1), mkdesc(o + 16384, 4096, 1024, 1), s);
      }
      wg_commit();
      if (layer == 0 && lane == 0) flag_wait(gFlag + (640 + 16 + r) * 32, epoch);
      __syncwarp();
      wg_wait<0>(); reg_fence(kv); reg_fence(pq);
      float4* kvg = gKV + ((layer * 8 + r) * 2 + c) * 640 + (tid & 127);
#pragma unroll
      for (int i = 0; i < 5; i++) {
        float v0, v1, v2, v3;
        if (i == 4) { v0 = kv[28]; v1 = kv[29]; v2 = kv[30]; v3 = kv[31]; }
        else { v0 = c ? kv[12 + 4 * i] : kv[4 * i]; v1 = c ? kv[13 + 4 * i] : kv[1 + 4 * i]; v2 = c ? kv[14 + 4 * i] : kv[2 + 4 * i]; v3 = c ? kv[15 + 4 * i] : kv[3 + 4 * i]; }
        asm volatile("red.relaxed.gpu.global.add.v4.f32 [%0], {%1,%2,%3,%4};" ::"l"(kvg + i * 128), "f"(v0), "f"(v1), "f"(v2), "f"(v3) : "memory");
      }
      __syncwarp();
      if (layer == 1) STAMP(28);
      if (lane == 0) flag_arrive(gFlag + (640 + layer * 8 + r) * 32);
      STAMP(2 + layer * 12);
      dual_softmax(pq, phiq);
    }
    {
      if (lane == 0) flag_wait(gFlag + (640 + layer * 8 + r) * 32, epoch * 128);
      __syncwarp();
      STAMP(3 + layer * 12);
      const float4* kvg = gKV + (layer * 8 + r) * 1280 + (tid & 127);
      uint4 kk[2][5];
#pragma unroll
      for (int e = 0; e < 2; e++)
#pragma unroll
        for (int i = 0; i < 5; i++) kk[e][i] = ldcg4(kvg + e * 640 + i * 128);
      const uint32_t srow = abuf + 24576 + stsm_row * 128;
#pragma unroll
      for (int e = 0; e < 2; e++) {
        uint32_t f[8][2];
#pragma unroll
        for (int j = 0; j < 8; j++) { f[j][0] = 0u; f[j][1] = 0u; }
#pragma unroll
        for (int i = 0; i < 4; i++) {
          const int j = i + 3 * e;
          const bool keep = j != 3 || (e ? t >= 2 : t < 2);
          f[j][0] = keep ? pack(__uint_as_float(kk[e][i].x), __uint_as_float(kk[e][i].y)) : 0u;
          f[j][1] = keep ? pack(__uint_as_float(kk[e][i].z), __uint_as_float(kk[e][i].w)) : 0u;
        }
        if (t == 0) {
          f[7][0] = e ? pack(0.f, __uint_as_float(kk[e][4].y)) : pack(__uint_as_float(kk[e][4].x), 0.f);
          f[7][1] = e ? pack(0.f, __uint_as_float(kk[e][4].w)) : pack(__uint_as_float(kk[e][4].z), 0.f);
        }
#pragma unroll
        for (int jp = 0; jp < 4; jp++)
          stsm4(srow + e * 8192 + (((2 * jp + stsm_hi) ^ (lane & 7)) << 4), f[2 * jp][0], f[2 * jp][1], f[2 * jp + 1][0], f[2 * jp + 1][1]);
      }
      fence_async_smem();
      bar_wg(c);
      float num[32];
      wg_fence();
#pragma unroll
      for (int e = 0; e < 2; e++)
#pragma unroll
        for (int s = 0; s < 4; s++)
          mma_rs_64(num, phiq[e][2 * s], phiq[2 + e][2 * s], s < 3 ? phiq[e][(2 * s + 1) % 7] : 0u, s < 3 ? phiq[2 + e][(2 * s + 1) % 7] : 0u,
                    mkdesc(abuf + 24576 + e * 8192 + s * 2048, 4096, 1024, 1), e + s);
      wg_commit();
      wg_wait<0>(); reg_fence(num);
      if (layer == 1) STAMP(29);
      float rd[4];
#pragma unroll
      for (int i = 0; i < 4; i++) rd[i] = __fdividef(1.f, __shfl_sync(~0u, num[28 + i], lane & ~3) + 1e-6f);
      uint32_t of[7][2];
#pragma unroll
      for (int j = 0; j < 7; j++) {
        const bool hb = j > 3 || (j == 3 && t >= 2);
        const float r0 = hb ? rd[1] : rd[0], r1 = hb ? rd[3] : rd[2];
        of[j][0] = pack(num[4 * j] * r0, num[4 * j + 1] * r0);
        of[j][1] = pack(num[4 * j + 2] * r1, num[4 * j + 3] * r1);
      }
#pragma unroll
      for (int nh = 0; nh < 2; nh++) {
        float acc[112];
        int sl[2];
#pragma unroll
        for (int st = 0; st < 2; st++) {
          const uint32_t bs = ring.acquire();
          wg_fence();
#pragma unroll
          for (int s = 0; s < 2; s++) {
            const int ks = st * 2 + s;
            mma_rs_224(acc, of[2 * ks][0], of[2 * ks][1], ks < 3 ? of[(2 * ks + 1) % 7][0] : 0u, ks < 3 ? of[(2 * ks + 1) % 7][1] : 0u,
                       mkdesc(bs + s * 1024, 2048, 512, 2), ks);
          }
          wg_commit();
          sl[st] = ring.advance();
        }
        wg_wait<0>(); reg_fence(acc);
        ring.release(sl[0], elect); ring.release(sl[1], elect);
        store_partials(acc, pdst, nh);
      }
    }
    exchange(layer * 2);
    {
      uint32_t hf[28][2];
      {
        float acc[112];
        int prev = -1;
#pragma unroll
        for (int st = 0; st < 14; st++) {
          if (!(st & 1)) mbar_wait(barA + (c * 7 + (st >> 1)) * 8, 0);
          const uint32_t bs = ring.acquire();
          wg_fence();
#pragma unroll
          for (int s = 0; s < 2; s++)
            mma_ss_224(acc, mkdesc(abuf + (st >> 1) * 8192 + (st & 1) * 64 + s * 32, 16, 1024, 1), mkdesc(bs + s * 1024, 2048, 512, 2), st + s);
          wg_commit();
          if (st > 0) { wg_wait<1>(); ring.release(prev, elect); }
          prev = ring.advance();
        }
        wg_wait<0>(); reg_fence(acc);
        ring.release(prev, elect);
        STAMP(7 + layer * 12);
        const float2* bs = reinterpret_cast<const float2*>(sg + OFF_B1) + t;
#pragma unroll
        for (int j = 0; j < 28; j++) {
          const float2 b = bs[4 * j];
          const float h0 = fmaxf(acc[4 * j] + b.x, 0.f), h1 = fmaxf(acc[4 * j + 1] + b.y, 0.f);
          const float h2 = fmaxf(acc[4 * j + 2] + b.x, 0.f), h3 = fmaxf(acc[4 * j + 3] + b.y, 0.f);
          hf[j][0] = pack(h0 * h0, h1 * h1); hf[j][1] = pack(h2 * h2, h3 * h3);
        }
      }
#pragma unroll
      for (int nh = 0; nh < 2; nh++) {
        float acc[112];
        int prev = -1;
#pragma unroll
        for (int st = 0; st < 7; st++) {
          const uint32_t bs = ring.acquire();
          wg_fence();
#pragma unroll
          for (int s = 0; s < 2; s++) {
            const int ks = st * 2 + s;
            mma_rs_224(acc, hf[2 * ks][0], hf[2 * ks][1], hf[2 * ks + 1][0], hf[2 * ks + 1][1], mkdesc(bs + s * 1024, 2048, 512, 2), ks);
          }
          wg_commit();
          if (st > 0) { wg_wait<1>(); ring.release(prev, elect); }
          prev = ring.advance();
        }
        wg_wait<0>(); reg_fence(acc);
        ring.release(prev, elect);
        store_partials(acc, pdst, nh);
      }
      STAMP(8 + layer * 12);
    }
    exchange(layer * 2 + 1);
  }
  STAMP(30);
  if (tid == 0) asm volatile("red.relaxed.gpu.global.add.u32 [%0], 1;" ::"l"(fDone) : "memory");
  }
}

typedef CUresult (*EncFn)(CUtensorMap*, CUtensorMapDataType, cuuint32_t, void*, const cuuint64_t*, const cuuint64_t*,
                          const cuuint32_t*, const cuuint32_t*, CUtensorMapInterleave, CUtensorMapSwizzle,
                          CUtensorMapL2promotion, CUtensorMapFloatOOBfill);

void make_map(EncFn enc, CUtensorMap* m, void* p, uint64_t d0, uint64_t d1, uint64_t d2, uint64_t s1, uint64_t s2,
              uint32_t b0, uint32_t b1, uint32_t b2, CUtensorMapSwizzle sw) {
  cuuint64_t dims[3] = {d0, d1, d2}, strides[2] = {s1, s2};
  cuuint32_t box[3] = {b0, b1, b2}, es[3] = {1, 1, 1};
  enc(m, CU_TENSOR_MAP_DATA_TYPE_BFLOAT16, 3, p, dims, strides, box, es, CU_TENSOR_MAP_INTERLEAVE_NONE, sw,
      CU_TENSOR_MAP_L2_PROMOTION_L2_256B, CU_TENSOR_MAP_FLOAT_OOB_FILL_NONE);
}

}

extern "C" void kernel_launch(void* const* d_in, const int* in_sizes, int n_in, void* d_out, int out_size) {
  static EncFn enc = nullptr;
  if (!enc) {
    cudaDriverEntryPointQueryResult st;
    void* fn = nullptr;
    cudaGetDriverEntryPoint("cuTensorMapEncodeTiled", &fn, cudaEnableDefault, &st);
    enc = (EncFn)fn;
    cudaFuncSetAttribute(fused_kernel, cudaFuncAttributeMaxDynamicSharedMemorySize, SMEM_BYTES);
  }
  CUtensorMap mQKV, mWO, mW1, mW2;
  make_map(enc, &mQKV, d_in[1], 448, 448, 3, 2688, 896, 64, 32, 3, CU_TENSOR_MAP_SWIZZLE_128B);
  make_map(enc, &mWO, d_in[3], 32, 448, 14, 896, 64, 32, 32, 7, CU_TENSOR_MAP_SWIZZLE_64B);
  make_map(enc, &mW1, d_in[5], 32, 448, 56, 3584, 64, 32, 32, 7, CU_TENSOR_MAP_SWIZZLE_64B);
  make_map(enc, &mW2, d_in[7], 32, 1792, 14, 896, 64, 32, 32, 7, CU_TENSOR_MAP_SWIZZLE_64B);
  fused_kernel<<<NCTA, 384, SMEM_BYTES, cudaStreamPerThread>>>(
      mQKV, mWO, mW1, mW2, (const __nv_bfloat16*)d_in[0], (const __nv_bfloat16*)d_in[2], (const __nv_bfloat16*)d_in[6],
      (const __nv_bfloat16*)d_in[8], (const __nv_bfloat16*)d_in[3], (const __nv_bfloat16*)d_in[5],
      (const __nv_bfloat16*)d_in[7], (__nv_bfloat16*)d_out);
}
```

```cpp
#include <cuda_runtime.h>
#include <cuda_bf16.h>
#include <cuda.h>
#include <stdint.h>

namespace {

constexpr int DM = 448, NCTA = 128;
constexpr int ABYTES = 57344;
constexpr int SLOT = 14336, NSLOT = 7;
constexpr int OFF_RING = 2 * ABYTES;
constexpr int OFF_WPHI = OFF_RING + NSLOT * SLOT;
constexpr int OFF_B1 = OFF_WPHI + 8192;
constexpr int OFF_CS = OFF_B1 + 896;
constexpr int OFF_BAR = OFF_CS + 1664;
constexpr int SMEM_BYTES = OFF_BAR + 256 + 1024;
constexpr int TILES_PER_LAYER = 46;

__device__ __align__(1024) unsigned char gP[16 * 2 * 8 * 8 * 7168];
__device__ __align__(1024) unsigned char gImg[3 * 32 * ABYTES];
__device__ __align__(1024) float2 gStat[2 * 2048 * 8];
__device__ __align__(1024) float4 gKV[2 * 8 * 2 * 5 * 128];
__device__ __align__(128) unsigned gFlag[(2 * 32 * 7 + 32 + 1) * 32];
#define STAMP(i)

__device__ __forceinline__ uint32_t smem_u32(const void* p) { return (uint32_t)__cvta_generic_to_shared(p); }
__device__ __forceinline__ void mbar_init(uint32_t b, int c) { asm volatile("mbarrier.init.shared::cta.b64 [%0], %1;" ::"r"(b), "r"(c)); }
__device__ __forceinline__ void mbar_expect(uint32_t b, int bytes) { asm volatile("mbarrier.arrive.expect_tx.shared::cta.b64 _, [%0], %1;" ::"r"(b), "r"(bytes) : "memory"); }
__device__ __forceinline__ void mbar_arrive(uint32_t b) { asm volatile("mbarrier.arrive.shared::cta.b64 _, [%0];" ::"r"(b) : "memory"); }
__device__ __forceinline__ void mbar_wait(uint32_t b, int par) {
  uint32_t ok; int n = 0;
  while (true) {
    asm volatile("{.reg .pred p; mbarrier.try_wait.parity.shared::cta.b64 p, [%1], %2; selp.u32 %0,1,0,p;}" : "=r"(ok) : "r"(b), "r"(par) : "memory");
    if (ok) break;
    if (++n > (1 << 22)) break;
  }
}
__device__ __forceinline__ void flag_wait(const unsigned* f, unsigned target) {
  unsigned v; int n = 0;
  while (true) {
    asm volatile("ld.acquire.gpu.global.u32 %0, [%1];" : "=r"(v) : "l"(f) : "memory");
    if ((int)(v - target) >= 0) break;
    if (++n > (1 << 21)) break;
  }
}
__device__ __forceinline__ void flag_arrive(unsigned* f) { asm volatile("red.release.gpu.global.add.u32 [%0], 1;" ::"l"(f) : "memory"); }
__device__ __forceinline__ void fence_async() { asm volatile("fence.proxy.async;" ::: "memory"); }
__device__ __forceinline__ void fence_async_smem() { asm volatile("fence.proxy.async.shared::cta;" ::: "memory"); }
template <int ID, int N> __device__ __forceinline__ void bar_sync() { asm volatile("bar.sync %0, %1;" ::"n"(ID), "n"(N) : "memory"); }
__device__ __forceinline__ void bar_wg(int c) { if (c) bar_sync<2, 128>(); else bar_sync<1, 128>(); }
__device__ __forceinline__ void wg_fence() { asm volatile("wgmma.fence.sync.aligned;" ::: "memory"); }
__device__ __forceinline__ void wg_commit() { asm volatile("wgmma.commit_group.sync.aligned;" ::: "memory"); }
template <int N> __device__ __forceinline__ void wg_wait() { asm volatile("wgmma.wait_group.sync.aligned %0;" ::"n"(N) : "memory"); }
template <int N> __device__ __forceinline__ void reg_fence(float (&d)[N]) {
#pragma unroll
  for (int i = 0; i < N; i++) asm volatile("" : "+f"(d[i])::"memory");
}
template <int N> __device__ __forceinline__ void reg_def(float (&d)[N]) {
#pragma unroll
  for (int i = 0; i < N; i++) d[i] = 0.f;
}
__device__ __forceinline__ uint64_t mkdesc(uint32_t addr, uint32_t lbo, uint32_t sbo, uint64_t swz) {
  return (uint64_t)((addr & 0x3FFFF) >> 4) | ((uint64_t)(lbo >> 4) << 16) | ((uint64_t)(sbo >> 4) << 32) | (swz << 62);
}
__device__ __forceinline__ uint32_t pack(float a, float b) {
  uint32_t r; asm("cvt.rn.bf16x2.f32 %0, %1, %2;" : "=r"(r) : "f"(b), "f"(a)); return r;
}
__device__ __forceinline__ float lo(uint32_t u) { return __uint_as_float(u << 16); }
__device__ __forceinline__ float hi(uint32_t u) { return __uint_as_float(u & 0xFFFF0000u); }
__device__ __forceinline__ float ex2(float x) { float y; asm("ex2.approx.ftz.f32 %0, %1;" : "=f"(y) : "f"(x)); return y; }
__device__ __forceinline__ void stsm4(uint32_t a, uint32_t r0, uint32_t r1, uint32_t r2, uint32_t r3) {
  asm volatile("stmatrix.sync.aligned.m8n8.x4.shared.b16 [%0], {%1,%2,%3,%4};" ::"r"(a), "r"(r0), "r"(r1), "r"(r2), "r"(r3) : "memory");
}
__device__ __forceinline__ void tma3(uint32_t dst, const CUtensorMap* m, int c0, int c1, int c2, uint32_t bar) {
  asm volatile("cp.async.bulk.tensor.3d.shared::cluster.global.mbarrier::complete_tx::bytes [%0], [%1, {%3,%4,%5}], [%2];"
               ::"r"(dst), "l"(m), "r"(bar), "r"(c0), "r"(c1), "r"(c2) : "memory");
}
__device__ __forceinline__ void tma2(uint32_t dst, const CUtensorMap* m, int c0, int c1, uint32_t bar) {
  asm volatile("cp.async.bulk.tensor.2d.shared::cluster.global.mbarrier::complete_tx::bytes [%0], [%1, {%3,%4}], [%2];"
               ::"r"(dst), "l"(m), "r"(bar), "r"(c0), "r"(c1) : "memory");
}
__device__ __forceinline__ uint32_t lds32(uint32_t a) { uint32_t v; asm volatile("ld.shared.u32 %0, [%1];" : "=r"(v) : "r"(a) : "memory"); return v; }
__device__ __forceinline__ void bulk_ld(uint32_t dst, const void* src, int bytes, uint32_t bar) {
  asm volatile("cp.async.bulk.shared::cluster.global.mbarrier::complete_tx::bytes [%0], [%1], %2, [%3];" ::"r"(dst), "l"(src), "r"(bytes), "r"(bar) : "memory");
}
__device__ __forceinline__ uint4 ldcg4(const void* p) {
  uint4 v; asm volatile("ld.global.cg.v4.u32 {%0,%1,%2,%3}, [%4];" : "=r"(v.x), "=r"(v.y), "=r"(v.z), "=r"(v.w) : "l"(p) : "memory"); return v;
}

__device__ __forceinline__ void mma_ss_184(float (&d)[92], uint64_t da, uint64_t db, int acc) {
  asm volatile("{.reg .pred p; setp.ne.b32 p, %94, 0;\n"
    "wgmma.mma_async.sync.aligned.m64n184k16.f32.bf16.bf16 {%0,%1,%2,%3,%4,%5,%6,%7,%8,%9,%10,%11,%12,%13,%14,%15,%16,%17,%18,%19,%20,%21,%22,%23,%24,%25,%26,%27,%28,%29,%30,%31,%32,%33,%34,%35,%36,%37,%38,%39,%40,%41,%42,%43,%44,%45,%46,%47,%48,%49,%50,%51,%52,%53,%54,%55,%56,%57,%58,%59,%60,%61,%62,%63,%64,%65,%66,%67,%68,%69,%70,%71,%72,%73,%74,%75,%76,%77,%78,%79,%80,%81,%82,%83,%84,%85,%86,%87,%88,%89,%90,%91}, %92, %93, p, 1, 1, 0, 1;}\n"
    : "+f"(d[0]),"+f"(d[1]),"+f"(d[2]),"+f"(d[3]),"+f"(d[4]),"+f"(d[5]),"+f"(d[6]),"+f"(d[7]),"+f"(d[8]),"+f"(d[9]),"+f"(d[10]),"+f"(d[11]),"+f"(d[12]),"+f"(d[13]),"+f"(d[14]),"+f"(d[15]),"+f"(d[16]),"+f"(d[17]),"+f"(d[18]),"+f"(d[19]),"+f"(d[20]),"+f"(d[21]),"+f"(d[22]),"+f"(d[23]),"+f"(d[24]),"+f"(d[25]),"+f"(d[26]),"+f"(d[27]),"+f"(d[28]),"+f"(d[29]),"+f"(d[30]),"+f"(d[31]),"+f"(d[32]),"+f"(d[33]),"+f"(d[34]),"+f"(d[35]),"+f"(d[36]),"+f"(d[37]),"+f"(d[38]),"+f"(d[39]),"+f"(d[40]),"+f"(d[41]),"+f"(d[42]),"+f"(d[43]),"+f"(d[44]),"+f"(d[45]),"+f"(d[46]),"+f"(d[47]),"+f"(d[48]),"+f"(d[49]),"+f"(d[50]),"+f"(d[51]),"+f"(d[52]),"+f"(d[53]),"+f"(d[54]),"+f"(d[55]),"+f"(d[56]),"+f"(d[57]),"+f"(d[58]),"+f"(d[59]),"+f"(d[60]),"+f"(d[61]),"+f"(d[62]),"+f"(d[63]),"+f"(d[64]),"+f"(d[65]),"+f"(d[66]),"+f"(d[67]),"+f"(d[68]),"+f"(d[69]),"+f"(d[70]),"+f"(d[71]),"+f"(d[72]),"+f"(d[73]),"+f"(d[74]),"+f"(d[75]),"+f"(d[76]),"+f"(d[77]),"+f"(d[78]),"+f"(d[79]),"+f"(d[80]),"+f"(d[81]),"+f"(d[82]),"+f"(d[83]),"+f"(d[84]),"+f"(d[85]),"+f"(d[86]),"+f"(d[87]),"+f"(d[88]),"+f"(d[89]),"+f"(d[90]),"+f"(d[91])
    : "l"(da), "l"(db), "r"(acc));
}
__device__ __forceinline__ void mma_ss_224(float (&d)[112], uint64_t da, uint64_t db, int acc) {
  asm volatile("{.reg .pred p; setp.ne.b32 p, %114, 0;\n"
    "wgmma.mma_async.sync.aligned.m64n224k16.f32.bf16.bf16 {%0,%1,%2,%3,%4,%5,%6,%7,%8,%9,%10,%11,%12,%13,%14,%15,%16,%17,%18,%19,%20,%21,%22,%23,%24,%25,%26,%27,%28,%29,%30,%31,%32,%33,%34,%35,%36,%37,%38,%39,%40,%41,%42,%43,%44,%45,%46,%47,%48,%49,%50,%51,%52,%53,%54,%55,%56,%57,%58,%59,%60,%61,%62,%63,%64,%65,%66,%67,%68,%69,%70,%71,%72,%73,%74,%75,%76,%77,%78,%79,%80,%81,%82,%83,%84,%85,%86,%87,%88,%89,%90,%91,%92,%93,%94,%95,%96,%97,%98,%99,%100,%101,%102,%103,%104,%105,%106,%107,%108,%109,%110,%111}, %112, %113, p, 1, 1, 0, 1;}\n"
    : "+f"(d[0]),"+f"(d[1]),"+f"(d[2]),"+f"(d[3]),"+f"(d[4]),"+f"(d[5]),"+f"(d[6]),"+f"(d[7]),"+f"(d[8]),"+f"(d[9]),"+f"(d[10]),"+f"(d[11]),"+f"(d[12]),"+f"(d[13]),"+f"(d[14]),"+f"(d[15]),"+f"(d[16]),"+f"(d[17]),"+f"(d[18]),"+f"(d[19]),"+f"(d[20]),"+f"(d[21]),"+f"(d[22]),"+f"(d[23]),"+f"(d[24]),"+f"(d[25]),"+f"(d[26]),"+f"(d[27]),"+f"(d[28]),"+f"(d[29]),"+f"(d[30]),"+f"(d[31]),"+f"(d[32]),"+f"(d[33]),"+f"(d[34]),"+f"(d[35]),"+f"(d[36]),"+f"(d[37]),"+f"(d[38]),"+f"(d[39]),"+f"(d[40]),"+f"(d[41]),"+f"(d[42]),"+f"(d[43]),"+f"(d[44]),"+f"(d[45]),"+f"(d[46]),"+f"(d[47]),"+f"(d[48]),"+f"(d[49]),"+f"(d[50]),"+f"(d[51]),"+f"(d[52]),"+f"(d[53]),"+f"(d[54]),"+f"(d[55]),"+f"(d[56]),"+f"(d[57]),"+f"(d[58]),"+f"(d[59]),"+f"(d[60]),"+f"(d[61]),"+f"(d[62]),"+f"(d[63]),"+f"(d[64]),"+f"(d[65]),"+f"(d[66]),"+f"(d[67]),"+f"(d[68]),"+f"(d[69]),"+f"(d[70]),"+f"(d[71]),"+f"(d[72]),"+f"(d[73]),"+f"(d[74]),"+f"(d[75]),"+f"(d[76]),"+f"(d[77]),"+f"(d[78]),"+f"(d[79]),"+f"(d[80]),"+f"(d[81]),"+f"(d[82]),"+f"(d[83]),"+f"(d[84]),"+f"(d[85]),"+f"(d[86]),"+f"(d[87]),"+f"(d[88]),"+f"(d[89]),"+f"(d[90]),"+f"(d[91]),"+f"(d[92]),"+f"(d[93]),"+f"(d[94]),"+f"(d[95]),"+f"(d[96]),"+f"(d[97]),"+f"(d[98]),"+f"(d[99]),"+f"(d[100]),"+f"(d[101]),"+f"(d[102]),"+f"(d[103]),"+f"(d[104]),"+f"(d[105]),"+f"(d[106]),"+f"(d[107]),"+f"(d[108]),"+f"(d[109]),"+f"(d[110]),"+f"(d[111])
    : "l"(da), "l"(db), "r"(acc));
}
__device__ __forceinline__ void mma_ss_56(float (&d)[28], uint64_t da, uint64_t db, int acc) {
  asm volatile("{.reg .pred p; setp.ne.b32 p, %30, 0;\n"
    "wgmma.mma_async.sync.aligned.m64n56k16.f32.bf16.bf16 {%0,%1,%2,%3,%4,%5,%6,%7,%8,%9,%10,%11,%12,%13,%14,%15,%16,%17,%18,%19,%20,%21,%22,%23,%24,%25,%26,%27}, %28, %29, p, 1, 1, 0, 1;}\n"
    : "+f"(d[0]),"+f"(d[1]),"+f"(d[2]),"+f"(d[3]),"+f"(d[4]),"+f"(d[5]),"+f"(d[6]),"+f"(d[7]),"+f"(d[8]),"+f"(d[9]),"+f"(d[10]),"+f"(d[11]),"+f"(d[12]),"+f"(d[13]),"+f"(d[14]),"+f"(d[15]),"+f"(d[16]),"+f"(d[17]),"+f"(d[18]),"+f"(d[19]),"+f"(d[20]),"+f"(d[21]),"+f"(d[22]),"+f"(d[23]),"+f"(d[24]),"+f"(d[25]),"+f"(d[26]),"+f"(d[27])
    : "l"(da), "l"(db), "r"(acc));
}
__device__ __forceinline__ void mma_rs_56(float (&d)[28], uint32_t a0, uint32_t a1, uint32_t a2, uint32_t a3, uint64_t db, int acc) {
  asm volatile("{.reg .pred p; setp.ne.b32 p, %33, 0;\n"
    "wgmma.mma_async.sync.aligned.m64n56k16.f32.bf16.bf16 {%0,%1,%2,%3,%4,%5,%6,%7,%8,%9,%10,%11,%12,%13,%14,%15,%16,%17,%18,%19,%20,%21,%22,%23,%24,%25,%26,%27}, {%28,%29,%30,%31}, %32, p, 1, 1, 1;}\n"
    : "+f"(d[0]),"+f"(d[1]),"+f"(d[2]),"+f"(d[3]),"+f"(d[4]),"+f"(d[5]),"+f"(d[6]),"+f"(d[7]),"+f"(d[8]),"+f"(d[9]),"+f"(d[10]),"+f"(d[11]),"+f"(d[12]),"+f"(d[13]),"+f"(d[14]),"+f"(d[15]),"+f"(d[16]),"+f"(d[17]),"+f"(d[18]),"+f"(d[19]),"+f"(d[20]),"+f"(d[21]),"+f"(d[22]),"+f"(d[23]),"+f"(d[24]),"+f"(d[25]),"+f"(d[26]),"+f"(d[27])
    : "r"(a0), "r"(a1), "r"(a2), "r"(a3), "l"(db), "r"(acc));
}
__device__ __forceinline__ void mma_ss_64t(float (&d)[32], uint64_t da, uint64_t db, int acc) {
  asm volatile("{.reg .pred p; setp.ne.b32 p, %34, 0;\n"
    "wgmma.mma_async.sync.aligned.m64n64k16.f32.bf16.bf16 {%0,%1,%2,%3,%4,%5,%6,%7,%8,%9,%10,%11,%12,%13,%14,%15,%16,%17,%18,%19,%20,%21,%22,%23,%24,%25,%26,%27,%28,%29,%30,%31}, %32, %33, p, 1, 1, 1, 1;}\n"
    : "+f"(d[0]),"+f"(d[1]),"+f"(d[2]),"+f"(d[3]),"+f"(d[4]),"+f"(d[5]),"+f"(d[6]),"+f"(d[7]),"+f"(d[8]),"+f"(d[9]),"+f"(d[10]),"+f"(d[11]),"+f"(d[12]),"+f"(d[13]),"+f"(d[14]),"+f"(d[15]),"+f"(d[16]),"+f"(d[17]),"+f"(d[18]),"+f"(d[19]),"+f"(d[20]),"+f"(d[21]),"+f"(d[22]),"+f"(d[23]),"+f"(d[24]),"+f"(d[25]),"+f"(d[26]),"+f"(d[27]),"+f"(d[28]),"+f"(d[29]),"+f"(d[30]),"+f"(d[31])
    : "l"(da), "l"(db), "r"(acc));
}
__device__ __forceinline__ void mma_rs_64(float (&d)[32], uint32_t a0, uint32_t a1, uint32_t a2, uint32_t a3, uint64_t db, int acc) {
  asm volatile("{.reg .pred p; setp.ne.b32 p, %37, 0;\n"
    "wgmma.mma_async.sync.aligned.m64n64k16.f32.bf16.bf16 {%0,%1,%2,%3,%4,%5,%6,%7,%8,%9,%10,%11,%12,%13,%14,%15,%16,%17,%18,%19,%20,%21,%22,%23,%24,%25,%26,%27,%28,%29,%30,%31}, {%32,%33,%34,%35}, %36, p, 1, 1, 1;}\n"
    : "+f"(d[0]),"+f"(d[1]),"+f"(d[2]),"+f"(d[3]),"+f"(d[4]),"+f"(d[5]),"+f"(d[6]),"+f"(d[7]),"+f"(d[8]),"+f"(d[9]),"+f"(d[10]),"+f"(d[11]),"+f"(d[12]),"+f"(d[13]),"+f"(d[14]),"+f"(d[15]),"+f"(d[16]),"+f"(d[17]),"+f"(d[18]),"+f"(d[19]),"+f"(d[20]),"+f"(d[21]),"+f"(d[22]),"+f"(d[23]),"+f"(d[24]),"+f"(d[25]),"+f"(d[26]),"+f"(d[27]),"+f"(d[28]),"+f"(d[29]),"+f"(d[30]),"+f"(d[31])
    : "r"(a0), "r"(a1), "r"(a2), "r"(a3), "l"(db), "r"(acc));
}

__device__ __forceinline__ void dual_softmax(const float (&p)[28], uint32_t (&phi)[4][7]) {
  constexpr float L2E = 1.4426950408889634f;
#pragma unroll
  for (int i = 0; i < 4; i++) {
    float mx = p[i], mn = p[i];
#pragma unroll
    for (int j = 1; j < 7; j++) { mx = fmaxf(mx, p[4 * j + i]); mn = fminf(mn, p[4 * j + i]); }
    mx = fmaxf(mx, __shfl_xor_sync(~0u, mx, 1)); mn = fminf(mn, __shfl_xor_sync(~0u, mn, 1));
    mx = fmaxf(mx, __shfl_xor_sync(~0u, mx, 2)); mn = fminf(mn, __shfl_xor_sync(~0u, mn, 2));
    float a[7], b[7], sa = 0.f, sb = 0.f;
    const float mxl = mx * L2E, mnl = mn * L2E;
#pragma unroll
    for (int j = 0; j < 7; j++) {
      a[j] = ex2(fmaf(p[4 * j + i], L2E, -mxl)); b[j] = ex2(fmaf(p[4 * j + i], -L2E, mnl));
      sa += a[j]; sb += b[j];
    }
    sa += __shfl_xor_sync(~0u, sa, 1); sb += __shfl_xor_sync(~0u, sb, 1);
    sa += __shfl_xor_sync(~0u, sa, 2); sb += __shfl_xor_sync(~0u, sb, 2);
    const float ra = __fdividef(1.f, sa), rb = __fdividef(1.f, sb);
#pragma unroll
    for (int j = 0; j < 7; j++) phi[i][j] = pack(a[j] * ra, b[j] * rb);
  }
}

struct Ring {
  uint32_t full, empty, base; int slot, par;
  __device__ __forceinline__ uint32_t acquire() { mbar_wait(full + slot * 8, par); return base + slot * SLOT; }
  __device__ __forceinline__ int advance() { int s = slot; if (++slot == NSLOT) { slot = 0; par ^= 1; } return s; }
  __device__ __forceinline__ void release(int s, bool elect) { if (elect) mbar_arrive(empty + s * 8); }
};
constexpr int FL_KV = 448, FL_ZERO = FL_KV + 16, FL_DONE = FL_KV + 32;

__global__ void __launch_bounds__(384, 1)
fused_kernel(const __grid_constant__ CUtensorMap mQKV, const __grid_constant__ CUtensorMap mWO,
             const __grid_constant__ CUtensorMap mW1, const __grid_constant__ CUtensorMap mW2,
             const __grid_constant__ CUtensorMap mX,
             const __nv_bfloat16* __restrict__ x, const __nv_bfloat16* __restrict__ wphi,
             const __nv_bfloat16* __restrict__ b1, const __nv_bfloat16* __restrict__ b2,
             const __nv_bfloat16* __restrict__ wo, const __nv_bfloat16* __restrict__ w1,
             const __nv_bfloat16* __restrict__ w2, __nv_bfloat16* __restrict__ out) {
  extern __shared__ unsigned char smem_raw[];
  const uint32_t sb = (smem_u32(smem_raw) + 1023) & ~1023u;
  unsigned char* sg = smem_raw + (sb - smem_u32(smem_raw));
  const int tid = threadIdx.x, lane = tid & 31;
  const int G = blockIdx.x >> 3, r = blockIdx.x & 7;
  const uint32_t barFull = sb + OFF_BAR, barEmpty = barFull + 56, barA = barEmpty + 56, barCS = barA + 112;
  if (tid == 0) {
    for (int i = 0; i < NSLOT; i++) { mbar_init(barFull + i * 8, 1); mbar_init(barEmpty + i * 8, 4); }
    for (int i = 0; i < 14; i++) mbar_init(barA + i * 8, 1);
    mbar_init(barCS, 64); mbar_init(barCS + 8, 64);
    asm volatile("fence.mbarrier_init.release.cluster;" ::: "memory");
  }
  __syncthreads();
  const int wgid = __shfl_sync(~0u, tid >> 7, 0);
  if (wgid == 2) {
    asm volatile("setmaxnreg.dec.sync.aligned.u32 40;");
    if (tid == 256) {
      int slot = 0, par = 1;
      for (int it = 0; it < 2 * TILES_PER_LAYER; it++) {
        const int i = it >= TILES_PER_LAYER ? it - TILES_PER_LAYER : it;
        mbar_wait(barEmpty + slot * 8, par);
        const uint32_t dst = sb + OFF_RING + slot * SLOT, fb = barFull + slot * 8;
        mbar_expect(fb, i < 14 ? 12288 : SLOT);
        if (i < 14) tma3(dst, &mQKV, 56 * r, 32 * i, 0, fb);
        else if (i < 18) tma2(dst, &mWO, 56 * r, 112 * (i - 14), fb);
        else if (i < 32) tma3(dst, &mW1, 0, 32 * (i - 18), 7 * r, fb);
        else tma2(dst, &mW2, 64 * ((i - 32) >> 1), 224 * r + 112 * (i & 1), fb);
        if (it >= 32) asm volatile("mbarrier.arrive.shared::cta.b64 _, [%0], 2;" ::"r"(barEmpty + slot * 8) : "memory");
        if (++slot == NSLOT) { slot = 0; par ^= 1; }
      }
    } else if (tid >= 352) {
      if (lane < 14) {
        mbar_expect(barA + lane * 8, 8192);
        tma2(sb + lane * 8192, &mX, 64 * (lane % 7), G * 128 + 64 * (lane / 7), barA + lane * 8);
      } else if (lane < 17) {
        const char* src = lane == 14 ? (const char*)wo + blockIdx.x * 3136 : (lane == 15 ? (const char*)w1 : (const char*)w2) + blockIdx.x * 12544;
        asm volatile("cp.async.bulk.prefetch.L2.global [%0], %1;" ::"l"(src), "r"(lane == 14 ? 3136 : 12544) : "memory");
      }
    } else if (tid >= 288) {
      const int idx = tid - 288;
      float s0 = 0.f, s1 = 0.f, s2 = 0.f, s3 = 0.f;
      int slot = 0, par = 0;
      for (int it = 0; it < 32; it++) {
        mbar_wait(barFull + slot * 8, par);
        const bool qkv = it < 14;
        if ((qkv && idx < 48) || (it >= 18 && idx < 56)) {
          const uint32_t base = sb + OFF_RING + slot * SLOT + (qkv ? (idx >> 4) * 4096 : (idx >> 3) * 2048) + (idx & 1) * 8;
          const int ch = qkv ? (idx >> 1) & 7 : (idx >> 1) & 3;
#pragma unroll 4
          for (int row = 0; row < 32; row++) {
            uint32_t u, v;
            const uint32_t a = base + (qkv ? row * 128 + ((ch ^ (row & 7)) << 4) : row * 64 + ((ch ^ ((row >> 1) & 3)) << 4));
            asm volatile("ld.shared.v2.u32 {%0,%1}, [%2];" : "=r"(u), "=r"(v) : "r"(a) : "memory");
            s0 += lo(u); s1 += hi(u); s2 += lo(v); s3 += hi(v);
          }
        }
        __syncwarp();
        if (lane == 0) mbar_arrive(barEmpty + slot * 8);
        if (it == 13 || it == 31) {
          if (idx < (qkv ? 48 : 56)) reinterpret_cast<float4*>(sg + OFF_CS + (qkv ? 0 : 768))[idx] = make_float4(s0, s1, s2, s3);
          mbar_arrive(barCS + (qkv ? 0 : 8));
          s0 = s1 = s2 = s3 = 0.f;
        }
        if (++slot == NSLOT) { slot = 0; par ^= 1; }
      }
    }
  } else {
  asm volatile("setmaxnreg.inc.sync.aligned.u32 232;");
  const int c = wgid, w = (tid >> 5) & 3, g = lane >> 2, t = lane & 3;
  const bool elect = (tid & 127) == 0;
  const uint32_t abuf = sb + c * ABYTES, barAc = barA + c * 56;
  const int row0 = G * 128 + c * 64;
  unsigned epoch;
  asm volatile("ld.relaxed.gpu.global.u32 %0, [%1];" : "=r"(epoch) : "l"(gFlag + FL_DONE * 32) : "memory");
  float mean[2], rstd[2];
  {
    uint32_t wv[8];
#pragma unroll
    for (int i = 0; i < 8; i++) {
      const int k = i * 8 + (tid >> 5), e = k >= 28;
      wv[i] = (k < 56 && lane < 28) ? (uint32_t)__ldg(reinterpret_cast<const unsigned short*>(wphi) + (2 * r + e) * 784 + (k - 28 * e) * 28 + lane) << (16 * e) : 0u;
    }
    const float bv = tid < 224 ? __bfloat162float(b1[224 * r + tid]) : 0.f;
    if (G == 0) {
#pragma unroll 1
      for (int i = tid; i < 2 * 1280; i += 256) gKV[((i >= 1280) * 7 + r) * 1280 + i] = make_float4(0.f, 0.f, 0.f, 0.f);
    }
#pragma unroll 1
    for (int hh = 0; hh < 2; hh++) {
      const uint4* src = reinterpret_cast<const uint4*>(x + (size_t)(row0 + w * 16 + hh * 8 + g) * DM) + t;
      uint4 v[14];
#pragma unroll
      for (int k = 0; k < 14; k++) v[k] = __ldg(src + k * 4);
      float s = 0.f, q = 0.f;
#pragma unroll
      for (int k = 0; k < 14; k++) s += (lo(v[k].x) + hi(v[k].x)) + (lo(v[k].y) + hi(v[k].y)) + (lo(v[k].z) + hi(v[k].z)) + (lo(v[k].w) + hi(v[k].w));
      s += __shfl_xor_sync(~0u, s, 1); s += __shfl_xor_sync(~0u, s, 2);
      s *= 1.f / DM;
#pragma unroll
      for (int k = 0; k < 14; k++) {
        const uint32_t e[4] = {v[k].x, v[k].y, v[k].z, v[k].w};
#pragma unroll
        for (int z = 0; z < 4; z++) { float a = lo(e[z]) - s, b = hi(e[z]) - s; q = fmaf(a, a, q); q = fmaf(b, b, q); }
      }
      q += __shfl_xor_sync(~0u, q, 1); q += __shfl_xor_sync(~0u, q, 2);
      q = rsqrtf(q * (1.f / DM) + 1e-5f);
      if (hh) { mean[1] = s; rstd[1] = q; } else { mean[0] = s; rstd[0] = q; mean[1] = 0.f; rstd[1] = 0.f; }
    }
#pragma unroll
    for (int i = 0; i < 8; i++) {
      const int k = i * 8 + (tid >> 5);
      *reinterpret_cast<uint32_t*>(sg + OFF_WPHI + k * 128 + ((g ^ (k & 7)) << 4) + t * 4) = wv[i];
    }
    if (tid < 224) reinterpret_cast<float*>(sg + OFF_B1)[tid] = bv;
    fence_async_smem();
    bar_sync<3, 256>();
    epoch = epoch / NCTA + 1;
    if (G == 0 && tid == 0) flag_arrive(gFlag + (FL_ZERO + r) * 32);
  }
  STAMP(0);
  Ring ring{barFull, barEmpty, sb + OFF_RING, 0, 0};
  int apar = 0;
  const uint32_t stsm_off = (w * 16 + ((lane >> 3) & 1) * 8 + (lane & 7)) * 128;
  const uint32_t stsm_hi = lane >> 4;
  const uint64_t dA = mkdesc(abuf, 16, 1024, 1);

  auto gather = [&](unsigned* fl, const unsigned char* img) {
    __syncwarp();
    if (lane == 0) flag_arrive(fl);
    if (elect) {
      flag_wait(fl, epoch * 32);
      fence_async();
#pragma unroll 1
      for (int k = 0; k < 7; k++) { mbar_expect(barAc + k * 8, 8192); bulk_ld(abuf + k * 8192, img + k * 8192, 8192, barAc + k * 8); }
    }
    __syncwarp();
    apar ^= 1;
  };
  auto slice_off = [&](int j, int hh) -> uint32_t {
    const int ci = 7 * r + j;
    return (ci >> 3) * 8192 + (w * 16 + hh * 8 + g) * 128 + (((ci & 7) ^ g) << 4) + t * 4;
  };
  auto load_stats = [&](const float2* st) {
#pragma unroll
    for (int hh = 0; hh < 2; hh++) {
      const uint4 u = ldcg4(st + (size_t)(row0 + w * 16 + hh * 8 + g) * 8 + 2 * t);
      const float m0 = __uint_as_float(u.x), m1 = __uint_as_float(u.z);
      float m = m0 + m1;
      m += __shfl_xor_sync(~0u, m, 1); m += __shfl_xor_sync(~0u, m, 2);
      m *= 0.125f;
      float q = __uint_as_float(u.y) + __uint_as_float(u.w) + 56.f * ((m0 - m) * (m0 - m) + (m1 - m) * (m1 - m));
      q += __shfl_xor_sync(~0u, q, 1); q += __shfl_xor_sync(~0u, q, 2);
      mean[hh] = m; rstd[hh] = rsqrtf(q * (1.f / DM) + 1e-5f);
    }
  };

#pragma unroll 1
  for (int layer = 0; layer < 2; layer++) {
    unsigned* const fl = gFlag + (layer * 32 + G * 2 + c) * 7 * 32;
    uint32_t phiq[4][7], xs[7][2];
    {
      float acc[92]; reg_def(acc);
      int prev = 0;
#pragma unroll 1
      for (int st = 0; st < 14; st++) {
        if (!(st & 1)) mbar_wait(barAc + (st >> 1) * 8, apar);
        const uint64_t da = dA + (st >> 1) * 512 + (st & 1) * 4, db = mkdesc(ring.acquire(), 4096, 1024, 1);
        wg_fence();
        mma_ss_184(acc, da, db, st);
        mma_ss_184(acc, da + 2, db + 128, 1);
        wg_commit();
        if (st > 0) { wg_wait<1>(); ring.release(prev, elect); }
        prev = ring.advance();
      }
      if (layer) load_stats(gStat + 2048 * 8); else mbar_wait(barCS, 0);
#pragma unroll
      for (int j = 0; j < 7; j++) { xs[j][0] = lds32(abuf + slice_off(j, 0)); xs[j][1] = lds32(abuf + slice_off(j, 1)); }
      wg_wait<0>(); reg_fence(acc);
      ring.release(prev, elect);
      STAMP(1 + layer * 12);
      uint32_t f[3][14];
      {
        const float2* cs = reinterpret_cast<const float2*>(sg + OFF_CS) + t;
        const float mr0 = -mean[0] * rstd[0], mr1 = -mean[1] * rstd[1];
#pragma unroll
        for (int p = 0; p < 3; p++)
#pragma unroll
          for (int j = 0; j < 7; j++) {
            const float2 s = cs[p * 32 + j * 4];
            const int b = p * 32 + j * 4;
            f[p][2 * j] = pack(fmaf(acc[b], rstd[0], s.x * mr0), fmaf(acc[b + 1], rstd[0], s.y * mr0));
            f[p][2 * j + 1] = pack(fmaf(acc[b + 2], rstd[1], s.x * mr1), fmaf(acc[b + 3], rstd[1], s.y * mr1));
          }
      }
      float pk[28], pq[28]; reg_def(pk); reg_def(pq);
      const uint64_t dW = mkdesc(sb + OFF_WPHI, 4096, 1024, 1);
      wg_fence();
#pragma unroll
      for (int s = 0; s < 4; s++)
        mma_rs_56(pk, f[1][4 * s], f[1][4 * s + 1], s < 3 ? f[1][(4 * s + 2) % 14] : 0u, s < 3 ? f[1][(4 * s + 3) % 14] : 0u, dW + s * 128, s);
      wg_commit();
#pragma unroll
      for (int s = 0; s < 4; s++)
        mma_rs_56(pq, f[0][4 * s], f[0][4 * s + 1], s < 3 ? f[0][(4 * s + 2) % 14] : 0u, s < 3 ? f[0][(4 * s + 3) % 14] : 0u, dW + s * 128, s);
      wg_commit();
      bar_wg(c);
      const uint32_t srow = abuf + stsm_off, ones = t == 0 ? 0x3F803F80u : 0u;
#pragma unroll
      for (int jp = 0; jp < 4; jp++)
        stsm4(srow + 16384 + (((2 * jp + stsm_hi) ^ (lane & 7)) << 4), f[2][4 * jp], f[2][4 * jp + 1],
              jp < 3 ? f[2][(4 * jp + 2) % 14] : ones, jp < 3 ? f[2][(4 * jp + 3) % 14] : ones);
      wg_wait<0>(); reg_fence(pk); reg_fence(pq);
#pragma unroll 1
      for (int pass = 0; pass < 2; pass++) {
        dual_softmax(pk, phiq);
        if (pass) break;
#pragma unroll
        for (int e = 0; e < 2; e++)
#pragma unroll
          for (int jp = 0; jp < 4; jp++)
            stsm4(srow + e * 8192 + (((2 * jp + stsm_hi) ^ (lane & 7)) << 4), phiq[e][2 * jp], phiq[2 + e][2 * jp],
                  jp < 3 ? phiq[e][(2 * jp + 1) % 7] : 0u, jp < 3 ? phiq[2 + e][(2 * jp + 1) % 7] : 0u);
        fence_async_smem();
        bar_sync<3, 256>();
        float kv[32]; reg_def(kv);
        const uint64_t dP = mkdesc(sb + c * 8192, 4096, 1024, 1), dV = mkdesc(sb + 16384, 4096, 1024, 1);
        wg_fence();
#pragma unroll
        for (int s = 0; s < 8; s++) mma_ss_64t(kv, dP + (s >> 2) * (ABYTES / 16) + (s & 3) * 128, dV + (s >> 2) * (ABYTES / 16) + (s & 3) * 128, s);
        wg_commit();
        if (layer == 0 && lane == 0) flag_wait(gFlag + (FL_ZERO + r) * 32, epoch);
        __syncwarp();
        wg_wait<0>(); reg_fence(kv);
        float4* kvg = gKV + ((layer * 8 + r) * 2 + c) * 640 + (tid & 127);
#pragma unroll
        for (int i = 0; i < 5; i++) {
          float v0, v1, v2, v3;
          if (i == 4) { v0 = kv[28]; v1 = kv[29]; v2 = kv[30]; v3 = kv[31]; }
          else { v0 = c ? kv[12 + 4 * i] : kv[4 * i]; v1 = c ? kv[13 + 4 * i] : kv[1 + 4 * i]; v2 = c ? kv[14 + 4 * i] : kv[2 + 4 * i]; v3 = c ? kv[15 + 4 * i] : kv[3 + 4 * i]; }
          const bool use = i == 4 ? t == 0 : (i == 0 ? (c == 0 || t >= 2) : (i == 3 ? (c == 1 || t < 2) : true));
          if (use) asm volatile("red.relaxed.gpu.global.add.v4.f32 [%0], {%1,%2,%3,%4};" ::"l"(kvg + i * 128), "f"(v0), "f"(v1), "f"(v2), "f"(v3) : "memory");
        }
        __syncwarp();
        if (lane == 0) flag_arrive(gFlag + (FL_KV + layer * 8 + r) * 32);
        __syncwarp();
        STAMP(2 + layer * 12);
#pragma unroll
        for (int i = 0; i < 28; i++) pk[i] = pq[i];
      }
    }
    {
      if (elect) flag_wait(gFlag + (FL_KV + layer * 8 + r) * 32, epoch * 128);
      bar_wg(c);
      STAMP(3 + layer * 12);
      const float4* kvg = gKV + (layer * 8 + r) * 1280 + (tid & 127);
      uint4 kk[2][5];
#pragma unroll
      for (int e = 0; e < 2; e++)
#pragma unroll
        for (int i = 0; i < 5; i++) kk[e][i] = ldcg4(kvg + e * 640 + i * 128);
      const uint32_t srow = abuf + 24576 + stsm_off;
#pragma unroll
      for (int e = 0; e < 2; e++) {
        uint32_t f[8][2];
#pragma unroll
        for (int j = 0; j < 8; j++) { f[j][0] = 0u; f[j][1] = 0u; }
#pragma unroll
        for (int i = 0; i < 4; i++) {
          f[i + 3 * e][0] = pack(__uint_as_float(kk[e][i].x), __uint_as_float(kk[e][i].y));
          f[i + 3 * e][1] = pack(__uint_as_float(kk[e][i].z), __uint_as_float(kk[e][i].w));
        }
        f[7][0] = e ? pack(0.f, __uint_as_float(kk[e][4].y)) : pack(__uint_as_float(kk[e][4].x), 0.f);
        f[7][1] = e ? pack(0.f, __uint_as_float(kk[e][4].w)) : pack(__uint_as_float(kk[e][4].z), 0.f);
#pragma unroll
        for (int jp = 0; jp < 4; jp++)
          stsm4(srow + e * 8192 + (((2 * jp + stsm_hi) ^ (lane & 7)) << 4), f[2 * jp][0], f[2 * jp][1], f[2 * jp + 1][0], f[2 * jp + 1][1]);
      }
      fence_async_smem();
      bar_wg(c);
      float num[32]; reg_def(num);
      const uint64_t dK = mkdesc(abuf + 24576, 4096, 1024, 1);
      wg_fence();
#pragma unroll
      for (int e = 0; e < 2; e++)
#pragma unroll
        for (int s = 0; s < 4; s++)
          mma_rs_64(num, phiq[e][2 * s], phiq[2 + e][2 * s], s < 3 ? phiq[e][(2 * s + 1) % 7] : 0u, s < 3 ? phiq[2 + e][(2 * s + 1) % 7] : 0u,
                    dK + e * 512 + s * 128, e + s);
      wg_commit();
      wg_wait<0>(); reg_fence(num);
      float rd[4];
#pragma unroll
      for (int i = 0; i < 4; i++) rd[i] = __fdividef(1.f, __shfl_sync(~0u, num[28 + i], lane & ~3) + 1e-6f);
      unsigned char* img = gImg + (size_t)(G * 2 + c) * ABYTES;
#pragma unroll
      for (int j = 0; j < 7; j++) {
        const bool hb = j > 3 || (j == 3 && t >= 2);
        const float r0 = hb ? rd[1] : rd[0], r1 = hb ? rd[3] : rd[2];
        *reinterpret_cast<uint32_t*>(img + slice_off(j, 0)) = pack(num[4 * j] * r0, num[4 * j + 1] * r0);
        *reinterpret_cast<uint32_t*>(img + slice_off(j, 1)) = pack(num[4 * j + 2] * r1, num[4 * j + 3] * r1);
      }
      STAMP(4 + layer * 12);
      gather(fl, img);
      STAMP(5 + layer * 12);
    }
    {
      float acc[28]; reg_def(acc);
      int prev = 0;
#pragma unroll 1
      for (int st = 0; st < 4; st++) {
        mbar_wait(barAc + (st * 7 + 3) / 4 * 8, apar);
        mbar_wait(barAc + (st * 7 + 6) / 4 * 8, apar);
        const uint64_t db = mkdesc(ring.acquire(), 4096, 1024, 1);
        wg_fence();
#pragma unroll
        for (int s = 0; s < 7; s++) { const int ks = st * 7 + s; mma_ss_56(acc, dA + (ks >> 2) * 512 + (ks & 3) * 2, db + s * 128, ks); }
        wg_commit();
        if (st > 0) { wg_wait<1>(); ring.release(prev, elect); }
        prev = ring.advance();
      }
      wg_wait<0>(); reg_fence(acc);
      ring.release(prev, elect);
      unsigned char* img = gImg + (size_t)(32 + G * 2 + c) * ABYTES;
#pragma unroll
      for (int hh = 0; hh < 2; hh++) {
        float s = 0.f, q = 0.f;
#pragma unroll
        for (int j = 0; j < 7; j++) {
          xs[j][hh] = pack(lo(xs[j][hh]) + acc[4 * j + 2 * hh], hi(xs[j][hh]) + acc[4 * j + 2 * hh + 1]);
          *reinterpret_cast<uint32_t*>(img + slice_off(j, hh)) = xs[j][hh];
          s += lo(xs[j][hh]) + hi(xs[j][hh]);
        }
        s += __shfl_xor_sync(~0u, s, 1); s += __shfl_xor_sync(~0u, s, 2);
        s *= 1.f / 56.f;
#pragma unroll
        for (int j = 0; j < 7; j++) { const float a = lo(xs[j][hh]) - s, b = hi(xs[j][hh]) - s; q = fmaf(a, a, q); q = fmaf(b, b, q); }
        q += __shfl_xor_sync(~0u, q, 1); q += __shfl_xor_sync(~0u, q, 2);
        if (t == 0) gStat[(size_t)(row0 + w * 16 + hh * 8 + g) * 8 + r] = make_float2(s, q);
      }
      STAMP(6 + layer * 12);
      gather(fl + 32, img);
      STAMP(7 + layer * 12);
    }
    {
      uint32_t hf[28][2];
      {
        float acc[112]; reg_def(acc);
        int prev = 0;
#pragma unroll 1
        for (int st = 0; st < 14; st++) {
          if (!(st & 1)) mbar_wait(barAc + (st >> 1) * 8, apar);
          const uint64_t da = dA + (st >> 1) * 512 + (st & 1) * 4, db = mkdesc(ring.acquire(), 2048, 512, 2);
          wg_fence();
          mma_ss_224(acc, da, db, st);
          mma_ss_224(acc, da + 2, db + 64, 1);
          wg_commit();
          if (st > 0) { wg_wait<1>(); ring.release(prev, elect); }
          prev = ring.advance();
        }
        load_stats(gStat);
        mbar_wait(barCS + 8, 0);
        wg_wait<0>(); reg_fence(acc);
        ring.release(prev, elect);
        STAMP(8 + layer * 12);
        const float2* bs = reinterpret_cast<const float2*>(sg + OFF_B1) + t;
        const float2* cs = reinterpret_cast<const float2*>(sg + OFF_CS + 768) + t;
        const float mr0 = -mean[0] * rstd[0], mr1 = -mean[1] * rstd[1];
#pragma unroll
        for (int j = 0; j < 28; j++) {
          const float2 b = bs[4 * j], s = cs[4 * j];
          const float h0 = fmaxf(fmaf(acc[4 * j], rstd[0], fmaf(s.x, mr0, b.x)), 0.f), h1 = fmaxf(fmaf(acc[4 * j + 1], rstd[0], fmaf(s.y, mr0, b.y)), 0.f);
          const float h2 = fmaxf(fmaf(acc[4 * j + 2], rstd[1], fmaf(s.x, mr1, b.x)), 0.f), h3 = fmaxf(fmaf(acc[4 * j + 3], rstd[1], fmaf(s.y, mr1, b.y)), 0.f);
          hf[j][0] = pack(h0 * h0, h1 * h1); hf[j][1] = pack(h2 * h2, h3 * h3);
        }
      }
      unsigned char* pdst = gP + (size_t)(((G * 2 + c) * 8 + 2 * w) * 8 + r) * 7168 + (g * 56 + t) * 16;
      uint4 pk[4] = {};
#pragma unroll 1
      for (int ch = 0; ch < 7; ch++) {
        float acc[32]; reg_def(acc);
        int sl0 = 0, sl1 = 0;
#pragma unroll
        for (int hk = 0; hk < 2; hk++) {
          const uint64_t db = mkdesc(ring.acquire(), 4096, 1024, 1);
          wg_fence();
#pragma unroll
          for (int s = 0; s < 7; s++) { const int ks = hk * 7 + s; mma_rs_64(acc, hf[2 * ks][0], hf[2 * ks][1], hf[2 * ks + 1][0], hf[2 * ks + 1][1], db + s * 128, ks); }
          wg_commit();
          if (hk) sl1 = ring.advance(); else sl0 = ring.advance();
        }
        if (ch > 0) {
#pragma unroll
          for (int i = 0; i < 4; i++) *reinterpret_cast<uint4*>(pdst + (i & 1) * (8 * 7168) + (i >> 1) * 64) = pk[i];
          pdst += 128;
        }
        wg_wait<1>(); ring.release(sl0, elect);
        wg_wait<0>(); reg_fence(acc); ring.release(sl1, elect);
#pragma unroll
        for (int i = 0; i < 4; i++) {
          const int b = (i >> 1) * 16 + (i & 1) * 2;
          pk[i] = make_uint4(pack(acc[b], acc[b + 1]), pack(acc[b + 4], acc[b + 5]), pack(acc[b + 8], acc[b + 9]), pack(acc[b + 12], acc[b + 13]));
        }
      }
#pragma unroll
      for (int i = 0; i < 4; i++) *reinterpret_cast<uint4*>(pdst + (i & 1) * (8 * 7168) + (i >> 1) * 64) = pk[i];
      STAMP(9 + layer * 12);
    }
    {
      __syncwarp();
      if (lane == 0) { flag_arrive(fl + (3 + w) * 32); flag_wait(fl + (3 + (r >> 1)) * 32, epoch * 8); }
      __syncwarp();
      STAMP(10 + layer * 12);
      const unsigned char* psrc = gP + (size_t)(((G * 2 + c) * 8 + r) * 8) * 7168 + (w * 2 * 56 + lane) * 16;
      unsigned char* img = gImg + (size_t)(64 + G * 2 + c) * ABYTES;
      float y[4][8];
      uint32_t off[4];
      if (lane < 28) {
        uint4 pv[8][4];
#pragma unroll
        for (int s = 0; s < 8; s++)
#pragma unroll
          for (int i = 0; i < 4; i++) pv[s][i] = ldcg4(psrc + s * 7168 + i * 448);
#pragma unroll
        for (int i = 0; i < 4; i++) {
          const int unit = g + 7 * (i & 1), row = r * 8 + w * 2 + (i >> 1);
          off[i] = (unit >> 1) * 8192 + row * 128 + ((((unit & 1) * 4) ^ (row & 7)) << 4) + t * 4;
#pragma unroll
          for (int jj = 0; jj < 4; jj++) {
            const uint32_t bb = __ldg(reinterpret_cast<const uint32_t*>(b2 + unit * 32 + jj * 8 + 2 * t)), xo = lds32(abuf + (off[i] ^ (jj << 4)));
            y[i][2 * jj] = lo(bb) + lo(xo); y[i][2 * jj + 1] = hi(bb) + hi(xo);
          }
        }
#pragma unroll
        for (int s = 0; s < 8; s++)
#pragma unroll
          for (int i = 0; i < 4; i++) {
            y[i][0] += lo(pv[s][i].x); y[i][1] += hi(pv[s][i].x); y[i][2] += lo(pv[s][i].y); y[i][3] += hi(pv[s][i].y);
            y[i][4] += lo(pv[s][i].z); y[i][5] += hi(pv[s][i].z); y[i][6] += lo(pv[s][i].w); y[i][7] += hi(pv[s][i].w);
          }
#pragma unroll
        for (int i = 0; i < 4; i++)
#pragma unroll
          for (int jj = 0; jj < 4; jj++) {
            const uint32_t v = pack(y[i][2 * jj], y[i][2 * jj + 1]);
            y[i][2 * jj] = lo(v); y[i][2 * jj + 1] = hi(v);
            unsigned char* dst = layer ? reinterpret_cast<unsigned char*>(out + (size_t)(row0 + r * 8 + w * 2 + (i >> 1)) * DM + (g + 7 * (i & 1)) * 32 + jj * 8 + 2 * t)
                                       : img + (off[i] ^ (jj << 4));
            *reinterpret_cast<uint32_t*>(dst) = v;
          }
      } else {
#pragma unroll
        for (int i = 0; i < 32; i++) y[i >> 3][i & 7] = 0.f;
      }
      if (layer) break;
      float s0 = 0.f, s1 = 0.f, q0 = 0.f, q1 = 0.f;
#pragma unroll
      for (int i = 0; i < 16; i++) { s0 += y[i >> 3][i & 7]; s1 += y[2 + (i >> 3)][i & 7]; }
#pragma unroll
      for (int o = 16; o; o >>= 1) { s0 += __shfl_xor_sync(~0u, s0, o); s1 += __shfl_xor_sync(~0u, s1, o); }
      s0 *= 1.f / DM; s1 *= 1.f / DM;
      if (lane < 28) {
#pragma unroll
        for (int i = 0; i < 16; i++) { const float a = y[i >> 3][i & 7] - s0, b = y[2 + (i >> 3)][i & 7] - s1; q0 = fmaf(a, a, q0); q1 = fmaf(b, b, q1); }
      }
#pragma unroll
      for (int o = 16; o; o >>= 1) { q0 += __shfl_xor_sync(~0u, q0, o); q1 += __shfl_xor_sync(~0u, q1, o); }
      if (lane < 16) gStat[(size_t)(2048 + row0 + r * 8 + w * 2) * 8 + lane] = lane < 8 ? make_float2(s0, q0 * 0.125f) : make_float2(s1, q1 * 0.125f);
      STAMP(11);
      gather(fl + 64, img);
      STAMP(12);
    }
  }
  STAMP(30);
  if (tid == 0) asm volatile("red.relaxed.gpu.global.add.u32 [%0], 1;" ::"l"(gFlag + FL_DONE * 32) : "memory");
  }
}

typedef CUresult (*EncFn)(CUtensorMap*, CUtensorMapDataType, cuuint32_t, void*, const cuuint64_t*, const cuuint64_t*,
                          const cuuint32_t*, const cuuint32_t*, CUtensorMapInterleave, CUtensorMapSwizzle,
                          CUtensorMapL2promotion, CUtensorMapFloatOOBfill);

void make_map(EncFn enc, CUtensorMap* m, void* p, int rank, uint64_t d0, uint64_t d1, uint64_t d2, uint64_t s1, uint64_t s2,
              uint32_t b0, uint32_t b1, uint32_t b2, CUtensorMapSwizzle sw) {
  cuuint64_t dims[3] = {d0, d1, d2}, strides[2] = {s1, s2};
  cuuint32_t box[3] = {b0, b1, b2}, es[3] = {1, 1, 1};
  enc(m, CU_TENSOR_MAP_DATA_TYPE_BFLOAT16, rank, p, dims, strides, box, es, CU_TENSOR_MAP_INTERLEAVE_NONE, sw,
      CU_TENSOR_MAP_L2_PROMOTION_L2_256B, CU_TENSOR_MAP_FLOAT_OOB_FILL_NONE);
}

}

extern "C" void kernel_launch(void* const* d_in, const int* in_sizes, int n_in, void* d_out, int out_size) {
  static EncFn enc = nullptr;
  if (!enc) {
    cudaDriverEntryPointQueryResult st;
    void* fn = nullptr;
    cudaGetDriverEntryPoint("cuTensorMapEncodeTiled", &fn, cudaEnableDefault, &st);
    enc = (EncFn)fn;
    cudaFuncSetAttribute(fused_kernel, cudaFuncAttributeMaxDynamicSharedMemorySize, SMEM_BYTES);
  }
  CUtensorMap mQKV, mWO, mW1, mW2, mX;
  make_map(enc, &mQKV, d_in[1], 3, 448, 448, 3, 2688, 896, 64, 32, 3, CU_TENSOR_MAP_SWIZZLE_128B);
  make_map(enc, &mWO, d_in[3], 2, 448, 448, 1, 896, 0, 64, 112, 1, CU_TENSOR_MAP_SWIZZLE_128B);
  make_map(enc, &mW1, d_in[5], 3, 32, 448, 56, 3584, 64, 32, 32, 7, CU_TENSOR_MAP_SWIZZLE_64B);
  make_map(enc, &mW2, d_in[7], 2, 448, 1792, 1, 896, 0, 64, 112, 1, CU_TENSOR_MAP_SWIZZLE_128B);
  make_map(enc, &mX, d_in[0], 2, 448, 2048, 1, 896, 0, 64, 64, 1, CU_TENSOR_MAP_SWIZZLE_128B);
  fused_kernel<<<NCTA, 384, SMEM_BYTES, cudaStreamPerThread>>>(
      mQKV, mWO, mW1, mW2, mX, (const __nv_bfloat16*)d_in[0], (const __nv_bfloat16*)d_in[2], (const __nv_bfloat16*)d_in[6],
      (const __nv_bfloat16*)d_in[8], (const __nv_bfloat16*)d_in[3], (const __nv_bfloat16*)d_in[5],
      (const __nv_bfloat16*)d_in[7], (__nv_bfloat16*)d_out);
}
```

```cpp
#include <cuda_runtime.h>
#include <cuda_bf16.h>
#include <cuda.h>
#include <stdint.h>

namespace {

constexpr int DM = 448, NCTA = 128;
constexpr int ABYTES = 57344;
constexpr int SLOT = 14336, NSLOT = 7;
constexpr int OFF_RING = 2 * ABYTES;
constexpr int OFF_WPHI = OFF_RING + NSLOT * SLOT;
constexpr int OFF_B1 = OFF_WPHI + 8192;
constexpr int OFF_CS = OFF_B1 + 896;
constexpr int OFF_BAR = OFF_CS + 1664;
constexpr int SMEM_BYTES = OFF_BAR + 256 + 1024;
constexpr int TILES_PER_LAYER = 46;

__device__ __align__(1024) unsigned char gP[16 * 2 * 8 * 8 * 7168];
__device__ __align__(1024) unsigned char gImg[3 * 32 * ABYTES];
__device__ __align__(1024) float2 gStat[2 * 2048 * 8];
__device__ __align__(1024) float4 gKV[2 * 8 * 2 * 5 * 128];
__device__ __align__(128) unsigned gFlag[(2 * 32 * 7 + 32 + 1) * 32];
#define STAMP(i)

__device__ __forceinline__ uint32_t smem_u32(const void* p) { return (uint32_t)__cvta_generic_to_shared(p); }
__device__ __forceinline__ void mbar_init(uint32_t b, int c) { asm volatile("mbarrier.init.shared::cta.b64 [%0], %1;" ::"r"(b), "r"(c)); }
__device__ __forceinline__ void mbar_expect(uint32_t b, int bytes) { asm volatile("mbarrier.arrive.expect_tx.shared::cta.b64 _, [%0], %1;" ::"r"(b), "r"(bytes) : "memory"); }
__device__ __forceinline__ void mbar_arrive(uint32_t b) { asm volatile("mbarrier.arrive.shared::cta.b64 _, [%0];" ::"r"(b) : "memory"); }
__device__ __forceinline__ void mbar_wait(uint32_t b, int par) {
  uint32_t ok; int n = 0;
  while (true) {
    asm volatile("{.reg .pred p; mbarrier.try_wait.parity.shared::cta.b64 p, [%1], %2; selp.u32 %0,1,0,p;}" : "=r"(ok) : "r"(b), "r"(par) : "memory");
    if (ok) break;
    if (++n > (1 << 22)) break;
  }
}
__device__ __forceinline__ void flag_wait(const unsigned* f, unsigned target) {
  unsigned v; int n = 0;
  while (true) {
    asm volatile("ld.acquire.gpu.global.u32 %0, [%1];" : "=r"(v) : "l"(f) : "memory");
    if ((int)(v - target) >= 0) break;
    if (++n > (1 << 21)) break;
  }
}
__device__ __forceinline__ void flag_arrive(unsigned* f) { asm volatile("red.release.gpu.global.add.u32 [%0], 1;" ::"l"(f) : "memory"); }
__device__ __forceinline__ void fence_async() { asm volatile("fence.proxy.async.global;" ::: "memory"); }
__device__ __forceinline__ void fence_async_smem() { asm volatile("fence.proxy.async.shared::cta;" ::: "memory"); }
template <int ID, int N> __device__ __forceinline__ void bar_sync() { asm volatile("bar.sync %0, %1;" ::"n"(ID), "n"(N) : "memory"); }
__device__ __forceinline__ void bar_wg(int c) { if (c) bar_sync<2, 128>(); else bar_sync<1, 128>(); }
__device__ __forceinline__ void wg_fence() { asm volatile("wgmma.fence.sync.aligned;" ::: "memory"); }
__device__ __forceinline__ void wg_commit() { asm volatile("wgmma.commit_group.sync.aligned;" ::: "memory"); }
template <int N> __device__ __forceinline__ void wg_wait() { asm volatile("wgmma.wait_group.sync.aligned %0;" ::"n"(N) : "memory"); }
template <int N> __device__ __forceinline__ void reg_fence(float (&d)[N]) {
#pragma unroll
  for (int i = 0; i < N; i++) asm volatile("" : "+f"(d[i])::"memory");
}
template <int N> __device__ __forceinline__ void reg_def(float (&d)[N]) {
#pragma unroll
  for (int i = 0; i < N; i++) d[i] = 0.f;
}
__device__ __forceinline__ uint64_t mkdesc(uint32_t addr, uint32_t lbo, uint32_t sbo, uint64_t swz) {
  return (uint64_t)((addr & 0x3FFFF) >> 4) | ((uint64_t)(lbo >> 4) << 16) | ((uint64_t)(sbo >> 4) << 32) | (swz << 62);
}
__device__ __forceinline__ uint32_t pack(float a, float b) {
  uint32_t r; asm("cvt.rn.bf16x2.f32 %0, %1, %2;" : "=r"(r) : "f"(b), "f"(a)); return r;
}
__device__ __forceinline__ float lo(uint32_t u) { return __uint_as_float(u << 16); }
__device__ __forceinline__ float hi(uint32_t u) { return __uint_as_float(u & 0xFFFF0000u); }
__device__ __forceinline__ float ex2(float x) { float y; asm("ex2.approx.ftz.f32 %0, %1;" : "=f"(y) : "f"(x)); return y; }
__device__ __forceinline__ void stsm4(uint32_t a, uint32_t r0, uint32_t r1, uint32_t r2, uint32_t r3) {
  asm volatile("stmatrix.sync.aligned.m8n8.x4.shared.b16 [%0], {%1,%2,%3,%4};" ::"r"(a), "r"(r0), "r"(r1), "r"(r2), "r"(r3) : "memory");
}
__device__ __forceinline__ void tma3(uint32_t dst, const CUtensorMap* m, int c0, int c1, int c2, uint32_t bar) {
  asm volatile("cp.async.bulk.tensor.3d.shared::cluster.global.mbarrier::complete_tx::bytes [%0], [%1, {%3,%4,%5}], [%2];"
               ::"r"(dst), "l"(m), "r"(bar), "r"(c0), "r"(c1), "r"(c2) : "memory");
}
__device__ __forceinline__ void tma2(uint32_t dst, const CUtensorMap* m, int c0, int c1, uint32_t bar) {
  asm volatile("cp.async.bulk.tensor.2d.shared::cluster.global.mbarrier::complete_tx::bytes [%0], [%1, {%3,%4}], [%2];"
               ::"r"(dst), "l"(m), "r"(bar), "r"(c0), "r"(c1) : "memory");
}
__device__ __forceinline__ uint32_t lds32(uint32_t a) { uint32_t v; asm volatile("ld.shared.u32 %0, [%1];" : "=r"(v) : "r"(a) : "memory"); return v; }
__device__ __forceinline__ void bulk_ld(uint32_t dst, const void* src, int bytes, uint32_t bar) {
  asm volatile("cp.async.bulk.shared::cluster.global.mbarrier::complete_tx::bytes [%0], [%1], %2, [%3];" ::"r"(dst), "l"(src), "r"(bytes), "r"(bar) : "memory");
}
__device__ __forceinline__ uint4 ldcg4(const void* p) {
  uint4 v; asm volatile("ld.global.cg.v4.u32 {%0,%1,%2,%3}, [%4];" : "=r"(v.x), "=r"(v.y), "=r"(v.z), "=r"(v.w) : "l"(p) : "memory"); return v;
}

__device__ __forceinline__ void mma_ss_184(float (&d)[92], uint64_t da, uint64_t db, int acc) {
  asm volatile("{.reg .pred p; setp.ne.b32 p, %94, 0;\n"
    "wgmma.mma_async.sync.aligned.m64n184k16.f32.bf16.bf16 {%0,%1,%2,%3,%4,%5,%6,%7,%8,%9,%10,%11,%12,%13,%14,%15,%16,%17,%18,%19,%20,%21,%22,%23,%24,%25,%26,%27,%28,%29,%30,%31,%32,%33,%34,%35,%36,%37,%38,%39,%40,%41,%42,%43,%44,%45,%46,%47,%48,%49,%50,%51,%52,%53,%54,%55,%56,%57,%58,%59,%60,%61,%62,%63,%64,%65,%66,%67,%68,%69,%70,%71,%72,%73,%74,%75,%76,%77,%78,%79,%80,%81,%82,%83,%84,%85,%86,%87,%88,%89,%90,%91}, %92, %93, p, 1, 1, 0, 1;}\n"
    : "+f"(d[0]),"+f"(d[1]),"+f"(d[2]),"+f"(d[3]),"+f"(d[4]),"+f"(d[5]),"+f"(d[6]),"+f"(d[7]),"+f"(d[8]),"+f"(d[9]),"+f"(d[10]),"+f"(d[11]),"+f"(d[12]),"+f"(d[13]),"+f"(d[14]),"+f"(d[15]),"+f"(d[16]),"+f"(d[17]),"+f"(d[18]),"+f"(d[19]),"+f"(d[20]),"+f"(d[21]),"+f"(d[22]),"+f"(d[23]),"+f"(d[24]),"+f"(d[25]),"+f"(d[26]),"+f"(d[27]),"+f"(d[28]),"+f"(d[29]),"+f"(d[30]),"+f"(d[31]),"+f"(d[32]),"+f"(d[33]),"+f"(d[34]),"+f"(d[35]),"+f"(d[36]),"+f"(d[37]),"+f"(d[38]),"+f"(d[39]),"+f"(d[40]),"+f"(d[41]),"+f"(d[42]),"+f"(d[43]),"+f"(d[44]),"+f"(d[45]),"+f"(d[46]),"+f"(d[47]),"+f"(d[48]),"+f"(d[49]),"+f"(d[50]),"+f"(d[51]),"+f"(d[52]),"+f"(d[53]),"+f"(d[54]),"+f"(d[55]),"+f"(d[56]),"+f"(d[57]),"+f"(d[58]),"+f"(d[59]),"+f"(d[60]),"+f"(d[61]),"+f"(d[62]),"+f"(d[63]),"+f"(d[64]),"+f"(d[65]),"+f"(d[66]),"+f"(d[67]),"+f"(d[68]),"+f"(d[69]),"+f"(d[70]),"+f"(d[71]),"+f"(d[72]),"+f"(d[73]),"+f"(d[74]),"+f"(d[75]),"+f"(d[76]),"+f"(d[77]),"+f"(d[78]),"+f"(d[79]),"+f"(d[80]),"+f"(d[81]),"+f"(d[82]),"+f"(d[83]),"+f"(d[84]),"+f"(d[85]),"+f"(d[86]),"+f"(d[87]),"+f"(d[88]),"+f"(d[89]),"+f"(d[90]),"+f"(d[91])
    : "l"(da), "l"(db), "r"(acc));
}
__device__ __forceinline__ void mma_ss_224(float (&d)[112], uint64_t da, uint64_t db, int acc) {
  asm volatile("{.reg .pred p; setp.ne.b32 p, %114, 0;\n"
    "wgmma.mma_async.sync.aligned.m64n224k16.f32.bf16.bf16 {%0,%1,%2,%3,%4,%5,%6,%7,%8,%9,%10,%11,%12,%13,%14,%15,%16,%17,%18,%19,%20,%21,%22,%23,%24,%25,%26,%27,%28,%29,%30,%31,%32,%33,%34,%35,%36,%37,%38,%39,%40,%41,%42,%43,%44,%45,%46,%47,%48,%49,%50,%51,%52,%53,%54,%55,%56,%57,%58,%59,%60,%61,%62,%63,%64,%65,%66,%67,%68,%69,%70,%71,%72,%73,%74,%75,%76,%77,%78,%79,%80,%81,%82,%83,%84,%85,%86,%87,%88,%89,%90,%91,%92,%93,%94,%95,%96,%97,%98,%99,%100,%101,%102,%103,%104,%105,%106,%107,%108,%109,%110,%111}, %112, %113, p, 1, 1, 0, 1;}\n"
    : "+f"(d[0]),"+f"(d[1]),"+f"(d[2]),"+f"(d[3]),"+f"(d[4]),"+f"(d[5]),"+f"(d[6]),"+f"(d[7]),"+f"(d[8]),"+f"(d[9]),"+f"(d[10]),"+f"(d[11]),"+f"(d[12]),"+f"(d[13]),"+f"(d[14]),"+f"(d[15]),"+f"(d[16]),"+f"(d[17]),"+f"(d[18]),"+f"(d[19]),"+f"(d[20]),"+f"(d[21]),"+f"(d[22]),"+f"(d[23]),"+f"(d[24]),"+f"(d[25]),"+f"(d[26]),"+f"(d[27]),"+f"(d[28]),"+f"(d[29]),"+f"(d[30]),"+f"(d[31]),"+f"(d[32]),"+f"(d[33]),"+f"(d[34]),"+f"(d[35]),"+f"(d[36]),"+f"(d[37]),"+f"(d[38]),"+f"(d[39]),"+f"(d[40]),"+f"(d[41]),"+f"(d[42]),"+f"(d[43]),"+f"(d[44]),"+f"(d[45]),"+f"(d[46]),"+f"(d[47]),"+f"(d[48]),"+f"(d[49]),"+f"(d[50]),"+f"(d[51]),"+f"(d[52]),"+f"(d[53]),"+f"(d[54]),"+f"(d[55]),"+f"(d[56]),"+f"(d[57]),"+f"(d[58]),"+f"(d[59]),"+f"(d[60]),"+f"(d[61]),"+f"(d[62]),"+f"(d[63]),"+f"(d[64]),"+f"(d[65]),"+f"(d[66]),"+f"(d[67]),"+f"(d[68]),"+f"(d[69]),"+f"(d[70]),"+f"(d[71]),"+f"(d[72]),"+f"(d[73]),"+f"(d[74]),"+f"(d[75]),"+f"(d[76]),"+f"(d[77]),"+f"(d[78]),"+f"(d[79]),"+f"(d[80]),"+f"(d[81]),"+f"(d[82]),"+f"(d[83]),"+f"(d[84]),"+f"(d[85]),"+f"(d[86]),"+f"(d[87]),"+f"(d[88]),"+f"(d[89]),"+f"(d[90]),"+f"(d[91]),"+f"(d[92]),"+f"(d[93]),"+f"(d[94]),"+f"(d[95]),"+f"(d[96]),"+f"(d[97]),"+f"(d[98]),"+f"(d[99]),"+f"(d[100]),"+f"(d[101]),"+f"(d[102]),"+f"(d[103]),"+f"(d[104]),"+f"(d[105]),"+f"(d[106]),"+f"(d[107]),"+f"(d[108]),"+f"(d[109]),"+f"(d[110]),"+f"(d[111])
    : "l"(da), "l"(db), "r"(acc));
}
__device__ __forceinline__ void mma_ss_56(float (&d)[28], uint64_t da, uint64_t db, int acc) {
  asm volatile("{.reg .pred p; setp.ne.b32 p, %30, 0;\n"
    "wgmma.mma_async.sync.aligned.m64n56k16.f32.bf16.bf16 {%0,%1,%2,%3,%4,%5,%6,%7,%8,%9,%10,%11,%12,%13,%14,%15,%16,%17,%18,%19,%20,%21,%22,%23,%24,%25,%26,%27}, %28, %29, p, 1, 1, 0, 1;}\n"
    : "+f"(d[0]),"+f"(d[1]),"+f"(d[2]),"+f"(d[3]),"+f"(d[4]),"+f"(d[5]),"+f"(d[6]),"+f"(d[7]),"+f"(d[8]),"+f"(d[9]),"+f"(d[10]),"+f"(d[11]),"+f"(d[12]),"+f"(d[13]),"+f"(d[14]),"+f"(d[15]),"+f"(d[16]),"+f"(d[17]),"+f"(d[18]),"+f"(d[19]),"+f"(d[20]),"+f"(d[21]),"+f"(d[22]),"+f"(d[23]),"+f"(d[24]),"+f"(d[25]),"+f"(d[26]),"+f"(d[27])
    : "l"(da), "l"(db), "r"(acc));
}
__device__ __forceinline__ void mma_rs_56(float (&d)[28], uint32_t a0, uint32_t a1, uint32_t a2, uint32_t a3, uint64_t db, int acc) {
  asm volatile("{.reg .pred p; setp.ne.b32 p, %33, 0;\n"
    "wgmma.mma_async.sync.aligned.m64n56k16.f32.bf16.bf16 {%0,%1,%2,%3,%4,%5,%6,%7,%8,%9,%10,%11,%12,%13,%14,%15,%16,%17,%18,%19,%20,%21,%22,%23,%24,%25,%26,%27}, {%28,%29,%30,%31}, %32, p, 1, 1, 1;}\n"
    : "+f"(d[0]),"+f"(d[1]),"+f"(d[2]),"+f"(d[3]),"+f"(d[4]),"+f"(d[5]),"+f"(d[6]),"+f"(d[7]),"+f"(d[8]),"+f"(d[9]),"+f"(d[10]),"+f"(d[11]),"+f"(d[12]),"+f"(d[13]),"+f"(d[14]),"+f"(d[15]),"+f"(d[16]),"+f"(d[17]),"+f"(d[18]),"+f"(d[19]),"+f"(d[20]),"+f"(d[21]),"+f"(d[22]),"+f"(d[23]),"+f"(d[24]),"+f"(d[25]),"+f"(d[26]),"+f"(d[27])
    : "r"(a0), "r"(a1), "r"(a2), "r"(a3), "l"(db), "r"(acc));
}
__device__ __forceinline__ void mma_ss_64t(float (&d)[32], uint64_t da, uint64_t db, int acc) {
  asm volatile("{.reg .pred p; setp.ne.b32 p, %34, 0;\n"
    "wgmma.mma_async.sync.aligned.m64n64k16.f32.bf16.bf16 {%0,%1,%2,%3,%4,%5,%6,%7,%8,%9,%10,%11,%12,%13,%14,%15,%16,%17,%18,%19,%20,%21,%22,%23,%24,%25,%26,%27,%28,%29,%30,%31}, %32, %33, p, 1, 1, 1, 1;}\n"
    : "+f"(d[0]),"+f"(d[1]),"+f"(d[2]),"+f"(d[3]),"+f"(d[4]),"+f"(d[5]),"+f"(d[6]),"+f"(d[7]),"+f"(d[8]),"+f"(d[9]),"+f"(d[10]),"+f"(d[11]),"+f"(d[12]),"+f"(d[13]),"+f"(d[14]),"+f"(d[15]),"+f"(d[16]),"+f"(d[17]),"+f"(d[18]),"+f"(d[19]),"+f"(d[20]),"+f"(d[21]),"+f"(d[22]),"+f"(d[23]),"+f"(d[24]),"+f"(d[25]),"+f"(d[26]),"+f"(d[27]),"+f"(d[28]),"+f"(d[29]),"+f"(d[30]),"+f"(d[31])
    : "l"(da), "l"(db), "r"(acc));
}
__device__ __forceinline__ void mma_rs_64(float (&d)[32], uint32_t a0, uint32_t a1, uint32_t a2, uint32_t a3, uint64_t db, int acc) {
  asm volatile("{.reg .pred p; setp.ne.b32 p, %37, 0;\n"
    "wgmma.mma_async.sync.aligned.m64n64k16.f32.bf16.bf16 {%0,%1,%2,%3,%4,%5,%6,%7,%8,%9,%10,%11,%12,%13,%14,%15,%16,%17,%18,%19,%20,%21,%22,%23,%24,%25,%26,%27,%28,%29,%30,%31}, {%32,%33,%34,%35}, %36, p, 1, 1, 1;}\n"
    : "+f"(d[0]),"+f"(d[1]),"+f"(d[2]),"+f"(d[3]),"+f"(d[4]),"+f"(d[5]),"+f"(d[6]),"+f"(d[7]),"+f"(d[8]),"+f"(d[9]),"+f"(d[10]),"+f"(d[11]),"+f"(d[12]),"+f"(d[13]),"+f"(d[14]),"+f"(d[15]),"+f"(d[16]),"+f"(d[17]),"+f"(d[18]),"+f"(d[19]),"+f"(d[20]),"+f"(d[21]),"+f"(d[22]),"+f"(d[23]),"+f"(d[24]),"+f"(d[25]),"+f"(d[26]),"+f"(d[27]),"+f"(d[28]),"+f"(d[29]),"+f"(d[30]),"+f"(d[31])
    : "r"(a0), "r"(a1), "r"(a2), "r"(a3), "l"(db), "r"(acc));
}

__device__ __forceinline__ void dual_softmax(const float (&p)[28], uint32_t (&phi)[4][7]) {
  constexpr float L2E = 1.4426950408889634f;
#pragma unroll
  for (int i = 0; i < 4; i++) {
    float mx = p[i], mn = p[i];
#pragma unroll
    for (int j = 1; j < 7; j++) { mx = fmaxf(mx, p[4 * j + i]); mn = fminf(mn, p[4 * j + i]); }
    mx = fmaxf(mx, __shfl_xor_sync(~0u, mx, 1)); mn = fminf(mn, __shfl_xor_sync(~0u, mn, 1));
    mx = fmaxf(mx, __shfl_xor_sync(~0u, mx, 2)); mn = fminf(mn, __shfl_xor_sync(~0u, mn, 2));
    float a[7], b[7], sa = 0.f, sb = 0.f;
    const float mxl = mx * L2E, mnl = mn * L2E;
#pragma unroll
    for (int j = 0; j < 7; j++) {
      a[j] = ex2(fmaf(p[4 * j + i], L2E, -mxl)); b[j] = ex2(fmaf(p[4 * j + i], -L2E, mnl));
      sa += a[j]; sb += b[j];
    }
    sa += __shfl_xor_sync(~0u, sa, 1); sb += __shfl_xor_sync(~0u, sb, 1);
    sa += __shfl_xor_sync(~0u, sa, 2); sb += __shfl_xor_sync(~0u, sb, 2);
    const float ra = __fdividef(1.f, sa), rb = __fdividef(1.f, sb);
#pragma unroll
    for (int j = 0; j < 7; j++) phi[i][j] = pack(a[j] * ra, b[j] * rb);
  }
}

struct Ring {
  uint32_t full, empty, base; int slot, par;
  __device__ __forceinline__ uint32_t acquire() { mbar_wait(full + slot * 8, par); return base + slot * SLOT; }
  __device__ __forceinline__ int advance() { int s = slot; if (++slot == NSLOT) { slot = 0; par ^= 1; } return s; }
  __device__ __forceinline__ void release(int s, bool elect) { if (elect) mbar_arrive(empty + s * 8); }
};
constexpr int FL_KV = 448, FL_ZERO = FL_KV + 16, FL_DONE = FL_KV + 32;

__global__ void __launch_bounds__(384, 1)
fused_kernel(const __grid_constant__ CUtensorMap mQKV, const __grid_constant__ CUtensorMap mWO,
             const __grid_constant__ CUtensorMap mW1, const __grid_constant__ CUtensorMap mW2,
             const __grid_constant__ CUtensorMap mX,
             const __nv_bfloat16* __restrict__ x, const __nv_bfloat16* __restrict__ wphi,
             const __nv_bfloat16* __restrict__ b1, const __nv_bfloat16* __restrict__ b2,
             const __nv_bfloat16* __restrict__ wo, const __nv_bfloat16* __restrict__ w1,
             const __nv_bfloat16* __restrict__ w2, __nv_bfloat16* __restrict__ out) {
  extern __shared__ unsigned char smem_raw[];
  const uint32_t sb = (smem_u32(smem_raw) + 1023) & ~1023u;
  unsigned char* sg = smem_raw + (sb - smem_u32(smem_raw));
  const int tid = threadIdx.x, lane = tid & 31;
  const int G = blockIdx.x >> 3, r = blockIdx.x & 7;
  const uint32_t barFull = sb + OFF_BAR, barEmpty = barFull + 56, barA = barEmpty + 56, barCS = barA + 112;
  if (tid == 0) {
    for (int i = 0; i < NSLOT; i++) { mbar_init(barFull + i * 8, 1); mbar_init(barEmpty + i * 8, 5); }
    for (int i = 0; i < 14; i++) mbar_init(barA + i * 8, 1);
    mbar_init(barCS, 96); mbar_init(barCS + 8, 96);
    asm volatile("fence.mbarrier_init.release.cluster;" ::: "memory");
  }
  for (int i = tid; i < 416; i += 384) reinterpret_cast<float*>(sg + OFF_CS)[i] = 0.f;
  __syncthreads();
  const int wgid = __shfl_sync(~0u, tid >> 7, 0);
  if (wgid == 2) {
    asm volatile("setmaxnreg.dec.sync.aligned.u32 40;");
    if (tid == 256) {
      int slot = 0, par = 1;
      for (int it = 0; it < 2 * TILES_PER_LAYER; it++) {
        const int i = it >= TILES_PER_LAYER ? it - TILES_PER_LAYER : it;
        mbar_wait(barEmpty + slot * 8, par);
        const uint32_t dst = sb + OFF_RING + slot * SLOT, fb = barFull + slot * 8;
        mbar_expect(fb, i < 14 ? 12288 : SLOT);
        if (i < 14) tma3(dst, &mQKV, 56 * r, 32 * i, 0, fb);
        else if (i < 18) tma2(dst, &mWO, 56 * r, 112 * (i - 14), fb);
        else if (i < 32) tma3(dst, &mW1, 0, 32 * (i - 18), 7 * r, fb);
        else tma2(dst, &mW2, 64 * ((i - 32) >> 1), 224 * r + 112 * (i & 1), fb);
        if (it >= 32) asm volatile("mbarrier.arrive.shared::cta.b64 _, [%0], 3;" ::"r"(barEmpty + slot * 8) : "memory");
        if (++slot == NSLOT) { slot = 0; par ^= 1; }
      }
    } else if (tid >= 288) {
      if (tid >= 352) {
        if (lane < 14) {
          mbar_expect(barA + lane * 8, 8192);
          tma2(sb + lane * 8192, &mX, 64 * (lane % 7), G * 128 + 64 * (lane / 7), barA + lane * 8);
        } else if (lane < 17) {
          const char* src = lane == 14 ? (const char*)wo + blockIdx.x * 3136 : (lane == 15 ? (const char*)w1 : (const char*)w2) + blockIdx.x * 12544;
          asm volatile("cp.async.bulk.prefetch.L2.global [%0], %1;" ::"l"(src), "r"(lane == 14 ? 3136 : 12544) : "memory");
        }
        __syncwarp();
      }
      const int hw = (tid - 288) >> 5;
      float s[8];
#pragma unroll
      for (int i = 0; i < 8; i++) s[i] = 0.f;
      int slot = 0, par = 0;
#pragma unroll 1
      for (int it = 0; it < 32; it++) {
        mbar_wait(barFull + slot * 8, par);
        const bool qkv = it < 14;
        if ((qkv && lane < 24) || (it >= 18 && lane < 28)) {
          const unsigned char* base = sg + OFF_RING + slot * SLOT + (qkv ? (lane >> 3) * 4096 : (lane >> 2) * 2048);
#pragma unroll
          for (int i = 0; i < 11; i++) {
            const int row = hw + 3 * i;
            uint4 u = make_uint4(0, 0, 0, 0);
            if (row < 32) u = *reinterpret_cast<const uint4*>(base + (qkv ? row * 128 + (((lane ^ row) & 7) << 4) : row * 64 + (((lane ^ (row >> 1)) & 3) << 4)));
            s[0] += lo(u.x); s[1] += hi(u.x); s[2] += lo(u.y); s[3] += hi(u.y); s[4] += lo(u.z); s[5] += hi(u.z); s[6] += lo(u.w); s[7] += hi(u.w);
          }
        }
        __syncwarp();
        if (lane == 0) mbar_arrive(barEmpty + slot * 8);
        if (it == 13 || it == 31) {
          if (lane < (qkv ? 24 : 28)) {
#pragma unroll
            for (int i = 0; i < 8; i++) { atomicAdd(reinterpret_cast<float*>(sg + OFF_CS + (qkv ? 0 : 768)) + lane * 8 + i, s[i]); s[i] = 0.f; }
          }
          mbar_arrive(barCS + (qkv ? 0 : 8));
        }
        if (++slot == NSLOT) { slot = 0; par ^= 1; }
      }
    }
  } else {
  asm volatile("setmaxnreg.inc.sync.aligned.u32 232;");
  const int c = wgid, w = (tid >> 5) & 3, g = lane >> 2, t = lane & 3;
  const bool elect = (tid & 127) == 0;
  const uint32_t abuf = sb + c * ABYTES, barAc = barA + c * 56;
  const int row0 = G * 128 + c * 64;
  unsigned epoch;
  asm volatile("ld.relaxed.gpu.global.u32 %0, [%1];" : "=r"(epoch) : "l"(gFlag + FL_DONE * 32) : "memory");
  STAMP(24);
  float mean[2], rstd[2];
  {
    uint32_t wv[8];
#pragma unroll
    for (int i = 0; i < 8; i++) {
      const int k = i * 8 + (tid >> 5), e = k >= 28;
      wv[i] = (k < 56 && lane < 28) ? (uint32_t)__ldg(reinterpret_cast<const unsigned short*>(wphi) + (2 * r + e) * 784 + (k - 28 * e) * 28 + lane) << (16 * e) : 0u;
    }
    const float bv = tid < 224 ? __bfloat162float(b1[224 * r + tid]) : 0.f;
    if (G == 0) {
#pragma unroll 1
      for (int i = tid; i < 2 * 1280; i += 256) gKV[((i >= 1280) * 7 + r) * 1280 + i] = make_float4(0.f, 0.f, 0.f, 0.f);
    }
#pragma unroll 1
    for (int hh = 0; hh < 2; hh++) {
      const uint4* src = reinterpret_cast<const uint4*>(x + (size_t)(row0 + w * 16 + hh * 8 + g) * DM) + t;
      uint4 v[14];
#pragma unroll
      for (int k = 0; k < 14; k++) v[k] = __ldg(src + k * 4);
      float s = 0.f, q = 0.f;
#pragma unroll
      for (int k = 0; k < 14; k++) s += (lo(v[k].x) + hi(v[k].x)) + (lo(v[k].y) + hi(v[k].y)) + (lo(v[k].z) + hi(v[k].z)) + (lo(v[k].w) + hi(v[k].w));
      s += __shfl_xor_sync(~0u, s, 1); s += __shfl_xor_sync(~0u, s, 2);
      s *= 1.f / DM;
#pragma unroll
      for (int k = 0; k < 14; k++) {
        const uint32_t e[4] = {v[k].x, v[k].y, v[k].z, v[k].w};
#pragma unroll
        for (int z = 0; z < 4; z++) { float a = lo(e[z]) - s, b = hi(e[z]) - s; q = fmaf(a, a, q); q = fmaf(b, b, q); }
      }
      q += __shfl_xor_sync(~0u, q, 1); q += __shfl_xor_sync(~0u, q, 2);
      q = rsqrtf(q * (1.f / DM) + 1e-5f);
      STAMP(25 + hh);
      if (hh) { mean[1] = s; rstd[1] = q; } else { mean[0] = s; rstd[0] = q; mean[1] = 0.f; rstd[1] = 0.f; }
    }
#pragma unroll
    for (int i = 0; i < 8; i++) {
      const int k = i * 8 + (tid >> 5);
      *reinterpret_cast<uint32_t*>(sg + OFF_WPHI + k * 128 + ((g ^ (k & 7)) << 4) + t * 4) = wv[i];
    }
    if (tid < 224) reinterpret_cast<float*>(sg + OFF_B1)[tid] = bv;
    fence_async_smem();
    bar_sync<3, 256>();
    epoch = epoch / NCTA + 1;
    if (G == 0 && tid == 0) flag_arrive(gFlag + (FL_ZERO + r) * 32);
  }
  STAMP(0);
  Ring ring{barFull, barEmpty, sb + OFF_RING, 0, 0};
  int apar = 0;
  const uint32_t stsm_off = (w * 16 + ((lane >> 3) & 1) * 8 + (lane & 7)) * 128;
  const uint32_t stsm_hi = lane >> 4;
  const uint64_t dA = mkdesc(abuf, 16, 1024, 1);

  auto gather = [&](unsigned* fl, const unsigned char* img) {
    __syncwarp();
    if (lane == 0) flag_arrive(fl);
    if (elect) {
      STAMP(27);
      flag_wait(fl, epoch * 32);
      STAMP(28);
      fence_async();
      STAMP(29);
#pragma unroll 1
      for (int k = 0; k < 7; k++) { mbar_expect(barAc + k * 8, 8192); bulk_ld(abuf + k * 8192, img + k * 8192, 8192, barAc + k * 8); }
    }
    __syncwarp();
    apar ^= 1;
  };
  auto slice_off = [&](int j, int hh) -> uint32_t {
    const int ci = 7 * r + j;
    return (ci >> 3) * 8192 + (w * 16 + hh * 8 + g) * 128 + (((ci & 7) ^ g) << 4) + t * 4;
  };
  auto load_stats = [&](const float2* st) {
#pragma unroll
    for (int hh = 0; hh < 2; hh++) {
      const uint4 u = ldcg4(st + (size_t)(row0 + w * 16 + hh * 8 + g) * 8 + 2 * t);
      const float m0 = __uint_as_float(u.x), m1 = __uint_as_float(u.z);
      float m = m0 + m1;
      m += __shfl_xor_sync(~0u, m, 1); m += __shfl_xor_sync(~0u, m, 2);
      m *= 0.125f;
      float q = __uint_as_float(u.y) + __uint_as_float(u.w) + 56.f * ((m0 - m) * (m0 - m) + (m1 - m) * (m1 - m));
      q += __shfl_xor_sync(~0u, q, 1); q += __shfl_xor_sync(~0u, q, 2);
      mean[hh] = m; rstd[hh] = rsqrtf(q * (1.f / DM) + 1e-5f);
    }
  };

#pragma unroll 1
  for (int layer = 0; layer < 2; layer++) {
    unsigned* const fl = gFlag + (layer * 32 + G * 2 + c) * 7 * 32;
    uint32_t phiq[4][7], xs[7][2];
    {
      float acc[92]; reg_def(acc);
      int prev = 0;
#pragma unroll 1
      for (int st = 0; st < 14; st++) {
        if (!(st & 1)) mbar_wait(barAc + (st >> 1) * 8, apar);
        const uint64_t da = dA + (st >> 1) * 512 + (st & 1) * 4, db = mkdesc(ring.acquire(), 4096, 1024, 1);
        wg_fence();
        mma_ss_184(acc, da, db, st);
        mma_ss_184(acc, da + 2, db + 128, 1);
        wg_commit();
        if (st > 0) { wg_wait<1>(); ring.release(prev, elect); }
        prev = ring.advance();
      }
      if (layer) load_stats(gStat + 2048 * 8); else mbar_wait(barCS, 0);
#pragma unroll
      for (int j = 0; j < 7; j++) { xs[j][0] = lds32(abuf + slice_off(j, 0)); xs[j][1] = lds32(abuf + slice_off(j, 1)); }
      wg_wait<0>(); reg_fence(acc);
      ring.release(prev, elect);
      STAMP(1 + layer * 12);
      uint32_t f[3][14];
      {
        const float2* cs = reinterpret_cast<const float2*>(sg + OFF_CS) + t;
        const float mr0 = -mean[0] * rstd[0], mr1 = -mean[1] * rstd[1];
#pragma unroll
        for (int p = 0; p < 3; p++)
#pragma unroll
          for (int j = 0; j < 7; j++) {
            const float2 s = cs[p * 32 + j * 4];
            const int b = p * 32 + j * 4;
            f[p][2 * j] = pack(fmaf(acc[b], rstd[0], s.x * mr0), fmaf(acc[b + 1], rstd[0], s.y * mr0));
            f[p][2 * j + 1] = pack(fmaf(acc[b + 2], rstd[1], s.x * mr1), fmaf(acc[b + 3], rstd[1], s.y * mr1));
          }
      }
      float pk[28], pq[28]; reg_def(pk); reg_def(pq);
      const uint64_t dW = mkdesc(sb + OFF_WPHI, 4096, 1024, 1);
      wg_fence();
#pragma unroll
      for (int s = 0; s < 4; s++)
        mma_rs_56(pk, f[1][4 * s], f[1][4 * s + 1], s < 3 ? f[1][(4 * s + 2) % 14] : 0u, s < 3 ? f[1][(4 * s + 3) % 14] : 0u, dW + s * 128, s);
      wg_commit();
#pragma unroll
      for (int s = 0; s < 4; s++)
        mma_rs_56(pq, f[0][4 * s], f[0][4 * s + 1], s < 3 ? f[0][(4 * s + 2) % 14] : 0u, s < 3 ? f[0][(4 * s + 3) % 14] : 0u, dW + s * 128, s);
      wg_commit();
      bar_wg(c);
      const uint32_t srow = abuf + stsm_off, ones = t == 0 ? 0x3F803F80u : 0u;
#pragma unroll
      for (int jp = 0; jp < 4; jp++)
        stsm4(srow + 16384 + (((2 * jp + stsm_hi) ^ (lane & 7)) << 4), f[2][4 * jp], f[2][4 * jp + 1],
              jp < 3 ? f[2][(4 * jp + 2) % 14] : ones, jp < 3 ? f[2][(4 * jp + 3) % 14] : ones);
      wg_wait<0>(); reg_fence(pk); reg_fence(pq);
#pragma unroll 1
      for (int pass = 0; pass < 2; pass++) {
        dual_softmax(pk, phiq);
        if (pass) break;
#pragma unroll
        for (int e = 0; e < 2; e++)
#pragma unroll
          for (int jp = 0; jp < 4; jp++)
            stsm4(srow + e * 8192 + (((2 * jp + stsm_hi) ^ (lane & 7)) << 4), phiq[e][2 * jp], phiq[2 + e][2 * jp],
                  jp < 3 ? phiq[e][(2 * jp + 1) % 7] : 0u, jp < 3 ? phiq[2 + e][(2 * jp + 1) % 7] : 0u);
        fence_async_smem();
        bar_sync<3, 256>();
        float kv[32]; reg_def(kv);
        const uint64_t dP = mkdesc(sb + c * 8192, 4096, 1024, 1), dV = mkdesc(sb + 16384, 4096, 1024, 1);
        wg_fence();
#pragma unroll
        for (int s = 0; s < 8; s++) mma_ss_64t(kv, dP + (s >> 2) * (ABYTES / 16) + (s & 3) * 128, dV + (s >> 2) * (ABYTES / 16) + (s & 3) * 128, s);
        wg_commit();
        if (layer == 0 && lane == 0) flag_wait(gFlag + (FL_ZERO + r) * 32, epoch);
        __syncwarp();
        wg_wait<0>(); reg_fence(kv);
        float4* kvg = gKV + ((layer * 8 + r) * 2 + c) * 640 + (tid & 127);
#pragma unroll
        for (int i = 0; i < 5; i++) {
          float v0, v1, v2, v3;
          if (i == 4) { v0 = kv[28]; v1 = kv[29]; v2 = kv[30]; v3 = kv[31]; }
          else { v0 = c ? kv[12 + 4 * i] : kv[4 * i]; v1 = c ? kv[13 + 4 * i] : kv[1 + 4 * i]; v2 = c ? kv[14 + 4 * i] : kv[2 + 4 * i]; v3 = c ? kv[15 + 4 * i] : kv[3 + 4 * i]; }
          const bool use = i == 4 ? t == 0 : (i == 0 ? (c == 0 || t >= 2) : (i == 3 ? (c == 1 || t < 2) : true));
          if (use) asm volatile("red.relaxed.gpu.global.add.v4.f32 [%0], {%1,%2,%3,%4};" ::"l"(kvg + i * 128), "f"(v0), "f"(v1), "f"(v2), "f"(v3) : "memory");
        }
        __syncwarp();
        if (lane == 0) flag_arrive(gFlag + (FL_KV + layer * 8 + r) * 32);
        __syncwarp();
        STAMP(2 + layer * 12);
#pragma unroll
        for (int i = 0; i < 28; i++) pk[i] = pq[i];
      }
    }
    {
      if (elect) flag_wait(gFlag + (FL_KV + layer * 8 + r) * 32, epoch * 128);
      bar_wg(c);
      STAMP(3 + layer * 12);
      const float4* kvg = gKV + (layer * 8 + r) * 1280 + (tid & 127);
      uint4 kk[2][5];
#pragma unroll
      for (int e = 0; e < 2; e++)
#pragma unroll
        for (int i = 0; i < 5; i++) kk[e][i] = ldcg4(kvg + e * 640 + i * 128);
      const uint32_t srow = abuf + 24576 + stsm_off;
#pragma unroll
      for (int e = 0; e < 2; e++) {
        uint32_t f[8][2];
#pragma unroll
        for (int j = 0; j < 8; j++) { f[j][0] = 0u; f[j][1] = 0u; }
#pragma unroll
        for (int i = 0; i < 4; i++) {
          f[i + 3 * e][0] = pack(__uint_as_float(kk[e][i].x), __uint_as_float(kk[e][i].y));
          f[i + 3 * e][1] = pack(__uint_as_float(kk[e][i].z), __uint_as_float(kk[e][i].w));
        }
        f[7][0] = e ? pack(0.f, __uint_as_float(kk[e][4].y)) : pack(__uint_as_float(kk[e][4].x), 0.f);
        f[7][1] = e ? pack(0.f, __uint_as_float(kk[e][4].w)) : pack(__uint_as_float(kk[e][4].z), 0.f);
#pragma unroll
        for (int jp = 0; jp < 4; jp++)
          stsm4(srow + e * 8192 + (((2 * jp + stsm_hi) ^ (lane & 7)) << 4), f[2 * jp][0], f[2 * jp][1], f[2 * jp + 1][0], f[2 * jp + 1][1]);
      }
      fence_async_smem();
      bar_wg(c);
      float num[32]; reg_def(num);
      const uint64_t dK = mkdesc(abuf + 24576, 4096, 1024, 1);
      wg_fence();
#pragma unroll
      for (int e = 0; e < 2; e++)
#pragma unroll
        for (int s = 0; s < 4; s++)
          mma_rs_64(num, phiq[e][2 * s], phiq[2 + e][2 * s], s < 3 ? phiq[e][(2 * s + 1) % 7] : 0u, s < 3 ? phiq[2 + e][(2 * s + 1) % 7] : 0u,
                    dK + e * 512 + s * 128, e + s);
      wg_commit();
      wg_wait<0>(); reg_fence(num);
      float rd[4];
#pragma unroll
      for (int i = 0; i < 4; i++) rd[i] = __fdividef(1.f, __shfl_sync(~0u, num[28 + i], lane & ~3) + 1e-6f);
      unsigned char* img = gImg + (size_t)(G * 2 + c) * ABYTES;
#pragma unroll
      for (int j = 0; j < 7; j++) {
        const bool hb = j > 3 || (j == 3 && t >= 2);
        const float r0 = hb ? rd[1] : rd[0], r1 = hb ? rd[3] : rd[2];
        *reinterpret_cast<uint32_t*>(img + slice_off(j, 0)) = pack(num[4 * j] * r0, num[4 * j + 1] * r0);
        *reinterpret_cast<uint32_t*>(img + slice_off(j, 1)) = pack(num[4 * j + 2] * r1, num[4 * j + 3] * r1);
      }
      STAMP(4 + layer * 12);
      gather(fl, img);
      STAMP(5 + layer * 12);
    }
    {
      float acc[28]; reg_def(acc);
      int prev = 0;
#pragma unroll 1
      for (int st = 0; st < 4; st++) {
        mbar_wait(barAc + (st * 7 + 3) / 4 * 8, apar);
        mbar_wait(barAc + (st * 7 + 6) / 4 * 8, apar);
        const uint64_t db = mkdesc(ring.acquire(), 4096, 1024, 1);
        wg_fence();
#pragma unroll
        for (int s = 0; s < 7; s++) { const int ks = st * 7 + s; mma_ss_56(acc, dA + (ks >> 2) * 512 + (ks & 3) * 2, db + s * 128, ks); }
        wg_commit();
        if (st > 0) { wg_wait<1>(); ring.release(prev, elect); }
        prev = ring.advance();
      }
      wg_wait<0>(); reg_fence(acc);
      ring.release(prev, elect);
      unsigned char* img = gImg + (size_t)(32 + G * 2 + c) * ABYTES;
#pragma unroll
      for (int hh = 0; hh < 2; hh++) {
        float s = 0.f, q = 0.f;
#pragma unroll
        for (int j = 0; j < 7; j++) {
          xs[j][hh] = pack(lo(xs[j][hh]) + acc[4 * j + 2 * hh], hi(xs[j][hh]) + acc[4 * j + 2 * hh + 1]);
          *reinterpret_cast<uint32_t*>(img + slice_off(j, hh)) = xs[j][hh];
          s += lo(xs[j][hh]) + hi(xs[j][hh]);
        }
        s += __shfl_xor_sync(~0u, s, 1); s += __shfl_xor_sync(~0u, s, 2);
        s *= 1.f / 56.f;
#pragma unroll
        for (int j = 0; j < 7; j++) { const float a = lo(xs[j][hh]) - s, b = hi(xs[j][hh]) - s; q = fmaf(a, a, q); q = fmaf(b, b, q); }
        q += __shfl_xor_sync(~0u, q, 1); q += __shfl_xor_sync(~0u, q, 2);
        if (t == 0) gStat[(size_t)(row0 + w * 16 + hh * 8 + g) * 8 + r] = make_float2(s, q);
      }
      STAMP(6 + layer * 12);
      gather(fl + 32, img);
      STAMP(7 + layer * 12);
    }
    {
      uint32_t hf[28][2];
      {
        float acc[112]; reg_def(acc);
        int prev = 0;
#pragma unroll 1
        for (int st = 0; st < 14; st++) {
          if (!(st & 1)) mbar_wait(barAc + (st >> 1) * 8, apar);
          const uint64_t da = dA + (st >> 1) * 512 + (st & 1) * 4, db = mkdesc(ring.acquire(), 2048, 512, 2);
          wg_fence();
          mma_ss_224(acc, da, db, st);
          mma_ss_224(acc, da + 2, db + 64, 1);
          wg_commit();
          if (st > 0) { wg_wait<1>(); ring.release(prev, elect); }
          prev = ring.advance();
        }
        load_stats(gStat);
        mbar_wait(barCS + 8, 0);
        wg_wait<0>(); reg_fence(acc);
        ring.release(prev, elect);
        STAMP(8 + layer * 12);
        const float2* bs = reinterpret_cast<const float2*>(sg + OFF_B1) + t;
        const float2* cs = reinterpret_cast<const float2*>(sg + OFF_CS + 768) + t;
        const float mr0 = -mean[0] * rstd[0], mr1 = -mean[1] * rstd[1];
#pragma unroll
        for (int j = 0; j < 28; j++) {
          const float2 b = bs[4 * j], s = cs[4 * j];
          const float h0 = fmaxf(fmaf(acc[4 * j], rstd[0], fmaf(s.x, mr0, b.x)), 0.f), h1 = fmaxf(fmaf(acc[4 * j + 1], rstd[0], fmaf(s.y, mr0, b.y)), 0.f);
          const float h2 = fmaxf(fmaf(acc[4 * j + 2], rstd[1], fmaf(s.x, mr1, b.x)), 0.f), h3 = fmaxf(fmaf(acc[4 * j + 3], rstd[1], fmaf(s.y, mr1, b.y)), 0.f);
          hf[j][0] = pack(h0 * h0, h1 * h1); hf[j][1] = pack(h2 * h2, h3 * h3);
        }
      }
      unsigned char* pdst = gP + (size_t)(((G * 2 + c) * 8 + 2 * w) * 8 + r) * 7168 + (g * 56 + t) * 16;
      uint4 pk[4] = {};
#pragma unroll 1
      for (int ch = 0; ch < 7; ch++) {
        float acc[32]; reg_def(acc);
        int sl0 = 0, sl1 = 0;
#pragma unroll
        for (int hk = 0; hk < 2; hk++) {
          const uint64_t db = mkdesc(ring.acquire(), 4096, 1024, 1);
          wg_fence();
#pragma unroll
          for (int s = 0; s < 7; s++) { const int ks = hk * 7 + s; mma_rs_64(acc, hf[2 * ks][0], hf[2 * ks][1], hf[2 * ks + 1][0], hf[2 * ks + 1][1], db + s * 128, ks); }
          wg_commit();
          if (hk) sl1 = ring.advance(); else sl0 = ring.advance();
        }
        if (ch > 0) {
#pragma unroll
          for (int i = 0; i < 4; i++) *reinterpret_cast<uint4*>(pdst + (i & 1) * (8 * 7168) + (i >> 1) * 64) = pk[i];
          pdst += 128;
        }
        wg_wait<1>(); ring.release(sl0, elect);
        wg_wait<0>(); reg_fence(acc); ring.release(sl1, elect);
#pragma unroll
        for (int i = 0; i < 4; i++) {
          const int b = (i >> 1) * 16 + (i & 1) * 2;
          pk[i] = make_uint4(pack(acc[b], acc[b + 1]), pack(acc[b + 4], acc[b + 5]), pack(acc[b + 8], acc[b + 9]), pack(acc[b + 12], acc[b + 13]));
        }
      }
#pragma unroll
      for (int i = 0; i < 4; i++) *reinterpret_cast<uint4*>(pdst + (i & 1) * (8 * 7168) + (i >> 1) * 64) = pk[i];
      STAMP(9 + layer * 12);
    }
    {
      __syncwarp();
      if (lane == 0) { flag_arrive(fl + (3 + w) * 32); flag_wait(fl + (3 + (r >> 1)) * 32, epoch * 8); }
      __syncwarp();
      STAMP(10 + layer * 12);
      const unsigned char* psrc = gP + (size_t)(((G * 2 + c) * 8 + r) * 8) * 7168 + (w * 2 * 56 + lane) * 16;
      unsigned char* img = gImg + (size_t)(64 + G * 2 + c) * ABYTES;
      float y[4][8];
      uint32_t off[4];
      if (lane < 28) {
        uint4 pv[8][4];
#pragma unroll
        for (int s = 0; s < 8; s++)
#pragma unroll
          for (int i = 0; i < 4; i++) pv[s][i] = ldcg4(psrc + s * 7168 + i * 448);
#pragma unroll
        for (int i = 0; i < 4; i++) {
          const int unit = g + 7 * (i & 1), row = r * 8 + w * 2 + (i >> 1);
          off[i] = (unit >> 1) * 8192 + row * 128 + ((((unit & 1) * 4) ^ (row & 7)) << 4) + t * 4;
#pragma unroll
          for (int jj = 0; jj < 4; jj++) {
            const uint32_t bb = __ldg(reinterpret_cast<const uint32_t*>(b2 + unit * 32 + jj * 8 + 2 * t)), xo = lds32(abuf + (off[i] ^ (jj << 4)));
            y[i][2 * jj] = lo(bb) + lo(xo); y[i][2 * jj + 1] = hi(bb) + hi(xo);
          }
        }
#pragma unroll
        for (int s = 0; s < 8; s++)
#pragma unroll
          for (int i = 0; i < 4; i++) {
            y[i][0] += lo(pv[s][i].x); y[i][1] += hi(pv[s][i].x); y[i][2] += lo(pv[s][i].y); y[i][3] += hi(pv[s][i].y);
            y[i][4] += lo(pv[s][i].z); y[i][5] += hi(pv[s][i].z); y[i][6] += lo(pv[s][i].w); y[i][7] += hi(pv[s][i].w);
          }
#pragma unroll
        for (int i = 0; i < 4; i++)
#pragma unroll
          for (int jj = 0; jj < 4; jj++) {
            const uint32_t v = pack(y[i][2 * jj], y[i][2 * jj + 1]);
            y[i][2 * jj] = lo(v); y[i][2 * jj + 1] = hi(v);
            unsigned char* dst = layer ? reinterpret_cast<unsigned char*>(out + (size_t)(row0 + r * 8 + w * 2 + (i >> 1)) * DM + (g + 7 * (i & 1)) * 32 + jj * 8 + 2 * t)
                                       : img + (off[i] ^ (jj << 4));
            *reinterpret_cast<uint32_t*>(dst) = v;
          }
      } else {
#pragma unroll
        for (int i = 0; i < 32; i++) y[i >> 3][i & 7] = 0.f;
      }
      if (layer) break;
      float s0 = 0.f, s1 = 0.f, q0 = 0.f, q1 = 0.f;
#pragma unroll
      for (int i = 0; i < 16; i++) { s0 += y[i >> 3][i & 7]; s1 += y[2 + (i >> 3)][i & 7]; }
#pragma unroll
      for (int o = 16; o; o >>= 1) { s0 += __shfl_xor_sync(~0u, s0, o); s1 += __shfl_xor_sync(~0u, s1, o); }
      s0 *= 1.f / DM; s1 *= 1.f / DM;
      if (lane < 28) {
#pragma unroll
        for (int i = 0; i < 16; i++) { const float a = y[i >> 3][i & 7] - s0, b = y[2 + (i >> 3)][i & 7] - s1; q0 = fmaf(a, a, q0); q1 = fmaf(b, b, q1); }
      }
#pragma unroll
      for (int o = 16; o; o >>= 1) { q0 += __shfl_xor_sync(~0u, q0, o); q1 += __shfl_xor_sync(~0u, q1, o); }
      if (lane < 16) gStat[(size_t)(2048 + row0 + r * 8 + w * 2) * 8 + lane] = lane < 8 ? make_float2(s0, q0 * 0.125f) : make_float2(s1, q1 * 0.125f);
      STAMP(11);
      gather(fl + 64, img);
      STAMP(12);
    }
  }
  STAMP(30);
  if (tid == 0) asm volatile("red.relaxed.gpu.global.add.u32 [%0], 1;" ::"l"(gFlag + FL_DONE * 32) : "memory");
  }
}

typedef CUresult (*EncFn)(CUtensorMap*, CUtensorMapDataType, cuuint32_t, void*, const cuuint64_t*, const cuuint64_t*,
                          const cuuint32_t*, const cuuint32_t*, CUtensorMapInterleave, CUtensorMapSwizzle,
                          CUtensorMapL2promotion, CUtensorMapFloatOOBfill);

void make_map(EncFn enc, CUtensorMap* m, void* p, int rank, uint64_t d0, uint64_t d1, uint64_t d2, uint64_t s1, uint64_t s2,
              uint32_t b0, uint32_t b1, uint32_t b2, CUtensorMapSwizzle sw) {
  cuuint64_t dims[3] = {d0, d1, d2}, strides[2] = {s1, s2};
  cuuint32_t box[3] = {b0, b1, b2}, es[3] = {1, 1, 1};
  enc(m, CU_TENSOR_MAP_DATA_TYPE_BFLOAT16, rank, p, dims, strides, box, es, CU_TENSOR_MAP_INTERLEAVE_NONE, sw,
      CU_TENSOR_MAP_L2_PROMOTION_L2_256B, CU_TENSOR_MAP_FLOAT_OOB_FILL_NONE);
}

}

extern "C" void kernel_launch(void* const* d_in, const int* in_sizes, int n_in, void* d_out, int out_size) {
  static EncFn enc = nullptr;
  if (!enc) {
    cudaDriverEntryPointQueryResult st;
    void* fn = nullptr;
    cudaGetDriverEntryPoint("cuTensorMapEncodeTiled", &fn, cudaEnableDefault, &st);
    enc = (EncFn)fn;
    cudaFuncSetAttribute(fused_kernel, cudaFuncAttributeMaxDynamicSharedMemorySize, SMEM_BYTES);
  }
  CUtensorMap mQKV, mWO, mW1, mW2, mX;
  make_map(enc, &mQKV, d_in[1], 3, 448, 448, 3, 2688, 896, 64, 32, 3, CU_TENSOR_MAP_SWIZZLE_128B);
  make_map(enc, &mWO, d_in[3], 2, 448, 448, 1, 896, 0, 64, 112, 1, CU_TENSOR_MAP_SWIZZLE_128B);
  make_map(enc, &mW1, d_in[5], 3, 32, 448, 56, 3584, 64, 32, 32, 7, CU_TENSOR_MAP_SWIZZLE_64B);
  make_map(enc, &mW2, d_in[7], 2, 448, 1792, 1, 896, 0, 64, 112, 1, CU_TENSOR_MAP_SWIZZLE_128B);
  make_map(enc, &mX, d_in[0], 2, 448, 2048, 1, 896, 0, 64, 64, 1, CU_TENSOR_MAP_SWIZZLE_128B);
  fused_kernel<<<NCTA, 384, SMEM_BYTES, cudaStreamPerThread>>>(
      mQKV, mWO, mW1, mW2, mX, (const __nv_bfloat16*)d_in[0], (const __nv_bfloat16*)d_in[2], (const __nv_bfloat16*)d_in[6],
      (const __nv_bfloat16*)d_in[8], (const __nv_bfloat16*)d_in[3], (const __nv_bfloat16*)d_in[5],
      (const __nv_bfloat16*)d_in[7], (__nv_bfloat16*)d_out);
}
```

```cpp
#include <cuda_runtime.h>
#include <cuda_bf16.h>
#include <cuda.h>
#include <stdint.h>

namespace {

constexpr int DM = 448, NCTA = 128;
constexpr int ABYTES = 57344;
constexpr int SLOT = 14336, NSLOT = 7;
constexpr int OFF_RING = 2 * ABYTES;
constexpr int OFF_WPHI = OFF_RING + NSLOT * SLOT;
constexpr int OFF_B1 = OFF_WPHI + 8192;
constexpr int OFF_CS = OFF_B1 + 896;
constexpr int OFF_CS0 = OFF_CS + 1664;
constexpr int OFF_BAR = OFF_CS0 + 1664;
constexpr int SMEM_BYTES = OFF_BAR + 256 + 1024;
constexpr int TILES_PER_LAYER = 46;

__device__ __align__(1024) unsigned char gP[16 * 2 * 8 * 8 * 7168];
__device__ __align__(1024) unsigned char gImg[3 * 32 * ABYTES];
__device__ __align__(1024) float2 gStat[2 * 2048 * 8];
__device__ __align__(1024) float4 gKV[2 * 8 * 2 * 5 * 128];
__device__ __align__(1024) float4 gCS[8 * 16 * 104];
__device__ __align__(128) unsigned gFlag[(2 * 32 * 7 + 32 + 1) * 32];
#define STAMP(i)

__device__ __forceinline__ uint32_t smem_u32(const void* p) { return (uint32_t)__cvta_generic_to_shared(p); }
__device__ __forceinline__ void mbar_init(uint32_t b, int c) { asm volatile("mbarrier.init.shared::cta.b64 [%0], %1;" ::"r"(b), "r"(c)); }
__device__ __forceinline__ void mbar_expect(uint32_t b, int bytes) { asm volatile("mbarrier.arrive.expect_tx.shared::cta.b64 _, [%0], %1;" ::"r"(b), "r"(bytes) : "memory"); }
__device__ __forceinline__ void mbar_arrive(uint32_t b) { asm volatile("mbarrier.arrive.shared::cta.b64 _, [%0];" ::"r"(b) : "memory"); }
__device__ __forceinline__ void mbar_wait(uint32_t b, int par) {
  uint32_t ok; int n = 0;
  while (true) {
    asm volatile("{.reg .pred p; mbarrier.try_wait.parity.shared::cta.b64 p, [%1], %2; selp.u32 %0,1,0,p;}" : "=r"(ok) : "r"(b), "r"(par) : "memory");
    if (ok) break;
    if (++n > (1 << 22)) break;
  }
}
__device__ __forceinline__ void flag_wait(const unsigned* f, unsigned target) {
  unsigned v; int n = 0;
  while (true) {
    asm volatile("ld.acquire.gpu.global.u32 %0, [%1];" : "=r"(v) : "l"(f) : "memory");
    if ((int)(v - target) >= 0) break;
    if (++n > (1 << 21)) break;
  }
}
__device__ __forceinline__ void flag_arrive(unsigned* f) { asm volatile("red.release.gpu.global.add.u32 [%0], 1;" ::"l"(f) : "memory"); }
__device__ __forceinline__ void fence_async() { asm volatile("fence.proxy.async.global;" ::: "memory"); }
__device__ __forceinline__ void fence_async_smem() { asm volatile("fence.proxy.async.shared::cta;" ::: "memory"); }
template <int ID, int N> __device__ __forceinline__ void bar_sync() { asm volatile("bar.sync %0, %1;" ::"n"(ID), "n"(N) : "memory"); }
__device__ __forceinline__ void bar_wg(int c) { if (c) bar_sync<2, 128>(); else bar_sync<1, 128>(); }
__device__ __forceinline__ void wg_fence() { asm volatile("wgmma.fence.sync.aligned;" ::: "memory"); }
__device__ __forceinline__ void wg_commit() { asm volatile("wgmma.commit_group.sync.aligned;" ::: "memory"); }
template <int N> __device__ __forceinline__ void wg_wait() { asm volatile("wgmma.wait_group.sync.aligned %0;" ::"n"(N) : "memory"); }
template <int N> __device__ __forceinline__ void reg_fence(float (&d)[N]) {
#pragma unroll
  for (int i = 0; i < N; i++) asm volatile("" : "+f"(d[i])::"memory");
}
template <int N> __device__ __forceinline__ void reg_def(float (&d)[N]) {
#pragma unroll
  for (int i = 0; i < N; i++) d[i] = 0.f;
}
__device__ __forceinline__ uint64_t mkdesc(uint32_t addr, uint32_t lbo, uint32_t sbo, uint64_t swz) {
  return (uint64_t)((addr & 0x3FFFF) >> 4) | ((uint64_t)(lbo >> 4) << 16) | ((uint64_t)(sbo >> 4) << 32) | (swz << 62);
}
__device__ __forceinline__ uint32_t pack(float a, float b) {
  uint32_t r; asm("cvt.rn.bf16x2.f32 %0, %1, %2;" : "=r"(r) : "f"(b), "f"(a)); return r;
}
__device__ __forceinline__ float lo(uint32_t u) { return __uint_as_float(u << 16); }
__device__ __forceinline__ float hi(uint32_t u) { return __uint_as_float(u & 0xFFFF0000u); }
__device__ __forceinline__ float ex2(float x) { float y; asm("ex2.approx.ftz.f32 %0, %1;" : "=f"(y) : "f"(x)); return y; }
__device__ __forceinline__ void stsm4(uint32_t a, uint32_t r0, uint32_t r1, uint32_t r2, uint32_t r3) {
  asm volatile("stmatrix.sync.aligned.m8n8.x4.shared.b16 [%0], {%1,%2,%3,%4};" ::"r"(a), "r"(r0), "r"(r1), "r"(r2), "r"(r3) : "memory");
}
__device__ __forceinline__ void tma3(uint32_t dst, const CUtensorMap* m, int c0, int c1, int c2, uint32_t bar) {
  asm volatile("cp.async.bulk.tensor.3d.shared::cluster.global.mbarrier::complete_tx::bytes [%0], [%1, {%3,%4,%5}], [%2];"
               ::"r"(dst), "l"(m), "r"(bar), "r"(c0), "r"(c1), "r"(c2) : "memory");
}
__device__ __forceinline__ void tma2(uint32_t dst, const CUtensorMap* m, int c0, int c1, uint32_t bar) {
  asm volatile("cp.async.bulk.tensor.2d.shared::cluster.global.mbarrier::complete_tx::bytes [%0], [%1, {%3,%4}], [%2];"
               ::"r"(dst), "l"(m), "r"(bar), "r"(c0), "r"(c1) : "memory");
}
__device__ __forceinline__ uint32_t lds32(uint32_t a) { uint32_t v; asm volatile("ld.shared.u32 %0, [%1];" : "=r"(v) : "r"(a) : "memory"); return v; }
__device__ __forceinline__ void bulk_ld(uint32_t dst, const void* src, int bytes, uint32_t bar) {
  asm volatile("cp.async.bulk.shared::cluster.global.mbarrier::complete_tx::bytes [%0], [%1], %2, [%3];" ::"r"(dst), "l"(src), "r"(bytes), "r"(bar) : "memory");
}
__device__ __forceinline__ uint4 ldcg4(const void* p) {
  uint4 v; asm volatile("ld.global.cg.v4.u32 {%0,%1,%2,%3}, [%4];" : "=r"(v.x), "=r"(v.y), "=r"(v.z), "=r"(v.w) : "l"(p) : "memory"); return v;
}

__device__ __forceinline__ uint2 ldcg2(const void* p) {
  uint2 v; asm volatile("ld.global.cg.v2.u32 {%0,%1}, [%2];" : "=r"(v.x), "=r"(v.y) : "l"(p) : "memory"); return v;
}

__device__ __forceinline__ void mma_ss_184(float (&d)[92], uint64_t da, uint64_t db, int acc) {
  asm volatile("{.reg .pred p; setp.ne.b32 p, %94, 0;\n"
    "wgmma.mma_async.sync.aligned.m64n184k16.f32.bf16.bf16 {%0,%1,%2,%3,%4,%5,%6,%7,%8,%9,%10,%11,%12,%13,%14,%15,%16,%17,%18,%19,%20,%21,%22,%23,%24,%25,%26,%27,%28,%29,%30,%31,%32,%33,%34,%35,%36,%37,%38,%39,%40,%41,%42,%43,%44,%45,%46,%47,%48,%49,%50,%51,%52,%53,%54,%55,%56,%57,%58,%59,%60,%61,%62,%63,%64,%65,%66,%67,%68,%69,%70,%71,%72,%73,%74,%75,%76,%77,%78,%79,%80,%81,%82,%83,%84,%85,%86,%87,%88,%89,%90,%91}, %92, %93, p, 1, 1, 0, 1;}\n"
    : "+f"(d[0]),"+f"(d[1]),"+f"(d[2]),"+f"(d[3]),"+f"(d[4]),"+f"(d[5]),"+f"(d[6]),"+f"(d[7]),"+f"(d[8]),"+f"(d[9]),"+f"(d[10]),"+f"(d[11]),"+f"(d[12]),"+f"(d[13]),"+f"(d[14]),"+f"(d[15]),"+f"(d[16]),"+f"(d[17]),"+f"(d[18]),"+f"(d[19]),"+f"(d[20]),"+f"(d[21]),"+f"(d[22]),"+f"(d[23]),"+f"(d[24]),"+f"(d[25]),"+f"(d[26]),"+f"(d[27]),"+f"(d[28]),"+f"(d[29]),"+f"(d[30]),"+f"(d[31]),"+f"(d[32]),"+f"(d[33]),"+f"(d[34]),"+f"(d[35]),"+f"(d[36]),"+f"(d[37]),"+f"(d[38]),"+f"(d[39]),"+f"(d[40]),"+f"(d[41]),"+f"(d[42]),"+f"(d[43]),"+f"(d[44]),"+f"(d[45]),"+f"(d[46]),"+f"(d[47]),"+f"(d[48]),"+f"(d[49]),"+f"(d[50]),"+f"(d[51]),"+f"(d[52]),"+f"(d[53]),"+f"(d[54]),"+f"(d[55]),"+f"(d[56]),"+f"(d[57]),"+f"(d[58]),"+f"(d[59]),"+f"(d[60]),"+f"(d[61]),"+f"(d[62]),"+f"(d[63]),"+f"(d[64]),"+f"(d[65]),"+f"(d[66]),"+f"(d[67]),"+f"(d[68]),"+f"(d[69]),"+f"(d[70]),"+f"(d[71]),"+f"(d[72]),"+f"(d[73]),"+f"(d[74]),"+f"(d[75]),"+f"(d[76]),"+f"(d[77]),"+f"(d[78]),"+f"(d[79]),"+f"(d[80]),"+f"(d[81]),"+f"(d[82]),"+f"(d[83]),"+f"(d[84]),"+f"(d[85]),"+f"(d[86]),"+f"(d[87]),"+f"(d[88]),"+f"(d[89]),"+f"(d[90]),"+f"(d[91])
    : "l"(da), "l"(db), "r"(acc));
}
__device__ __forceinline__ void mma_ss_224(float (&d)[112], uint64_t da, uint64_t db, int acc) {
  asm volatile("{.reg .pred p; setp.ne.b32 p, %114, 0;\n"
    "wgmma.mma_async.sync.aligned.m64n224k16.f32.bf16.bf16 {%0,%1,%2,%3,%4,%5,%6,%7,%8,%9,%10,%11,%12,%13,%14,%15,%16,%17,%18,%19,%20,%21,%22,%23,%24,%25,%26,%27,%28,%29,%30,%31,%32,%33,%34,%35,%36,%37,%38,%39,%40,%41,%42,%43,%44,%45,%46,%47,%48,%49,%50,%51,%52,%53,%54,%55,%56,%57,%58,%59,%60,%61,%62,%63,%64,%65,%66,%67,%68,%69,%70,%71,%72,%73,%74,%75,%76,%77,%78,%79,%80,%81,%82,%83,%84,%85,%86,%87,%88,%89,%90,%91,%92,%93,%94,%95,%96,%97,%98,%99,%100,%101,%102,%103,%104,%105,%106,%107,%108,%109,%110,%111}, %112, %113, p, 1, 1, 0, 1;}\n"
    : "+f"(d[0]),"+f"(d[1]),"+f"(d[2]),"+f"(d[3]),"+f"(d[4]),"+f"(d[5]),"+f"(d[6]),"+f"(d[7]),"+f"(d[8]),"+f"(d[9]),"+f"(d[10]),"+f"(d[11]),"+f"(d[12]),"+f"(d[13]),"+f"(d[14]),"+f"(d[15]),"+f"(d[16]),"+f"(d[17]),"+f"(d[18]),"+f"(d[19]),"+f"(d[20]),"+f"(d[21]),"+f"(d[22]),"+f"(d[23]),"+f"(d[24]),"+f"(d[25]),"+f"(d[26]),"+f"(d[27]),"+f"(d[28]),"+f"(d[29]),"+f"(d[30]),"+f"(d[31]),"+f"(d[32]),"+f"(d[33]),"+f"(d[34]),"+f"(d[35]),"+f"(d[36]),"+f"(d[37]),"+f"(d[38]),"+f"(d[39]),"+f"(d[40]),"+f"(d[41]),"+f"(d[42]),"+f"(d[43]),"+f"(d[44]),"+f"(d[45]),"+f"(d[46]),"+f"(d[47]),"+f"(d[48]),"+f"(d[49]),"+f"(d[50]),"+f"(d[51]),"+f"(d[52]),"+f"(d[53]),"+f"(d[54]),"+f"(d[55]),"+f"(d[56]),"+f"(d[57]),"+f"(d[58]),"+f"(d[59]),"+f"(d[60]),"+f"(d[61]),"+f"(d[62]),"+f"(d[63]),"+f"(d[64]),"+f"(d[65]),"+f"(d[66]),"+f"(d[67]),"+f"(d[68]),"+f"(d[69]),"+f"(d[70]),"+f"(d[71]),"+f"(d[72]),"+f"(d[73]),"+f"(d[74]),"+f"(d[75]),"+f"(d[76]),"+f"(d[77]),"+f"(d[78]),"+f"(d[79]),"+f"(d[80]),"+f"(d[81]),"+f"(d[82]),"+f"(d[83]),"+f"(d[84]),"+f"(d[85]),"+f"(d[86]),"+f"(d[87]),"+f"(d[88]),"+f"(d[89]),"+f"(d[90]),"+f"(d[91]),"+f"(d[92]),"+f"(d[93]),"+f"(d[94]),"+f"(d[95]),"+f"(d[96]),"+f"(d[97]),"+f"(d[98]),"+f"(d[99]),"+f"(d[100]),"+f"(d[101]),"+f"(d[102]),"+f"(d[103]),"+f"(d[104]),"+f"(d[105]),"+f"(d[106]),"+f"(d[107]),"+f"(d[108]),"+f"(d[109]),"+f"(d[110]),"+f"(d[111])
    : "l"(da), "l"(db), "r"(acc));
}
__device__ __forceinline__ void mma_ss_56(float (&d)[28], uint64_t da, uint64_t db, int acc) {
  asm volatile("{.reg .pred p; setp.ne.b32 p, %30, 0;\n"
    "wgmma.mma_async.sync.aligned.m64n56k16.f32.bf16.bf16 {%0,%1,%2,%3,%4,%5,%6,%7,%8,%9,%10,%11,%12,%13,%14,%15,%16,%17,%18,%19,%20,%21,%22,%23,%24,%25,%26,%27}, %28, %29, p, 1, 1, 0, 1;}\n"
    : "+f"(d[0]),"+f"(d[1]),"+f"(d[2]),"+f"(d[3]),"+f"(d[4]),"+f"(d[5]),"+f"(d[6]),"+f"(d[7]),"+f"(d[8]),"+f"(d[9]),"+f"(d[10]),"+f"(d[11]),"+f"(d[12]),"+f"(d[13]),"+f"(d[14]),"+f"(d[15]),"+f"(d[16]),"+f"(d[17]),"+f"(d[18]),"+f"(d[19]),"+f"(d[20]),"+f"(d[21]),"+f"(d[22]),"+f"(d[23]),"+f"(d[24]),"+f"(d[25]),"+f"(d[26]),"+f"(d[27])
    : "l"(da), "l"(db), "r"(acc));
}
__device__ __forceinline__ void mma_rs_56(float (&d)[28], uint32_t a0, uint32_t a1, uint32_t a2, uint32_t a3, uint64_t db, int acc) {
  asm volatile("{.reg .pred p; setp.ne.b32 p, %33, 0;\n"
    "wgmma.mma_async.sync.aligned.m64n56k16.f32.bf16.bf16 {%0,%1,%2,%3,%4,%5,%6,%7,%8,%9,%10,%11,%12,%13,%14,%15,%16,%17,%18,%19,%20,%21,%22,%23,%24,%25,%26,%27}, {%28,%29,%30,%31}, %32, p, 1, 1, 1;}\n"
    : "+f"(d[0]),"+f"(d[1]),"+f"(d[2]),"+f"(d[3]),"+f"(d[4]),"+f"(d[5]),"+f"(d[6]),"+f"(d[7]),"+f"(d[8]),"+f"(d[9]),"+f"(d[10]),"+f"(d[11]),"+f"(d[12]),"+f"(d[13]),"+f"(d[14]),"+f"(d[15]),"+f"(d[16]),"+f"(d[17]),"+f"(d[18]),"+f"(d[19]),"+f"(d[20]),"+f"(d[21]),"+f"(d[22]),"+f"(d[23]),"+f"(d[24]),"+f"(d[25]),"+f"(d[26]),"+f"(d[27])
    : "r"(a0), "r"(a1), "r"(a2), "r"(a3), "l"(db), "r"(acc));
}
__device__ __forceinline__ void mma_ss_64t(float (&d)[32], uint64_t da, uint64_t db, int acc) {
  asm volatile("{.reg .pred p; setp.ne.b32 p, %34, 0;\n"
    "wgmma.mma_async.sync.aligned.m64n64k16.f32.bf16.bf16 {%0,%1,%2,%3,%4,%5,%6,%7,%8,%9,%10,%11,%12,%13,%14,%15,%16,%17,%18,%19,%20,%21,%22,%23,%24,%25,%26,%27,%28,%29,%30,%31}, %32, %33, p, 1, 1, 1, 1;}\n"
    : "+f"(d[0]),"+f"(d[1]),"+f"(d[2]),"+f"(d[3]),"+f"(d[4]),"+f"(d[5]),"+f"(d[6]),"+f"(d[7]),"+f"(d[8]),"+f"(d[9]),"+f"(d[10]),"+f"(d[11]),"+f"(d[12]),"+f"(d[13]),"+f"(d[14]),"+f"(d[15]),"+f"(d[16]),"+f"(d[17]),"+f"(d[18]),"+f"(d[19]),"+f"(d[20]),"+f"(d[21]),"+f"(d[22]),"+f"(d[23]),"+f"(d[24]),"+f"(d[25]),"+f"(d[26]),"+f"(d[27]),"+f"(d[28]),"+f"(d[29]),"+f"(d[30]),"+f"(d[31])
    : "l"(da), "l"(db), "r"(acc));
}
__device__ __forceinline__ void mma_rs_64(float (&d)[32], uint32_t a0, uint32_t a1, uint32_t a2, uint32_t a3, uint64_t db, int acc) {
  asm volatile("{.reg .pred p; setp.ne.b32 p, %37, 0;\n"
    "wgmma.mma_async.sync.aligned.m64n64k16.f32.bf16.bf16 {%0,%1,%2,%3,%4,%5,%6,%7,%8,%9,%10,%11,%12,%13,%14,%15,%16,%17,%18,%19,%20,%21,%22,%23,%24,%25,%26,%27,%28,%29,%30,%31}, {%32,%33,%34,%35}, %36, p, 1, 1, 1;}\n"
    : "+f"(d[0]),"+f"(d[1]),"+f"(d[2]),"+f"(d[3]),"+f"(d[4]),"+f"(d[5]),"+f"(d[6]),"+f"(d[7]),"+f"(d[8]),"+f"(d[9]),"+f"(d[10]),"+f"(d[11]),"+f"(d[12]),"+f"(d[13]),"+f"(d[14]),"+f"(d[15]),"+f"(d[16]),"+f"(d[17]),"+f"(d[18]),"+f"(d[19]),"+f"(d[20]),"+f"(d[21]),"+f"(d[22]),"+f"(d[23]),"+f"(d[24]),"+f"(d[25]),"+f"(d[26]),"+f"(d[27]),"+f"(d[28]),"+f"(d[29]),"+f"(d[30]),"+f"(d[31])
    : "r"(a0), "r"(a1), "r"(a2), "r"(a3), "l"(db), "r"(acc));
}

__device__ __forceinline__ void dual_softmax(const float (&p)[28], uint32_t (&phi)[4][7]) {
  constexpr float L2E = 1.4426950408889634f;
#pragma unroll
  for (int i = 0; i < 4; i++) {
    float mx = p[i], mn = p[i];
#pragma unroll
    for (int j = 1; j < 7; j++) { mx = fmaxf(mx, p[4 * j + i]); mn = fminf(mn, p[4 * j + i]); }
    mx = fmaxf(mx, __shfl_xor_sync(~0u, mx, 1)); mn = fminf(mn, __shfl_xor_sync(~0u, mn, 1));
    mx = fmaxf(mx, __shfl_xor_sync(~0u, mx, 2)); mn = fminf(mn, __shfl_xor_sync(~0u, mn, 2));
    float a[7], b[7], sa = 0.f, sb = 0.f;
    const float mxl = mx * L2E, mnl = mn * L2E;
#pragma unroll
    for (int j = 0; j < 7; j++) {
      a[j] = ex2(fmaf(p[4 * j + i], L2E, -mxl)); b[j] = ex2(fmaf(p[4 * j + i], -L2E, mnl));
      sa += a[j]; sb += b[j];
    }
    sa += __shfl_xor_sync(~0u, sa, 1); sb += __shfl_xor_sync(~0u, sb, 1);
    sa += __shfl_xor_sync(~0u, sa, 2); sb += __shfl_xor_sync(~0u, sb, 2);
    const float ra = __fdividef(1.f, sa), rb = __fdividef(1.f, sb);
#pragma unroll
    for (int j = 0; j < 7; j++) phi[i][j] = pack(a[j] * ra, b[j] * rb);
  }
}

struct Ring {
  uint32_t full, empty, base; int slot, par;
  __device__ __forceinline__ uint32_t acquire() { mbar_wait(full + slot * 8, par); return base + slot * SLOT; }
  __device__ __forceinline__ int advance() { int s = slot; if (++slot == NSLOT) { slot = 0; par ^= 1; } return s; }
  __device__ __forceinline__ void release(int s, bool elect) { if (elect) mbar_arrive(empty + s * 8); }
};
constexpr int FL_KV = 448, FL_ZERO = FL_KV + 16, FL_CS = FL_KV + 24, FL_DONE = FL_KV + 32;

__global__ void __launch_bounds__(384, 1)
fused_kernel(const __grid_constant__ CUtensorMap mQKV, const __grid_constant__ CUtensorMap mWO,
             const __grid_constant__ CUtensorMap mW1, const __grid_constant__ CUtensorMap mW2,
             const __grid_constant__ CUtensorMap mX,
             const __nv_bfloat16* __restrict__ x, const __nv_bfloat16* __restrict__ wphi,
             const __nv_bfloat16* __restrict__ b1, const __nv_bfloat16* __restrict__ b2,
             const __nv_bfloat16* __restrict__ wqkv, const __nv_bfloat16* __restrict__ wo, const __nv_bfloat16* __restrict__ w1,
             const __nv_bfloat16* __restrict__ w2, __nv_bfloat16* __restrict__ out) {
  extern __shared__ unsigned char smem_raw[];
  const uint32_t sb = (smem_u32(smem_raw) + 1023) & ~1023u;
  unsigned char* sg = smem_raw + (sb - smem_u32(smem_raw));
  const int tid = threadIdx.x, lane = tid & 31;
  const int G = blockIdx.x >> 3, r = blockIdx.x & 7;
  const uint32_t barFull = sb + OFF_BAR, barEmpty = barFull + 56, barA = barEmpty + 56, barCS = barA + 112;
  if (tid == 0) {
    for (int i = 0; i < NSLOT; i++) { mbar_init(barFull + i * 8, 1); mbar_init(barEmpty + i * 8, 2); }
    for (int i = 0; i < 14; i++) mbar_init(barA + i * 8, 1);
    mbar_init(barCS, 64);
    asm volatile("fence.mbarrier_init.release.cluster;" ::: "memory");
  }
  for (int i = tid; i < 416; i += 384) reinterpret_cast<float*>(sg + OFF_CS0)[i] = 0.f;
  __syncthreads();
  const int wgid = __shfl_sync(~0u, tid >> 7, 0);
  if (wgid == 2) {
    asm volatile("setmaxnreg.dec.sync.aligned.u32 40;");
    if (tid == 256) {
      int slot = 0, par = 1;
      for (int it = 0; it < 2 * TILES_PER_LAYER; it++) {
        const int i = it >= TILES_PER_LAYER ? it - TILES_PER_LAYER : it;
        mbar_wait(barEmpty + slot * 8, par);
        const uint32_t dst = sb + OFF_RING + slot * SLOT, fb = barFull + slot * 8;
        mbar_expect(fb, i < 14 ? 12288 : SLOT);
        if (i < 14) tma3(dst, &mQKV, 56 * r, 32 * i, 0, fb);
        else if (i < 18) tma2(dst, &mWO, 56 * r, 112 * (i - 14), fb);
        else if (i < 32) tma3(dst, &mW1, 0, 32 * (i - 18), 7 * r, fb);
        else tma2(dst, &mW2, 64 * ((i - 32) >> 1), 224 * r + 112 * (i & 1), fb);
        if (++slot == NSLOT) { slot = 0; par ^= 1; }
      }
    } else if (tid >= 352) {
      if (lane < 14) {
        mbar_expect(barA + lane * 8, 8192);
        tma2(sb + lane * 8192, &mX, 64 * (lane % 7), G * 128 + 64 * (lane / 7), barA + lane * 8);
      } else if (lane < 16) {
        mbar_wait(barA, 0);
        const char* src = lane == 14 ? (const char*)wo + blockIdx.x * 3136 : (const char*)w2 + blockIdx.x * 12544;
        asm volatile("cp.async.bulk.prefetch.L2.global [%0], %1;" ::"l"(src), "r"(lane == 14 ? 3136 : 12544) : "memory");
      }
    } else if (tid >= 288) {
      unsigned ep;
      asm volatile("ld.relaxed.gpu.global.u32 %0, [%1];" : "=r"(ep) : "l"(gFlag + FL_DONE * 32) : "memory");
      const int idx = tid - 288;
      bar_sync<4, 320>();
      if (idx < 52) {
        gCS[(r * 16 + G) * 104 + idx] = reinterpret_cast<const float4*>(sg + OFF_CS0)[idx];
        gCS[(r * 16 + G) * 104 + 52 + idx] = reinterpret_cast<const float4*>(sg + OFF_CS0)[52 + idx];
      }
      __syncwarp();
      if (lane == 0) { flag_arrive(gFlag + (FL_CS + r) * 32); flag_wait(gFlag + (FL_CS + r) * 32, (ep / NCTA + 1) * 32); }
      __syncwarp();
      if (idx < 52) {
#pragma unroll 1
        for (int hh = 0; hh < 2; hh++) {
          float4 a = make_float4(0.f, 0.f, 0.f, 0.f);
#pragma unroll 4
          for (int i = 0; i < 16; i++) { const float4 v = __ldcg(gCS + (r * 16 + i) * 104 + hh * 52 + idx); a.x += v.x; a.y += v.y; a.z += v.z; a.w += v.w; }
          reinterpret_cast<float4*>(sg + OFF_CS)[hh * 52 + idx] = a;
        }
      }
      mbar_arrive(barCS);
    }
  } else {
  asm volatile("setmaxnreg.inc.sync.aligned.u32 232;");
  const int c = wgid, w = (tid >> 5) & 3, g = lane >> 2, t = lane & 3;
  const bool elect = (tid & 127) == 0;
  const uint32_t abuf = sb + c * ABYTES, barAc = barA + c * 56;
  const int row0 = G * 128 + c * 64;
  unsigned epoch;
  asm volatile("ld.relaxed.gpu.global.u32 %0, [%1];" : "=r"(epoch) : "l"(gFlag + FL_DONE * 32) : "memory");
  STAMP(24);
  float mean[2], rstd[2];
  {
    uint32_t wv[8];
#pragma unroll
    for (int i = 0; i < 8; i++) {
      const int k = i * 8 + (tid >> 5), e = k >= 28;
      wv[i] = (k < 56 && lane < 28) ? (uint32_t)__ldg(reinterpret_cast<const unsigned short*>(wphi) + (2 * r + e) * 784 + (k - 28 * e) * 28 + lane) << (16 * e) : 0u;
    }
    const float bv = tid < 224 ? __bfloat162float(b1[224 * r + tid]) : 0.f;
    {
      const int ch = tid & 63, k0 = G * 28 + (tid >> 6) * 7;
      if (ch < 49) {
        const bool q = ch < 21;
        const int p = ch / 7;
        const uint4* src = q ? reinterpret_cast<const uint4*>(wqkv + (size_t)k0 * 1344 + p * 448 + 56 * r) + (ch - 7 * p)
                             : reinterpret_cast<const uint4*>(w1 + (size_t)k0 * 1792 + 224 * r) + (ch - 21);
        uint4 u[7];
#pragma unroll
        for (int i = 0; i < 7; i++) u[i] = __ldg(src + i * (q ? 168 : 224));
        float s[8] = {};
#pragma unroll
        for (int i = 0; i < 7; i++) { s[0] += lo(u[i].x); s[1] += hi(u[i].x); s[2] += lo(u[i].y); s[3] += hi(u[i].y); s[4] += lo(u[i].z); s[5] += hi(u[i].z); s[6] += lo(u[i].w); s[7] += hi(u[i].w); }
        float* dst = reinterpret_cast<float*>(sg + OFF_CS0) + (q ? ch + p : ch + 3) * 8;
#pragma unroll
        for (int i = 0; i < 8; i++) atomicAdd(dst + i, s[i]);
      }
      asm volatile("bar.arrive 4, 320;" ::: "memory");
    }
    if (G == 0) {
#pragma unroll 1
      for (int i = tid; i < 2 * 1280; i += 256) gKV[((i >= 1280) * 7 + r) * 1280 + i] = make_float4(0.f, 0.f, 0.f, 0.f);
    }
#pragma unroll 1
    for (int hh = 0; hh < 2; hh++) {
      const uint4* src = reinterpret_cast<const uint4*>(x + (size_t)(row0 + w * 16 + hh * 8 + g) * DM) + t;
      uint4 v[14];
#pragma unroll
      for (int k = 0; k < 14; k++) v[k] = __ldg(src + k * 4);
      float s = 0.f, q = 0.f;
#pragma unroll
      for (int k = 0; k < 14; k++) s += (lo(v[k].x) + hi(v[k].x)) + (lo(v[k].y) + hi(v[k].y)) + (lo(v[k].z) + hi(v[k].z)) + (lo(v[k].w) + hi(v[k].w));
      s += __shfl_xor_sync(~0u, s, 1); s += __shfl_xor_sync(~0u, s, 2);
      s *= 1.f / DM;
#pragma unroll
      for (int k = 0; k < 14; k++) {
        const uint32_t e[4] = {v[k].x, v[k].y, v[k].z, v[k].w};
#pragma unroll
        for (int z = 0; z < 4; z++) { float a = lo(e[z]) - s, b = hi(e[z]) - s; q = fmaf(a, a, q); q = fmaf(b, b, q); }
      }
      q += __shfl_xor_sync(~0u, q, 1); q += __shfl_xor_sync(~0u, q, 2);
      q = rsqrtf(q * (1.f / DM) + 1e-5f);
      STAMP(25 + hh);
      if (hh) { mean[1] = s; rstd[1] = q; } else { mean[0] = s; rstd[0] = q; mean[1] = 0.f; rstd[1] = 0.f; }
    }
#pragma unroll
    for (int i = 0; i < 8; i++) {
      const int k = i * 8 + (tid >> 5);
      *reinterpret_cast<uint32_t*>(sg + OFF_WPHI + k * 128 + ((g ^ (k & 7)) << 4) + t * 4) = wv[i];
    }
    if (tid < 224) reinterpret_cast<float*>(sg + OFF_B1)[tid] = bv;
    fence_async_smem();
    bar_sync<3, 256>();
    epoch = epoch / NCTA + 1;
    if (G == 0 && tid == 0) flag_arrive(gFlag + (FL_ZERO + r) * 32);
  }
  STAMP(0);
  Ring ring{barFull, barEmpty, sb + OFF_RING, 0, 0};
  int apar = 0;
  const uint32_t stsm_off = (w * 16 + ((lane >> 3) & 1) * 8 + (lane & 7)) * 128;
  const uint32_t stsm_hi = lane >> 4;
  const uint64_t dA = mkdesc(abuf, 1024, 128, 0);

  auto gather = [&](unsigned* fl, const unsigned char* img) {
    __syncwarp();
    if (lane == 0) flag_arrive(fl);
    if (w == 0) {
      STAMP(27);
      if (lane == 0) flag_wait(fl, epoch * 32);
      __syncwarp();
      STAMP(28);
      if (lane < 7) { fence_async(); mbar_expect(barAc + lane * 8, 8192); bulk_ld(abuf + lane * 8192, img + lane * 8192, 8192, barAc + lane * 8); }
    }
    __syncwarp();
    apar ^= 1;
  };
  auto slice_off = [&](int j, int hh) -> uint32_t {
    return (7 * r + j) * 1024 + (w * 2 + hh) * 128 + lane * 4;
  };
  auto load_stats = [&](const float2* st) {
#pragma unroll
    for (int hh = 0; hh < 2; hh++) {
      const uint4 u = ldcg4(st + (size_t)(row0 + w * 16 + hh * 8 + g) * 8 + 2 * t);
      const float m0 = __uint_as_float(u.x), m1 = __uint_as_float(u.z);
      float m = m0 + m1;
      m += __shfl_xor_sync(~0u, m, 1); m += __shfl_xor_sync(~0u, m, 2);
      m *= 0.125f;
      float q = __uint_as_float(u.y) + __uint_as_float(u.w) + 56.f * ((m0 - m) * (m0 - m) + (m1 - m) * (m1 - m));
      q += __shfl_xor_sync(~0u, q, 1); q += __shfl_xor_sync(~0u, q, 2);
      mean[hh] = m; rstd[hh] = rsqrtf(q * (1.f / DM) + 1e-5f);
    }
  };

#pragma unroll 1
  for (int layer = 0; layer < 2; layer++) {
    unsigned* const fl = gFlag + (layer * 32 + G * 2 + c) * 7 * 32;
    uint32_t phiq[4][7], xs[7][2];
    {
      float acc[92]; reg_def(acc);
      const uint64_t dQ = layer ? dA : mkdesc(abuf, 16, 1024, 1);
      const int kstep = layer ? 128 : 2;
      int prev = 0;
#pragma unroll 1
      for (int st = 0; st < 14; st++) {
        if (!(st & 1)) mbar_wait(barAc + (st >> 1) * 8, apar);
        const uint64_t da = dQ + (st >> 1) * 512 + (st & 1) * 2 * kstep, db = mkdesc(ring.acquire(), 4096, 1024, 1);
        wg_fence();
        mma_ss_184(acc, da, db, st);
        mma_ss_184(acc, da + kstep, db + 128, 1);
        wg_commit();
        if (st > 0) { wg_wait<1>(); ring.release(prev, elect); }
        prev = ring.advance();
      }
      if (layer) load_stats(gStat + 2048 * 8); else mbar_wait(barCS, 0);
#pragma unroll
      for (int j = 0; j < 7; j++) {
        const int ci = 7 * r + j;
        const uint32_t a = abuf + (layer ? slice_off(j, 0) : (ci >> 3) * 8192 + (w * 16 + g) * 128 + (((ci & 7) ^ g) << 4) + t * 4);
        xs[j][0] = lds32(a); xs[j][1] = lds32(a + (layer ? 128 : 1024));
      }
      wg_wait<0>(); reg_fence(acc);
      ring.release(prev, elect);
      STAMP(1 + layer * 12);
      uint32_t f[3][14];
      {
        const float2* cs = reinterpret_cast<const float2*>(sg + OFF_CS) + t;
        const float mr0 = -mean[0] * rstd[0], mr1 = -mean[1] * rstd[1];
#pragma unroll
        for (int p = 0; p < 3; p++)
#pragma unroll
          for (int j = 0; j < 7; j++) {
            const float2 s = cs[p * 32 + j * 4];
            const int b = p * 32 + j * 4;
            f[p][2 * j] = pack(fmaf(acc[b], rstd[0], s.x * mr0), fmaf(acc[b + 1], rstd[0], s.y * mr0));
            f[p][2 * j + 1] = pack(fmaf(acc[b + 2], rstd[1], s.x * mr1), fmaf(acc[b + 3], rstd[1], s.y * mr1));
          }
      }
      float pk[28], pq[28]; reg_def(pk); reg_def(pq);
      const uint64_t dW = mkdesc(sb + OFF_WPHI, 4096, 1024, 1);
      wg_fence();
#pragma unroll
      for (int s = 0; s < 4; s++)
        mma_rs_56(pk, f[1][4 * s], f[1][4 * s + 1], s < 3 ? f[1][(4 * s + 2) % 14] : 0u, s < 3 ? f[1][(4 * s + 3) % 14] : 0u, dW + s * 128, s);
      wg_commit();
#pragma unroll
      for (int s = 0; s < 4; s++)
        mma_rs_56(pq, f[0][4 * s], f[0][4 * s + 1], s < 3 ? f[0][(4 * s + 2) % 14] : 0u, s < 3 ? f[0][(4 * s + 3) % 14] : 0u, dW + s * 128, s);
      wg_commit();
      bar_wg(c);
      const uint32_t srow = abuf + stsm_off, ones = t == 0 ? 0x3F803F80u : 0u;
#pragma unroll
      for (int jp = 0; jp < 4; jp++)
        stsm4(srow + 16384 + (((2 * jp + stsm_hi) ^ (lane & 7)) << 4), f[2][4 * jp], f[2][4 * jp + 1],
              jp < 3 ? f[2][(4 * jp + 2) % 14] : ones, jp < 3 ? f[2][(4 * jp + 3) % 14] : ones);
      wg_wait<0>(); reg_fence(pk); reg_fence(pq);
#pragma unroll 1
      for (int pass = 0; pass < 2; pass++) {
        dual_softmax(pk, phiq);
        if (pass) break;
#pragma unroll
        for (int e = 0; e < 2; e++)
#pragma unroll
          for (int jp = 0; jp < 4; jp++)
            stsm4(srow + e * 8192 + (((2 * jp + stsm_hi) ^ (lane & 7)) << 4), phiq[e][2 * jp], phiq[2 + e][2 * jp],
                  jp < 3 ? phiq[e][(2 * jp + 1) % 7] : 0u, jp < 3 ? phiq[2 + e][(2 * jp + 1) % 7] : 0u);
        fence_async_smem();
        bar_sync<3, 256>();
        float kv[32]; reg_def(kv);
        const uint64_t dP = mkdesc(sb + c * 8192, 4096, 1024, 1), dV = mkdesc(sb + 16384, 4096, 1024, 1);
        wg_fence();
#pragma unroll
        for (int s = 0; s < 8; s++) mma_ss_64t(kv, dP + (s >> 2) * (ABYTES / 16) + (s & 3) * 128, dV + (s >> 2) * (ABYTES / 16) + (s & 3) * 128, s);
        wg_commit();
        if (layer == 0 && lane == 0) flag_wait(gFlag + (FL_ZERO + r) * 32, epoch);
        __syncwarp();
        wg_wait<0>(); reg_fence(kv);
        float4* kvg = gKV + ((layer * 8 + r) * 2 + c) * 640 + (tid & 127);
#pragma unroll
        for (int i = 0; i < 5; i++) {
          float v0, v1, v2, v3;
          if (i == 4) { v0 = kv[28]; v1 = kv[29]; v2 = kv[30]; v3 = kv[31]; }
          else { v0 = c ? kv[12 + 4 * i] : kv[4 * i]; v1 = c ? kv[13 + 4 * i] : kv[1 + 4 * i]; v2 = c ? kv[14 + 4 * i] : kv[2 + 4 * i]; v3 = c ? kv[15 + 4 * i] : kv[3 + 4 * i]; }
          const bool use = i == 4 ? t == 0 : (i == 0 ? (c == 0 || t >= 2) : (i == 3 ? (c == 1 || t < 2) : true));
          if (use) asm volatile("red.relaxed.gpu.global.add.v4.f32 [%0], {%1,%2,%3,%4};" ::"l"(kvg + i * 128), "f"(v0), "f"(v1), "f"(v2), "f"(v3) : "memory");
        }
        __syncwarp();
        if (lane == 0) flag_arrive(gFlag + (FL_KV + layer * 8 + r) * 32);
        __syncwarp();
        STAMP(2 + layer * 12);
#pragma unroll
        for (int i = 0; i < 28; i++) pk[i] = pq[i];
      }
    }
    {
      if (elect) flag_wait(gFlag + (FL_KV + layer * 8 + r) * 32, epoch * 128);
      bar_wg(c);
      STAMP(3 + layer * 12);
      const float4* kvg = gKV + (layer * 8 + r) * 1280 + (tid & 127);
      uint4 kk[2][5];
#pragma unroll
      for (int e = 0; e < 2; e++)
#pragma unroll
        for (int i = 0; i < 5; i++) kk[e][i] = ldcg4(kvg + e * 640 + i * 128);
      const uint32_t srow = abuf + 24576 + stsm_off;
#pragma unroll
      for (int e = 0; e < 2; e++) {
        uint32_t f[8][2];
#pragma unroll
        for (int j = 0; j < 8; j++) { f[j][0] = 0u; f[j][1] = 0u; }
#pragma unroll
        for (int i = 0; i < 4; i++) {
          f[i + 3 * e][0] = pack(__uint_as_float(kk[e][i].x), __uint_as_float(kk[e][i].y));
          f[i + 3 * e][1] = pack(__uint_as_float(kk[e][i].z), __uint_as_float(kk[e][i].w));
        }
        f[7][0] = e ? pack(0.f, __uint_as_float(kk[e][4].y)) : pack(__uint_as_float(kk[e][4].x), 0.f);
        f[7][1] = e ? pack(0.f, __uint_as_float(kk[e][4].w)) : pack(__uint_as_float(kk[e][4].z), 0.f);
#pragma unroll
        for (int jp = 0; jp < 4; jp++)
          stsm4(srow + e * 8192 + (((2 * jp + stsm_hi) ^ (lane & 7)) << 4), f[2 * jp][0], f[2 * jp][1], f[2 * jp + 1][0], f[2 * jp + 1][1]);
      }
      fence_async_smem();
      bar_wg(c);
      float num[32]; reg_def(num);
      const uint64_t dK = mkdesc(abuf + 24576, 4096, 1024, 1);
      wg_fence();
#pragma unroll
      for (int e = 0; e < 2; e++)
#pragma unroll
        for (int s = 0; s < 4; s++)
          mma_rs_64(num, phiq[e][2 * s], phiq[2 + e][2 * s], s < 3 ? phiq[e][(2 * s + 1) % 7] : 0u, s < 3 ? phiq[2 + e][(2 * s + 1) % 7] : 0u,
                    dK + e * 512 + s * 128, e + s);
      wg_commit();
      wg_wait<0>(); reg_fence(num);
      float rd[4];
#pragma unroll
      for (int i = 0; i < 4; i++) rd[i] = __fdividef(1.f, __shfl_sync(~0u, num[28 + i], lane & ~3) + 1e-6f);
      unsigned char* img = gImg + (size_t)(G * 2 + c) * ABYTES;
#pragma unroll
      for (int j = 0; j < 7; j++) {
        const bool hb = j > 3 || (j == 3 && t >= 2);
        const float r0 = hb ? rd[1] : rd[0], r1 = hb ? rd[3] : rd[2];
        *reinterpret_cast<uint32_t*>(img + slice_off(j, 0)) = pack(num[4 * j] * r0, num[4 * j + 1] * r0);
        *reinterpret_cast<uint32_t*>(img + slice_off(j, 1)) = pack(num[4 * j + 2] * r1, num[4 * j + 3] * r1);
      }
      STAMP(4 + layer * 12);
      gather(fl, img);
      STAMP(5 + layer * 12);
    }
    {
      float acc[28]; reg_def(acc);
      int prev = 0;
#pragma unroll 1
      for (int st = 0; st < 4; st++) {
        mbar_wait(barAc + (st * 7 + 3) / 4 * 8, apar);
        mbar_wait(barAc + (st * 7 + 6) / 4 * 8, apar);
        const uint64_t db = mkdesc(ring.acquire(), 4096, 1024, 1);
        wg_fence();
#pragma unroll
        for (int s = 0; s < 7; s++) { const int ks = st * 7 + s; mma_ss_56(acc, dA + ks * 128, db + s * 128, ks); }
        wg_commit();
        if (st > 0) { wg_wait<1>(); ring.release(prev, elect); }
        prev = ring.advance();
      }
      wg_wait<0>(); reg_fence(acc);
      ring.release(prev, elect);
      unsigned char* img = gImg + (size_t)(32 + G * 2 + c) * ABYTES;
#pragma unroll
      for (int hh = 0; hh < 2; hh++) {
        float s = 0.f, q = 0.f;
#pragma unroll
        for (int j = 0; j < 7; j++) {
          xs[j][hh] = pack(lo(xs[j][hh]) + acc[4 * j + 2 * hh], hi(xs[j][hh]) + acc[4 * j + 2 * hh + 1]);
          *reinterpret_cast<uint32_t*>(img + slice_off(j, hh)) = xs[j][hh];
          s += lo(xs[j][hh]) + hi(xs[j][hh]);
        }
        s += __shfl_xor_sync(~0u, s, 1); s += __shfl_xor_sync(~0u, s, 2);
        s *= 1.f / 56.f;
#pragma unroll
        for (int j = 0; j < 7; j++) { const float a = lo(xs[j][hh]) - s, b = hi(xs[j][hh]) - s; q = fmaf(a, a, q); q = fmaf(b, b, q); }
        q += __shfl_xor_sync(~0u, q, 1); q += __shfl_xor_sync(~0u, q, 2);
        if (t == 0) gStat[(size_t)(row0 + w * 16 + hh * 8 + g) * 8 + r] = make_float2(s, q);
      }
      STAMP(6 + layer * 12);
      gather(fl + 32, img);
      STAMP(7 + layer * 12);
    }
    {
      uint32_t hf[28][2];
      {
        float acc[112]; reg_def(acc);
        int prev = 0;
#pragma unroll 1
        for (int st = 0; st < 14; st++) {
          if (!(st & 1)) mbar_wait(barAc + (st >> 1) * 8, apar);
          const uint64_t da = dA + st * 256, db = mkdesc(ring.acquire(), 2048, 512, 2);
          wg_fence();
          mma_ss_224(acc, da, db, st);
          mma_ss_224(acc, da + 128, db + 64, 1);
          wg_commit();
          if (st > 0) { wg_wait<1>(); ring.release(prev, elect); }
          prev = ring.advance();
        }
        load_stats(gStat);
        wg_wait<0>(); reg_fence(acc);
        ring.release(prev, elect);
        STAMP(8 + layer * 12);
        const float2* bs = reinterpret_cast<const float2*>(sg + OFF_B1) + t;
        const float2* cs = reinterpret_cast<const float2*>(sg + OFF_CS + 768) + t;
        const float mr0 = -mean[0] * rstd[0], mr1 = -mean[1] * rstd[1];
#pragma unroll
        for (int j = 0; j < 28; j++) {
          const float2 b = bs[4 * j], s = cs[4 * j];
          const float h0 = fmaxf(fmaf(acc[4 * j], rstd[0], fmaf(s.x, mr0, b.x)), 0.f), h1 = fmaxf(fmaf(acc[4 * j + 1], rstd[0], fmaf(s.y, mr0, b.y)), 0.f);
          const float h2 = fmaxf(fmaf(acc[4 * j + 2], rstd[1], fmaf(s.x, mr1, b.x)), 0.f), h3 = fmaxf(fmaf(acc[4 * j + 3], rstd[1], fmaf(s.y, mr1, b.y)), 0.f);
          hf[j][0] = pack(h0 * h0, h1 * h1); hf[j][1] = pack(h2 * h2, h3 * h3);
        }
      }
      unsigned char* pdst = gP + (size_t)(((G * 2 + c) * 8 + 2 * w) * 8 + r) * 7168 + lane * 8;
      uint2 pk[8] = {};
#pragma unroll 1
      for (int ch = 0; ch < 7; ch++) {
        float acc[32]; reg_def(acc);
        int sl0 = 0, sl1 = 0;
#pragma unroll
        for (int hk = 0; hk < 2; hk++) {
          const uint64_t db = mkdesc(ring.acquire(), 4096, 1024, 1);
          wg_fence();
#pragma unroll
          for (int s = 0; s < 7; s++) { const int ks = hk * 7 + s; mma_rs_64(acc, hf[2 * ks][0], hf[2 * ks][1], hf[2 * ks + 1][0], hf[2 * ks + 1][1], db + s * 128, ks); }
          wg_commit();
          if (hk) sl1 = ring.advance(); else sl0 = ring.advance();
        }
        if (ch > 0) {
#pragma unroll
          for (int i = 0; i < 8; i++) *reinterpret_cast<uint2*>(pdst + (i & 1) * (8 * 7168) + (i >> 1) * 256) = pk[i];
          pdst += 1024;
        }
        wg_wait<1>(); ring.release(sl0, elect);
        wg_wait<0>(); reg_fence(acc); ring.release(sl1, elect);
#pragma unroll
        for (int i = 0; i < 8; i++) {
          const int b = (i >> 1) * 8 + (i & 1) * 2;
          pk[i] = make_uint2(pack(acc[b], acc[b + 1]), pack(acc[b + 4], acc[b + 5]));
        }
      }
#pragma unroll
      for (int i = 0; i < 8; i++) *reinterpret_cast<uint2*>(pdst + (i & 1) * (8 * 7168) + (i >> 1) * 256) = pk[i];
      STAMP(9 + layer * 12);
    }
    {
      uint32_t bx[14];
#pragma unroll
      for (int j = 0; j < 14; j++) bx[j] = __ldg(reinterpret_cast<const uint32_t*>(b2 + w * 112 + j * 8 + 2 * t));
      __syncwarp();
      if (lane == 0) { flag_arrive(fl + (3 + w) * 32); flag_wait(fl + (3 + (r >> 1)) * 32, epoch * 8); }
      __syncwarp();
      STAMP(10 + layer * 12);
      const unsigned char* psrc = gP + (size_t)(((G * 2 + c) * 8 + r) * 8) * 7168 + w * 1792 + lane * 8;
      unsigned char* img = gImg + (size_t)(64 + G * 2 + c) * ABYTES;
      uint2 pv[8][7];
#pragma unroll
      for (int s = 0; s < 8; s++)
#pragma unroll
        for (int i = 0; i < 7; i++) pv[s][i] = ldcg2(psrc + s * 7168 + i * 256);
      const uint32_t off = w * 14336 + r * 128 + lane * 4;
      unsigned char* dst = layer ? reinterpret_cast<unsigned char*>(out + (size_t)(row0 + r * 8 + g) * DM + w * 112 + 2 * t) : img + off;
      float sm = 0.f, q = 0.f;
#pragma unroll
      for (int j = 0; j < 14; j++) {
        float y0 = lo(bx[j]), y1 = hi(bx[j]);
        const uint32_t xo = lds32(abuf + off + j * 1024);
        y0 += lo(xo); y1 += hi(xo);
#pragma unroll
        for (int s = 0; s < 8; s++) { const uint32_t u = (j & 1) ? pv[s][j >> 1].y : pv[s][j >> 1].x; y0 += lo(u); y1 += hi(u); }
        bx[j] = pack(y0, y1);
        *reinterpret_cast<uint32_t*>(dst + j * (layer ? 16 : 1024)) = bx[j];
        sm += lo(bx[j]) + hi(bx[j]);
      }
      if (layer) break;
      sm += __shfl_xor_sync(~0u, sm, 1); sm += __shfl_xor_sync(~0u, sm, 2);
      sm *= 1.f / 112.f;
#pragma unroll
      for (int j = 0; j < 14; j++) { const float a = lo(bx[j]) - sm, b = hi(bx[j]) - sm; q = fmaf(a, a, q); q = fmaf(b, b, q); }
      q += __shfl_xor_sync(~0u, q, 1); q += __shfl_xor_sync(~0u, q, 2);
      if (t < 2) gStat[(size_t)(2048 + row0 + r * 8 + g) * 8 + 2 * w + t] = make_float2(sm, q * 0.5f);
      STAMP(11);
      gather(fl + 64, img);
      STAMP(12);
    }
  }
  STAMP(30);
  if (tid == 0) asm volatile("red.relaxed.gpu.global.add.u32 [%0], 1;" ::"l"(gFlag + FL_DONE * 32) : "memory");
  }
}

typedef CUresult (*EncFn)(CUtensorMap*, CUtensorMapDataType, cuuint32_t, void*, const cuuint64_t*, const cuuint64_t*,
                          const cuuint32_t*, const cuuint32_t*, CUtensorMapInterleave, CUtensorMapSwizzle,
                          CUtensorMapL2promotion, CUtensorMapFloatOOBfill);

void make_map(EncFn enc, CUtensorMap* m, void* p, int rank, uint64_t d0, uint64_t d1, uint64_t d2, uint64_t s1, uint64_t s2,
              uint32_t b0, uint32_t b1, uint32_t b2, CUtensorMapSwizzle sw) {
  cuuint64_t dims[3] = {d0, d1, d2}, strides[2] = {s1, s2};
  cuuint32_t box[3] = {b0, b1, b2}, es[3] = {1, 1, 1};
  enc(m, CU_TENSOR_MAP_DATA_TYPE_BFLOAT16, rank, p, dims, strides, box, es, CU_TENSOR_MAP_INTERLEAVE_NONE, sw,
      CU_TENSOR_MAP_L2_PROMOTION_L2_256B, CU_TENSOR_MAP_FLOAT_OOB_FILL_NONE);
}

}

extern "C" void kernel_launch(void* const* d_in, const int* in_sizes, int n_in, void* d_out, int out_size) {
  static EncFn enc = nullptr;
  if (!enc) {
    cudaDriverEntryPointQueryResult st;
    void* fn = nullptr;
    cudaGetDriverEntryPoint("cuTensorMapEncodeTiled", &fn, cudaEnableDefault, &st);
    enc = (EncFn)fn;
    cudaFuncSetAttribute(fused_kernel, cudaFuncAttributeMaxDynamicSharedMemorySize, SMEM_BYTES);
  }
  CUtensorMap mQKV, mWO, mW1, mW2, mX;
  make_map(enc, &mQKV, d_in[1], 3, 448, 448, 3, 2688, 896, 64, 32, 3, CU_TENSOR_MAP_SWIZZLE_128B);
  make_map(enc, &mWO, d_in[3], 2, 448, 448, 1, 896, 0, 64, 112, 1, CU_TENSOR_MAP_SWIZZLE_128B);
  make_map(enc, &mW1, d_in[5], 3, 32, 448, 56, 3584, 64, 32, 32, 7, CU_TENSOR_MAP_SWIZZLE_64B);
  make_map(enc, &mW2, d_in[7], 2, 448, 1792, 1, 896, 0, 64, 112, 1, CU_TENSOR_MAP_SWIZZLE_128B);
  make_map(enc, &mX, d_in[0], 2, 448, 2048, 1, 896, 0, 64, 64, 1, CU_TENSOR_MAP_SWIZZLE_128B);
  fused_kernel<<<NCTA, 384, SMEM_BYTES, cudaStreamPerThread>>>(
      mQKV, mWO, mW1, mW2, mX, (const __nv_bfloat16*)d_in[0], (const __nv_bfloat16*)d_in[2], (const __nv_bfloat16*)d_in[6],
      (const __nv_bfloat16*)d_in[8], (const __nv_bfloat16*)d_in[1], (const __nv_bfloat16*)d_in[3], (const __nv_bfloat16*)d_in[5],
      (const __nv_bfloat16*)d_in[7], (__nv_bfloat16*)d_out);
}
```

```cpp
#include <cuda_runtime.h>
#include <cuda_bf16.h>
#include <cuda.h>
#include <stdint.h>

namespace {

constexpr int DM = 448, NCTA = 128;
constexpr int ABYTES = 57344;
constexpr int SLOT = 14336, NSLOT = 7;
constexpr int OFF_RING = 2 * ABYTES;
constexpr int OFF_WPHI = OFF_RING + NSLOT * SLOT;
constexpr int OFF_B1 = OFF_WPHI + 8192;
constexpr int OFF_CS = OFF_B1 + 896;
constexpr int OFF_BAR = OFF_CS + 1664;
constexpr int SMEM_BYTES = OFF_BAR + 256 + 1024;
constexpr int TILES_PER_LAYER = 46;

__device__ __align__(1024) unsigned char gP[16 * 2 * 8 * 8 * 7168];
__device__ __align__(1024) unsigned char gImg[3 * 32 * ABYTES];
__device__ __align__(1024) float2 gStat[2 * 2048 * 8];
__device__ __align__(1024) float4 gKV[2 * 8 * 2 * 5 * 128];
__device__ __align__(1024) float4 gCS[8 * 16 * 104];
__device__ __align__(128) unsigned gFlag[(2 * 32 * 7 + 32 + 1) * 32];
#define STAMP(i)

__device__ __forceinline__ uint32_t smem_u32(const void* p) { return (uint32_t)__cvta_generic_to_shared(p); }
__device__ __forceinline__ void mbar_init(uint32_t b, int c) { asm volatile("mbarrier.init.shared::cta.b64 [%0], %1;" ::"r"(b), "r"(c)); }
__device__ __forceinline__ void mbar_expect(uint32_t b, int bytes) { asm volatile("mbarrier.arrive.expect_tx.shared::cta.b64 _, [%0], %1;" ::"r"(b), "r"(bytes) : "memory"); }
__device__ __forceinline__ void mbar_arrive(uint32_t b) { asm volatile("mbarrier.arrive.shared::cta.b64 _, [%0];" ::"r"(b) : "memory"); }
__device__ __forceinline__ void mbar_wait(uint32_t b, int par) {
  uint32_t ok; int n = 0;
  while (true) {
    asm volatile("{.reg .pred p; mbarrier.try_wait.parity.shared::cta.b64 p, [%1], %2; selp.u32 %0,1,0,p;}" : "=r"(ok) : "r"(b), "r"(par) : "memory");
    if (ok) break;
    if (++n > (1 << 22)) break;
  }
}
__device__ __forceinline__ void flag_wait(const unsigned* f, unsigned target) {
  unsigned v; int n = 0;
  while (true) {
    asm volatile("ld.acquire.gpu.global.u32 %0, [%1];" : "=r"(v) : "l"(f) : "memory");
    if ((int)(v - target) >= 0) break;
    if (++n > (1 << 21)) break;
  }
}
__device__ __forceinline__ void flag_arrive(unsigned* f) { asm volatile("red.release.gpu.global.add.u32 [%0], 1;" ::"l"(f) : "memory"); }
__device__ __forceinline__ void fence_async() { asm volatile("fence.proxy.async.global;" ::: "memory"); }
__device__ __forceinline__ void fence_async_smem() { asm volatile("fence.proxy.async.shared::cta;" ::: "memory"); }
template <int ID, int N> __device__ __forceinline__ void bar_sync() { asm volatile("bar.sync %0, %1;" ::"n"(ID), "n"(N) : "memory"); }
__device__ __forceinline__ void bar_wg(int c) { if (c) bar_sync<2, 128>(); else bar_sync<1, 128>(); }
__device__ __forceinline__ void wg_fence() { asm volatile("wgmma.fence.sync.aligned;" ::: "memory"); }
__device__ __forceinline__ void wg_commit() { asm volatile("wgmma.commit_group.sync.aligned;" ::: "memory"); }
template <int N> __device__ __forceinline__ void wg_wait() { asm volatile("wgmma.wait_group.sync.aligned %0;" ::"n"(N) : "memory"); }
template <int N> __device__ __forceinline__ void reg_fence(float (&d)[N]) {
#pragma unroll
  for (int i = 0; i < N; i++) asm volatile("" : "+f"(d[i])::"memory");
}
template <int N> __device__ __forceinline__ void reg_def(float (&d)[N]) {
#pragma unroll
  for (int i = 0; i < N; i++) d[i] = 0.f;
}
__device__ __forceinline__ uint64_t mkdesc(uint32_t addr, uint32_t lbo, uint32_t sbo, uint64_t swz) {
  return (uint64_t)((addr & 0x3FFFF) >> 4) | ((uint64_t)(lbo >> 4) << 16) | ((uint64_t)(sbo >> 4) << 32) | (swz << 62);
}
__device__ __forceinline__ uint32_t pack(float a, float b) {
  uint32_t r; asm("cvt.rn.bf16x2.f32 %0, %1, %2;" : "=r"(r) : "f"(b), "f"(a)); return r;
}
__device__ __forceinline__ float lo(uint32_t u) { return __uint_as_float(u << 16); }
__device__ __forceinline__ float hi(uint32_t u) { return __uint_as_float(u & 0xFFFF0000u); }
__device__ __forceinline__ float ex2(float x) { float y; asm("ex2.approx.ftz.f32 %0, %1;" : "=f"(y) : "f"(x)); return y; }
__device__ __forceinline__ void stsm4(uint32_t a, uint32_t r0, uint32_t r1, uint32_t r2, uint32_t r3) {
  asm volatile("stmatrix.sync.aligned.m8n8.x4.shared.b16 [%0], {%1,%2,%3,%4};" ::"r"(a), "r"(r0), "r"(r1), "r"(r2), "r"(r3) : "memory");
}
__device__ __forceinline__ void tma3(uint32_t dst, const CUtensorMap* m, int c0, int c1, int c2, uint32_t bar) {
  asm volatile("cp.async.bulk.tensor.3d.shared::cluster.global.mbarrier::complete_tx::bytes [%0], [%1, {%3,%4,%5}], [%2];"
               ::"r"(dst), "l"(m), "r"(bar), "r"(c0), "r"(c1), "r"(c2) : "memory");
}
__device__ __forceinline__ void tma2(uint32_t dst, const CUtensorMap* m, int c0, int c1, uint32_t bar) {
  asm volatile("cp.async.bulk.tensor.2d.shared::cluster.global.mbarrier::complete_tx::bytes [%0], [%1, {%3,%4}], [%2];"
               ::"r"(dst), "l"(m), "r"(bar), "r"(c0), "r"(c1) : "memory");
}
__device__ __forceinline__ uint32_t lds32(uint32_t a) { uint32_t v; asm volatile("ld.shared.u32 %0, [%1];" : "=r"(v) : "r"(a) : "memory"); return v; }
__device__ __forceinline__ void bulk_ld(uint32_t dst, const void* src, int bytes, uint32_t bar) {
  asm volatile("cp.async.bulk.shared::cluster.global.mbarrier::complete_tx::bytes [%0], [%1], %2, [%3];" ::"r"(dst), "l"(src), "r"(bytes), "r"(bar) : "memory");
}
__device__ __forceinline__ uint4 ldcg4(const void* p) {
  uint4 v; asm volatile("ld.global.cg.v4.u32 {%0,%1,%2,%3}, [%4];" : "=r"(v.x), "=r"(v.y), "=r"(v.z), "=r"(v.w) : "l"(p) : "memory"); return v;
}

__device__ __forceinline__ uint2 ldcg2(const void* p) {
  uint2 v; asm volatile("ld.global.cg.v2.u32 {%0,%1}, [%2];" : "=r"(v.x), "=r"(v.y) : "l"(p) : "memory"); return v;
}

__device__ __forceinline__ void mma_ss_184(float (&d)[92], uint64_t da, uint64_t db, int acc) {
  asm volatile("{.reg .pred p; setp.ne.b32 p, %94, 0;\n"
    "wgmma.mma_async.sync.aligned.m64n184k16.f32.bf16.bf16 {%0,%1,%2,%3,%4,%5,%6,%7,%8,%9,%10,%11,%12,%13,%14,%15,%16,%17,%18,%19,%20,%21,%22,%23,%24,%25,%26,%27,%28,%29,%30,%31,%32,%33,%34,%35,%36,%37,%38,%39,%40,%41,%42,%43,%44,%45,%46,%47,%48,%49,%50,%51,%52,%53,%54,%55,%56,%57,%58,%59,%60,%61,%62,%63,%64,%65,%66,%67,%68,%69,%70,%71,%72,%73,%74,%75,%76,%77,%78,%79,%80,%81,%82,%83,%84,%85,%86,%87,%88,%89,%90,%91}, %92, %93, p, 1, 1, 0, 1;}\n"
    : "+f"(d[0]),"+f"(d[1]),"+f"(d[2]),"+f"(d[3]),"+f"(d[4]),"+f"(d[5]),"+f"(d[6]),"+f"(d[7]),"+f"(d[8]),"+f"(d[9]),"+f"(d[10]),"+f"(d[11]),"+f"(d[12]),"+f"(d[13]),"+f"(d[14]),"+f"(d[15]),"+f"(d[16]),"+f"(d[17]),"+f"(d[18]),"+f"(d[19]),"+f"(d[20]),"+f"(d[21]),"+f"(d[22]),"+f"(d[23]),"+f"(d[24]),"+f"(d[25]),"+f"(d[26]),"+f"(d[27]),"+f"(d[28]),"+f"(d[29]),"+f"(d[30]),"+f"(d[31]),"+f"(d[32]),"+f"(d[33]),"+f"(d[34]),"+f"(d[35]),"+f"(d[36]),"+f"(d[37]),"+f"(d[38]),"+f"(d[39]),"+f"(d[40]),"+f"(d[41]),"+f"(d[42]),"+f"(d[43]),"+f"(d[44]),"+f"(d[45]),"+f"(d[46]),"+f"(d[47]),"+f"(d[48]),"+f"(d[49]),"+f"(d[50]),"+f"(d[51]),"+f"(d[52]),"+f"(d[53]),"+f"(d[54]),"+f"(d[55]),"+f"(d[56]),"+f"(d[57]),"+f"(d[58]),"+f"(d[59]),"+f"(d[60]),"+f"(d[61]),"+f"(d[62]),"+f"(d[63]),"+f"(d[64]),"+f"(d[65]),"+f"(d[66]),"+f"(d[67]),"+f"(d[68]),"+f"(d[69]),"+f"(d[70]),"+f"(d[71]),"+f"(d[72]),"+f"(d[73]),"+f"(d[74]),"+f"(d[75]),"+f"(d[76]),"+f"(d[77]),"+f"(d[78]),"+f"(d[79]),"+f"(d[80]),"+f"(d[81]),"+f"(d[82]),"+f"(d[83]),"+f"(d[84]),"+f"(d[85]),"+f"(d[86]),"+f"(d[87]),"+f"(d[88]),"+f"(d[89]),"+f"(d[90]),"+f"(d[91])
    : "l"(da), "l"(db), "r"(acc));
}
__device__ __forceinline__ void mma_ss_224(float (&d)[112], uint64_t da, uint64_t db, int acc) {
  asm volatile("{.reg .pred p; setp.ne.b32 p, %114, 0;\n"
    "wgmma.mma_async.sync.aligned.m64n224k16.f32.bf16.bf16 {%0,%1,%2,%3,%4,%5,%6,%7,%8,%9,%10,%11,%12,%13,%14,%15,%16,%17,%18,%19,%20,%21,%22,%23,%24,%25,%26,%27,%28,%29,%30,%31,%32,%33,%34,%35,%36,%37,%38,%39,%40,%41,%42,%43,%44,%45,%46,%47,%48,%49,%50,%51,%52,%53,%54,%55,%56,%57,%58,%59,%60,%61,%62,%63,%64,%65,%66,%67,%68,%69,%70,%71,%72,%73,%74,%75,%76,%77,%78,%79,%80,%81,%82,%83,%84,%85,%86,%87,%88,%89,%90,%91,%92,%93,%94,%95,%96,%97,%98,%99,%100,%101,%102,%103,%104,%105,%106,%107,%108,%109,%110,%111}, %112, %113, p, 1, 1, 0, 1;}\n"
    : "+f"(d[0]),"+f"(d[1]),"+f"(d[2]),"+f"(d[3]),"+f"(d[4]),"+f"(d[5]),"+f"(d[6]),"+f"(d[7]),"+f"(d[8]),"+f"(d[9]),"+f"(d[10]),"+f"(d[11]),"+f"(d[12]),"+f"(d[13]),"+f"(d[14]),"+f"(d[15]),"+f"(d[16]),"+f"(d[17]),"+f"(d[18]),"+f"(d[19]),"+f"(d[20]),"+f"(d[21]),"+f"(d[22]),"+f"(d[23]),"+f"(d[24]),"+f"(d[25]),"+f"(d[26]),"+f"(d[27]),"+f"(d[28]),"+f"(d[29]),"+f"(d[30]),"+f"(d[31]),"+f"(d[32]),"+f"(d[33]),"+f"(d[34]),"+f"(d[35]),"+f"(d[36]),"+f"(d[37]),"+f"(d[38]),"+f"(d[39]),"+f"(d[40]),"+f"(d[41]),"+f"(d[42]),"+f"(d[43]),"+f"(d[44]),"+f"(d[45]),"+f"(d[46]),"+f"(d[47]),"+f"(d[48]),"+f"(d[49]),"+f"(d[50]),"+f"(d[51]),"+f"(d[52]),"+f"(d[53]),"+f"(d[54]),"+f"(d[55]),"+f"(d[56]),"+f"(d[57]),"+f"(d[58]),"+f"(d[59]),"+f"(d[60]),"+f"(d[61]),"+f"(d[62]),"+f"(d[63]),"+f"(d[64]),"+f"(d[65]),"+f"(d[66]),"+f"(d[67]),"+f"(d[68]),"+f"(d[69]),"+f"(d[70]),"+f"(d[71]),"+f"(d[72]),"+f"(d[73]),"+f"(d[74]),"+f"(d[75]),"+f"(d[76]),"+f"(d[77]),"+f"(d[78]),"+f"(d[79]),"+f"(d[80]),"+f"(d[81]),"+f"(d[82]),"+f"(d[83]),"+f"(d[84]),"+f"(d[85]),"+f"(d[86]),"+f"(d[87]),"+f"(d[88]),"+f"(d[89]),"+f"(d[90]),"+f"(d[91]),"+f"(d[92]),"+f"(d[93]),"+f"(d[94]),"+f"(d[95]),"+f"(d[96]),"+f"(d[97]),"+f"(d[98]),"+f"(d[99]),"+f"(d[100]),"+f"(d[101]),"+f"(d[102]),"+f"(d[103]),"+f"(d[104]),"+f"(d[105]),"+f"(d[106]),"+f"(d[107]),"+f"(d[108]),"+f"(d[109]),"+f"(d[110]),"+f"(d[111])
    : "l"(da), "l"(db), "r"(acc));
}
__device__ __forceinline__ void mma_ss_56(float (&d)[28], uint64_t da, uint64_t db, int acc) {
  asm volatile("{.reg .pred p; setp.ne.b32 p, %30, 0;\n"
    "wgmma.mma_async.sync.aligned.m64n56k16.f32.bf16.bf16 {%0,%1,%2,%3,%4,%5,%6,%7,%8,%9,%10,%11,%12,%13,%14,%15,%16,%17,%18,%19,%20,%21,%22,%23,%24,%25,%26,%27}, %28, %29, p, 1, 1, 0, 1;}\n"
    : "+f"(d[0]),"+f"(d[1]),"+f"(d[2]),"+f"(d[3]),"+f"(d[4]),"+f"(d[5]),"+f"(d[6]),"+f"(d[7]),"+f"(d[8]),"+f"(d[9]),"+f"(d[10]),"+f"(d[11]),"+f"(d[12]),"+f"(d[13]),"+f"(d[14]),"+f"(d[15]),"+f"(d[16]),"+f"(d[17]),"+f"(d[18]),"+f"(d[19]),"+f"(d[20]),"+f"(d[21]),"+f"(d[22]),"+f"(d[23]),"+f"(d[24]),"+f"(d[25]),"+f"(d[26]),"+f"(d[27])
    : "l"(da), "l"(db), "r"(acc));
}
__device__ __forceinline__ void mma_rs_56(float (&d)[28], uint32_t a0, uint32_t a1, uint32_t a2, uint32_t a3, uint64_t db, int acc) {
  asm volatile("{.reg .pred p; setp.ne.b32 p, %33, 0;\n"
    "wgmma.mma_async.sync.aligned.m64n56k16.f32.bf16.bf16 {%0,%1,%2,%3,%4,%5,%6,%7,%8,%9,%10,%11,%12,%13,%14,%15,%16,%17,%18,%19,%20,%21,%22,%23,%24,%25,%26,%27}, {%28,%29,%30,%31}, %32, p, 1, 1, 1;}\n"
    : "+f"(d[0]),"+f"(d[1]),"+f"(d[2]),"+f"(d[3]),"+f"(d[4]),"+f"(d[5]),"+f"(d[6]),"+f"(d[7]),"+f"(d[8]),"+f"(d[9]),"+f"(d[10]),"+f"(d[11]),"+f"(d[12]),"+f"(d[13]),"+f"(d[14]),"+f"(d[15]),"+f"(d[16]),"+f"(d[17]),"+f"(d[18]),"+f"(d[19]),"+f"(d[20]),"+f"(d[21]),"+f"(d[22]),"+f"(d[23]),"+f"(d[24]),"+f"(d[25]),"+f"(d[26]),"+f"(d[27])
    : "r"(a0), "r"(a1), "r"(a2), "r"(a3), "l"(db), "r"(acc));
}
__device__ __forceinline__ void mma_ss_64t(float (&d)[32], uint64_t da, uint64_t db, int acc) {
  asm volatile("{.reg .pred p; setp.ne.b32 p, %34, 0;\n"
    "wgmma.mma_async.sync.aligned.m64n64k16.f32.bf16.bf16 {%0,%1,%2,%3,%4,%5,%6,%7,%8,%9,%10,%11,%12,%13,%14,%15,%16,%17,%18,%19,%20,%21,%22,%23,%24,%25,%26,%27,%28,%29,%30,%31}, %32, %33, p, 1, 1, 1, 1;}\n"
    : "+f"(d[0]),"+f"(d[1]),"+f"(d[2]),"+f"(d[3]),"+f"(d[4]),"+f"(d[5]),"+f"(d[6]),"+f"(d[7]),"+f"(d[8]),"+f"(d[9]),"+f"(d[10]),"+f"(d[11]),"+f"(d[12]),"+f"(d[13]),"+f"(d[14]),"+f"(d[15]),"+f"(d[16]),"+f"(d[17]),"+f"(d[18]),"+f"(d[19]),"+f"(d[20]),"+f"(d[21]),"+f"(d[22]),"+f"(d[23]),"+f"(d[24]),"+f"(d[25]),"+f"(d[26]),"+f"(d[27]),"+f"(d[28]),"+f"(d[29]),"+f"(d[30]),"+f"(d[31])
    : "l"(da), "l"(db), "r"(acc));
}
__device__ __forceinline__ void mma_rs_64(float (&d)[32], uint32_t a0, uint32_t a1, uint32_t a2, uint32_t a3, uint64_t db, int acc) {
  asm volatile("{.reg .pred p; setp.ne.b32 p, %37, 0;\n"
    "wgmma.mma_async.sync.aligned.m64n64k16.f32.bf16.bf16 {%0,%1,%2,%3,%4,%5,%6,%7,%8,%9,%10,%11,%12,%13,%14,%15,%16,%17,%18,%19,%20,%21,%22,%23,%24,%25,%26,%27,%28,%29,%30,%31}, {%32,%33,%34,%35}, %36, p, 1, 1, 1;}\n"
    : "+f"(d[0]),"+f"(d[1]),"+f"(d[2]),"+f"(d[3]),"+f"(d[4]),"+f"(d[5]),"+f"(d[6]),"+f"(d[7]),"+f"(d[8]),"+f"(d[9]),"+f"(d[10]),"+f"(d[11]),"+f"(d[12]),"+f"(d[13]),"+f"(d[14]),"+f"(d[15]),"+f"(d[16]),"+f"(d[17]),"+f"(d[18]),"+f"(d[19]),"+f"(d[20]),"+f"(d[21]),"+f"(d[22]),"+f"(d[23]),"+f"(d[24]),"+f"(d[25]),"+f"(d[26]),"+f"(d[27]),"+f"(d[28]),"+f"(d[29]),"+f"(d[30]),"+f"(d[31])
    : "r"(a0), "r"(a1), "r"(a2), "r"(a3), "l"(db), "r"(acc));
}

__device__ __forceinline__ void dual_softmax(const float (&p)[28], uint32_t (&phi)[4][7]) {
  constexpr float L2E = 1.4426950408889634f;
#pragma unroll
  for (int i = 0; i < 4; i++) {
    float mx = p[i], mn = p[i];
#pragma unroll
    for (int j = 1; j < 7; j++) { mx = fmaxf(mx, p[4 * j + i]); mn = fminf(mn, p[4 * j + i]); }
    mx = fmaxf(mx, __shfl_xor_sync(~0u, mx, 1)); mn = fminf(mn, __shfl_xor_sync(~0u, mn, 1));
    mx = fmaxf(mx, __shfl_xor_sync(~0u, mx, 2)); mn = fminf(mn, __shfl_xor_sync(~0u, mn, 2));
    float a[7], b[7], sa = 0.f, sb = 0.f;
    const float mxl = mx * L2E, mnl = mn * L2E;
#pragma unroll
    for (int j = 0; j < 7; j++) {
      a[j] = ex2(fmaf(p[4 * j + i], L2E, -mxl)); b[j] = ex2(fmaf(p[4 * j + i], -L2E, mnl));
      sa += a[j]; sb += b[j];
    }
    sa += __shfl_xor_sync(~0u, sa, 1); sb += __shfl_xor_sync(~0u, sb, 1);
    sa += __shfl_xor_sync(~0u, sa, 2); sb += __shfl_xor_sync(~0u, sb, 2);
    const float ra = __fdividef(1.f, sa), rb = __fdividef(1.f, sb);
#pragma unroll
    for (int j = 0; j < 7; j++) phi[i][j] = pack(a[j] * ra, b[j] * rb);
  }
}

struct Ring {
  uint32_t full, empty, base; int slot, par;
  __device__ __forceinline__ uint32_t acquire() { mbar_wait(full + slot * 8, par); return base + slot * SLOT; }
  __device__ __forceinline__ int advance() { int s = slot; if (++slot == NSLOT) { slot = 0; par ^= 1; } return s; }
  __device__ __forceinline__ void release(int s, bool elect) { if (elect) mbar_arrive(empty + s * 8); }
};
constexpr int FL_KV = 448, FL_ZERO = FL_KV + 16, FL_CS = FL_KV + 24, FL_DONE = FL_KV + 32;

__global__ void __launch_bounds__(384, 1)
fused_kernel(const __grid_constant__ CUtensorMap mQKV, const __grid_constant__ CUtensorMap mWO,
             const __grid_constant__ CUtensorMap mW1, const __grid_constant__ CUtensorMap mW2,
             const __grid_constant__ CUtensorMap mX,
             const __nv_bfloat16* __restrict__ x, const __nv_bfloat16* __restrict__ wphi,
             const __nv_bfloat16* __restrict__ b1, const __nv_bfloat16* __restrict__ b2,
             const __nv_bfloat16* __restrict__ wqkv, const __nv_bfloat16* __restrict__ wo, const __nv_bfloat16* __restrict__ w1,
             const __nv_bfloat16* __restrict__ w2, __nv_bfloat16* __restrict__ out) {
  extern __shared__ unsigned char smem_raw[];
  const uint32_t sb = (smem_u32(smem_raw) + 1023) & ~1023u;
  unsigned char* sg = smem_raw + (sb - smem_u32(smem_raw));
  const int tid = threadIdx.x, lane = tid & 31;
  const int G = blockIdx.x >> 3, r = blockIdx.x & 7;
  const uint32_t barFull = sb + OFF_BAR, barEmpty = barFull + 56, barA = barEmpty + 56, barCS = barA + 112;
  if (tid == 0) {
    for (int i = 0; i < NSLOT; i++) { mbar_init(barFull + i * 8, 1); mbar_init(barEmpty + i * 8, 2); }
    for (int i = 0; i < 14; i++) mbar_init(barA + i * 8, 1);
    mbar_init(barCS, 64);
    asm volatile("fence.mbarrier_init.release.cluster;" ::: "memory");
  }
  __syncthreads();
  const int wgid = __shfl_sync(~0u, tid >> 7, 0);
  if (wgid == 2) {
    asm volatile("setmaxnreg.dec.sync.aligned.u32 40;");
    if (tid == 256) {
      int slot = 0, par = 1;
      for (int it = 0; it < 2 * TILES_PER_LAYER; it++) {
        const int i = it >= TILES_PER_LAYER ? it - TILES_PER_LAYER : it;
        mbar_wait(barEmpty + slot * 8, par);
        const uint32_t dst = sb + OFF_RING + slot * SLOT, fb = barFull + slot * 8;
        mbar_expect(fb, i < 14 ? 12288 : SLOT);
        if (i < 14) tma3(dst, &mQKV, 56 * r, 32 * i, 0, fb);
        else if (i < 18) tma2(dst, &mWO, 56 * r, 112 * (i - 14), fb);
        else if (i < 32) tma3(dst, &mW1, 0, 32 * (i - 18), 7 * r, fb);
        else tma2(dst, &mW2, 64 * ((i - 32) >> 1), 224 * r + 112 * (i & 1), fb);
        if (++slot == NSLOT) { slot = 0; par ^= 1; }
      }
    } else if (tid >= 352) {
      if (lane < 14) {
        mbar_expect(barA + lane * 8, 8192);
        tma2(sb + lane * 8192, &mX, 64 * (lane % 7), G * 128 + 64 * (lane / 7), barA + lane * 8);
      } else if (lane < 16) {
        const char* src = lane == 14 ? (const char*)wo + blockIdx.x * 3136 : (const char*)w2 + blockIdx.x * 12544;
        asm volatile("cp.async.bulk.prefetch.L2.global [%0], %1;" ::"l"(src), "r"(lane == 14 ? 3136 : 12544) : "memory");
      }
    } else if (tid >= 288) {
      unsigned ep;
      asm volatile("ld.relaxed.gpu.global.u32 %0, [%1];" : "=r"(ep) : "l"(gFlag + FL_DONE * 32) : "memory");
      const int idx = tid - 288;
      bar_sync<4, 320>();
      if (lane == 0) { flag_arrive(gFlag + (FL_CS + r) * 32); flag_wait(gFlag + (FL_CS + r) * 32, (ep / NCTA + 1) * 32); }
      __syncwarp();
      if (idx < 52) {
#pragma unroll 1
        for (int hh = 0; hh < 2; hh++) {
          float4 a = make_float4(0.f, 0.f, 0.f, 0.f);
#pragma unroll 4
          for (int i = 0; i < 16; i++) { const float4 v = __ldcg(gCS + (r * 16 + i) * 104 + hh * 52 + idx); a.x += v.x; a.y += v.y; a.z += v.z; a.w += v.w; }
          reinterpret_cast<float4*>(sg + OFF_CS)[hh * 52 + idx] = a;
        }
      }
      mbar_arrive(barCS);
    }
  } else {
  asm volatile("setmaxnreg.inc.sync.aligned.u32 232;");
  const int c = wgid, w = (tid >> 5) & 3, g = lane >> 2, t = lane & 3;
  const bool elect = (tid & 127) == 0;
  const uint32_t abuf = sb + c * ABYTES, barAc = barA + c * 56;
  const int row0 = G * 128 + c * 64;
  unsigned epoch;
  asm volatile("ld.relaxed.gpu.global.u32 %0, [%1];" : "=r"(epoch) : "l"(gFlag + FL_DONE * 32) : "memory");
  STAMP(24);
  float mean[2], rstd[2];
  {
    uint32_t wv[7];
#pragma unroll
    for (int i = 0; i < 7; i++)
      wv[i] = __ldg(reinterpret_cast<const unsigned short*>(wphi) + (56 * r + i * 8 + (tid >> 5)) * 28 + min(lane, 27));
    const float bv = __bfloat162float(b1[224 * r + min(tid, 223)]);
    {
      const int ch = min(tid >> 2, 48), k0 = G * 28 + t * 7;
      const bool q = ch < 21;
      const int p = ch / 7;
      const uint4* src = q ? reinterpret_cast<const uint4*>(wqkv + (size_t)k0 * 1344 + p * 448 + 56 * r) + (ch - 7 * p)
                           : reinterpret_cast<const uint4*>(w1 + (size_t)k0 * 1792 + 224 * r) + (ch - 21);
      uint4 u[7];
#pragma unroll
      for (int i = 0; i < 7; i++) u[i] = __ldg(src + i * (q ? 168 : 224));
      float s[8] = {};
#pragma unroll
      for (int i = 0; i < 7; i++) { s[0] += lo(u[i].x); s[1] += hi(u[i].x); s[2] += lo(u[i].y); s[3] += hi(u[i].y); s[4] += lo(u[i].z); s[5] += hi(u[i].z); s[6] += lo(u[i].w); s[7] += hi(u[i].w); }
#pragma unroll
      for (int i = 0; i < 8; i++) { s[i] += __shfl_xor_sync(~0u, s[i], 1); s[i] += __shfl_xor_sync(~0u, s[i], 2); }
      if (t < 2 && tid < 196) gCS[(r * 16 + G) * 104 + (q ? ch + p : ch + 3) * 2 + t] = t ? make_float4(s[4], s[5], s[6], s[7]) : make_float4(s[0], s[1], s[2], s[3]);
      asm volatile("bar.arrive 4, 320;" ::: "memory");
    }
    if (G == 0) {
#pragma unroll 1
      for (int i = tid; i < 2 * 1280; i += 256) gKV[((i >= 1280) * 7 + r) * 1280 + i] = make_float4(0.f, 0.f, 0.f, 0.f);
    }
#pragma unroll 1
    for (int hh = 0; hh < 2; hh++) {
      const uint4* src = reinterpret_cast<const uint4*>(x + (size_t)(row0 + w * 16 + hh * 8 + g) * DM) + t;
      uint4 v[14];
#pragma unroll
      for (int k = 0; k < 14; k++) v[k] = __ldg(src + k * 4);
      float s = 0.f, q = 0.f;
#pragma unroll
      for (int k = 0; k < 14; k++) s += (lo(v[k].x) + hi(v[k].x)) + (lo(v[k].y) + hi(v[k].y)) + (lo(v[k].z) + hi(v[k].z)) + (lo(v[k].w) + hi(v[k].w));
      s += __shfl_xor_sync(~0u, s, 1); s += __shfl_xor_sync(~0u, s, 2);
      s *= 1.f / DM;
#pragma unroll
      for (int k = 0; k < 14; k++) {
        const uint32_t e[4] = {v[k].x, v[k].y, v[k].z, v[k].w};
#pragma unroll
        for (int z = 0; z < 4; z++) { float a = lo(e[z]) - s, b = hi(e[z]) - s; q = fmaf(a, a, q); q = fmaf(b, b, q); }
      }
      q += __shfl_xor_sync(~0u, q, 1); q += __shfl_xor_sync(~0u, q, 2);
      q = rsqrtf(q * (1.f / DM) + 1e-5f);
      STAMP(25 + hh);
      if (hh) { mean[1] = s; rstd[1] = q; } else { mean[0] = s; rstd[0] = q; mean[1] = 0.f; rstd[1] = 0.f; }
    }
#pragma unroll
    for (int i = 0; i < 8; i++) {
      const int k = i * 8 + (tid >> 5);
      *reinterpret_cast<uint32_t*>(sg + OFF_WPHI + k * 128 + ((g ^ (k & 7)) << 4) + t * 4) = (i < 7 && lane < 28) ? wv[i % 7] << (k >= 28 ? 16 : 0) : 0u;
    }
    if (tid < 224) reinterpret_cast<float*>(sg + OFF_B1)[tid] = bv;
    fence_async_smem();
    bar_sync<3, 256>();
    epoch = epoch / NCTA + 1;
    if (G == 0 && tid == 0) flag_arrive(gFlag + (FL_ZERO + r) * 32);
  }
  STAMP(0);
  Ring ring{barFull, barEmpty, sb + OFF_RING, 0, 0};
  int apar = 0;
  const uint32_t stsm_off = (w * 16 + ((lane >> 3) & 1) * 8 + (lane & 7)) * 128;
  const uint32_t stsm_hi = lane >> 4;
  const uint64_t dA = mkdesc(abuf, 1024, 128, 0);

  auto gather = [&](unsigned* fl, const unsigned char* img) {
    __syncwarp();
    if (lane == 0) flag_arrive(fl);
    if (w == 0) {
      STAMP(27);
      if (lane == 0) flag_wait(fl, epoch * 32);
      __syncwarp();
      STAMP(28);
      if (lane < 7) { fence_async(); mbar_expect(barAc + lane * 8, 8192); bulk_ld(abuf + lane * 8192, img + lane * 8192, 8192, barAc + lane * 8); }
    }
    __syncwarp();
    apar ^= 1;
  };
  auto slice_off = [&](int j, int hh) -> uint32_t {
    return (7 * r + j) * 1024 + (w * 2 + hh) * 128 + lane * 4;
  };
  auto load_stats = [&](const float2* st) {
#pragma unroll
    for (int hh = 0; hh < 2; hh++) {
      const uint4 u = ldcg4(st + (size_t)(row0 + w * 16 + hh * 8 + g) * 8 + 2 * t);
      const float m0 = __uint_as_float(u.x), m1 = __uint_as_float(u.z);
      float m = m0 + m1;
      m += __shfl_xor_sync(~0u, m, 1); m += __shfl_xor_sync(~0u, m, 2);
      m *= 0.125f;
      float q = __uint_as_float(u.y) + __uint_as_float(u.w) + 56.f * ((m0 - m) * (m0 - m) + (m1 - m) * (m1 - m));
      q += __shfl_xor_sync(~0u, q, 1); q += __shfl_xor_sync(~0u, q, 2);
      mean[hh] = m; rstd[hh] = rsqrtf(q * (1.f / DM) + 1e-5f);
    }
  };

#pragma unroll 1
  for (int layer = 0; layer < 2; layer++) {
    unsigned* const fl = gFlag + (layer * 32 + G * 2 + c) * 7 * 32;
    uint32_t phiq[4][7], xs[7][2];
    {
      float acc[92]; reg_def(acc);
      const uint64_t dQ = layer ? dA : mkdesc(abuf, 16, 1024, 1);
      const int kstep = layer ? 128 : 2;
      int prev = 0;
#pragma unroll 1
      for (int st = 0; st < 14; st++) {
        if (!(st & 1)) mbar_wait(barAc + (st >> 1) * 8, apar);
        const uint64_t da = dQ + (st >> 1) * 512 + (st & 1) * 2 * kstep, db = mkdesc(ring.acquire(), 4096, 1024, 1);
        wg_fence();
        mma_ss_184(acc, da, db, st);
        mma_ss_184(acc, da + kstep, db + 128, 1);
        wg_commit();
        if (st > 0) { wg_wait<1>(); ring.release(prev, elect); }
        prev = ring.advance();
      }
      if (layer) load_stats(gStat + 2048 * 8); else mbar_wait(barCS, 0);
#pragma unroll
      for (int j = 0; j < 7; j++) {
        const int ci = 7 * r + j;
        const uint32_t a = abuf + (layer ? slice_off(j, 0) : (ci >> 3) * 8192 + (w * 16 + g) * 128 + (((ci & 7) ^ g) << 4) + t * 4);
        xs[j][0] = lds32(a); xs[j][1] = lds32(a + (layer ? 128 : 1024));
      }
      wg_wait<0>(); reg_fence(acc);
      ring.release(prev, elect);
      STAMP(1 + layer * 12);
      uint32_t f[3][14];
      {
        const float2* cs = reinterpret_cast<const float2*>(sg + OFF_CS) + t;
        const float mr0 = -mean[0] * rstd[0], mr1 = -mean[1] * rstd[1];
#pragma unroll
        for (int p = 0; p < 3; p++)
#pragma unroll
          for (int j = 0; j < 7; j++) {
            const float2 s = cs[p * 32 + j * 4];
            const int b = p * 32 + j * 4;
            f[p][2 * j] = pack(fmaf(acc[b], rstd[0], s.x * mr0), fmaf(acc[b + 1], rstd[0], s.y * mr0));
            f[p][2 * j + 1] = pack(fmaf(acc[b + 2], rstd[1], s.x * mr1), fmaf(acc[b + 3], rstd[1], s.y * mr1));
          }
      }
      float pk[28], pq[28]; reg_def(pk); reg_def(pq);
      const uint64_t dW = mkdesc(sb + OFF_WPHI, 4096, 1024, 1);
      wg_fence();
#pragma unroll
      for (int s = 0; s < 4; s++)
        mma_rs_56(pk, f[1][4 * s], f[1][4 * s + 1], s < 3 ? f[1][(4 * s + 2) % 14] : 0u, s < 3 ? f[1][(4 * s + 3) % 14] : 0u, dW + s * 128, s);
      wg_commit();
#pragma unroll
      for (int s = 0; s < 4; s++)
        mma_rs_56(pq, f[0][4 * s], f[0][4 * s + 1], s < 3 ? f[0][(4 * s + 2) % 14] : 0u, s < 3 ? f[0][(4 * s + 3) % 14] : 0u, dW + s * 128, s);
      wg_commit();
      bar_wg(c);
      const uint32_t srow = abuf + stsm_off, ones = t == 0 ? 0x3F803F80u : 0u;
#pragma unroll
      for (int jp = 0; jp < 4; jp++)
        stsm4(srow + 16384 + (((2 * jp + stsm_hi) ^ (lane & 7)) << 4), f[2][4 * jp], f[2][4 * jp + 1],
              jp < 3 ? f[2][(4 * jp + 2) % 14] : ones, jp < 3 ? f[2][(4 * jp + 3) % 14] : ones);
      wg_wait<0>(); reg_fence(pk); reg_fence(pq);
#pragma unroll 1
      for (int pass = 0; pass < 2; pass++) {
        dual_softmax(pk, phiq);
        if (pass) break;
#pragma unroll
        for (int e = 0; e < 2; e++)
#pragma unroll
          for (int jp = 0; jp < 4; jp++)
            stsm4(srow + e * 8192 + (((2 * jp + stsm_hi) ^ (lane & 7)) << 4), phiq[e][2 * jp], phiq[2 + e][2 * jp],
                  jp < 3 ? phiq[e][(2 * jp + 1) % 7] : 0u, jp < 3 ? phiq[2 + e][(2 * jp + 1) % 7] : 0u);
        fence_async_smem();
        bar_sync<3, 256>();
        float kv[32]; reg_def(kv);
        const uint64_t dP = mkdesc(sb + c * 8192, 4096, 1024, 1), dV = mkdesc(sb + 16384, 4096, 1024, 1);
        wg_fence();
#pragma unroll
        for (int s = 0; s < 8; s++) mma_ss_64t(kv, dP + (s >> 2) * (ABYTES / 16) + (s & 3) * 128, dV + (s >> 2) * (ABYTES / 16) + (s & 3) * 128, s);
        wg_commit();
        if (layer == 0 && lane == 0) flag_wait(gFlag + (FL_ZERO + r) * 32, epoch);
        __syncwarp();
        wg_wait<0>(); reg_fence(kv);
        float4* kvg = gKV + ((layer * 8 + r) * 2 + c) * 640 + (tid & 127);
#pragma unroll
        for (int i = 0; i < 5; i++) {
          float v0, v1, v2, v3;
          if (i == 4) { v0 = kv[28]; v1 = kv[29]; v2 = kv[30]; v3 = kv[31]; }
          else { v0 = c ? kv[12 + 4 * i] : kv[4 * i]; v1 = c ? kv[13 + 4 * i] : kv[1 + 4 * i]; v2 = c ? kv[14 + 4 * i] : kv[2 + 4 * i]; v3 = c ? kv[15 + 4 * i] : kv[3 + 4 * i]; }
          const bool use = i == 4 ? t == 0 : (i == 0 ? (c == 0 || t >= 2) : (i == 3 ? (c == 1 || t < 2) : true));
          if (use) asm volatile("red.relaxed.gpu.global.add.v4.f32 [%0], {%1,%2,%3,%4};" ::"l"(kvg + i * 128), "f"(v0), "f"(v1), "f"(v2), "f"(v3) : "memory");
        }
        __syncwarp();
        if (lane == 0) flag_arrive(gFlag + (FL_KV + layer * 8 + r) * 32);
        __syncwarp();
        STAMP(2 + layer * 12);
#pragma unroll
        for (int i = 0; i < 28; i++) pk[i] = pq[i];
      }
    }
    {
      if (elect) flag_wait(gFlag + (FL_KV + layer * 8 + r) * 32, epoch * 128);
      bar_wg(c);
      STAMP(3 + layer * 12);
      const float4* kvg = gKV + (layer * 8 + r) * 1280 + (tid & 127);
      uint4 kk[2][5];
#pragma unroll
      for (int e = 0; e < 2; e++)
#pragma unroll
        for (int i = 0; i < 5; i++) kk[e][i] = ldcg4(kvg + e * 640 + i * 128);
      const uint32_t srow = abuf + 24576 + stsm_off;
#pragma unroll
      for (int e = 0; e < 2; e++) {
        uint32_t f[8][2];
#pragma unroll
        for (int j = 0; j < 8; j++) { f[j][0] = 0u; f[j][1] = 0u; }
#pragma unroll
        for (int i = 0; i < 4; i++) {
          f[i + 3 * e][0] = pack(__uint_as_float(kk[e][i].x), __uint_as_float(kk[e][i].y));
          f[i + 3 * e][1] = pack(__uint_as_float(kk[e][i].z), __uint_as_float(kk[e][i].w));
        }
        f[7][0] = e ? pack(0.f, __uint_as_float(kk[e][4].y)) : pack(__uint_as_float(kk[e][4].x), 0.f);
        f[7][1] = e ? pack(0.f, __uint_as_float(kk[e][4].w)) : pack(__uint_as_float(kk[e][4].z), 0.f);
#pragma unroll
        for (int jp = 0; jp < 4; jp++)
          stsm4(srow + e * 8192 + (((2 * jp + stsm_hi) ^ (lane & 7)) << 4), f[2 * jp][0], f[2 * jp][1], f[2 * jp + 1][0], f[2 * jp + 1][1]);
      }
      fence_async_smem();
      bar_wg(c);
      float num[32]; reg_def(num);
      const uint64_t dK = mkdesc(abuf + 24576, 4096, 1024, 1);
      wg_fence();
#pragma unroll
      for (int e = 0; e < 2; e++)
#pragma unroll
        for (int s = 0; s < 4; s++)
          mma_rs_64(num, phiq[e][2 * s], phiq[2 + e][2 * s], s < 3 ? phiq[e][(2 * s + 1) % 7] : 0u, s < 3 ? phiq[2 + e][(2 * s + 1) % 7] : 0u,
                    dK + e * 512 + s * 128, e + s);
      wg_commit();
      wg_wait<0>(); reg_fence(num);
      float rd[4];
#pragma unroll
      for (int i = 0; i < 4; i++) rd[i] = __fdividef(1.f, __shfl_sync(~0u, num[28 + i], lane & ~3) + 1e-6f);
      unsigned char* img = gImg + (size_t)(G * 2 + c) * ABYTES;
#pragma unroll
      for (int j = 0; j < 7; j++) {
        const bool hb = j > 3 || (j == 3 && t >= 2);
        const float r0 = hb ? rd[1] : rd[0], r1 = hb ? rd[3] : rd[2];
        *reinterpret_cast<uint32_t*>(img + slice_off(j, 0)) = pack(num[4 * j] * r0, num[4 * j + 1] * r0);
        *reinterpret_cast<uint32_t*>(img + slice_off(j, 1)) = pack(num[4 * j + 2] * r1, num[4 * j + 3] * r1);
      }
      STAMP(4 + layer * 12);
      gather(fl, img);
      STAMP(5 + layer * 12);
    }
    {
      float acc[28]; reg_def(acc);
      int prev = 0;
#pragma unroll 1
      for (int st = 0; st < 4; st++) {
        mbar_wait(barAc + (st * 7 + 3) / 4 * 8, apar);
        mbar_wait(barAc + (st * 7 + 6) / 4 * 8, apar);
        const uint64_t db = mkdesc(ring.acquire(), 4096, 1024, 1);
        wg_fence();
#pragma unroll
        for (int s = 0; s < 7; s++) { const int ks = st * 7 + s; mma_ss_56(acc, dA + ks * 128, db + s * 128, ks); }
        wg_commit();
        if (st > 0) { wg_wait<1>(); ring.release(prev, elect); }
        prev = ring.advance();
      }
      wg_wait<0>(); reg_fence(acc);
      ring.release(prev, elect);
      unsigned char* img = gImg + (size_t)(32 + G * 2 + c) * ABYTES;
#pragma unroll
      for (int hh = 0; hh < 2; hh++) {
        float s = 0.f, q = 0.f;
#pragma unroll
        for (int j = 0; j < 7; j++) {
          xs[j][hh] = pack(lo(xs[j][hh]) + acc[4 * j + 2 * hh], hi(xs[j][hh]) + acc[4 * j + 2 * hh + 1]);
          *reinterpret_cast<uint32_t*>(img + slice_off(j, hh)) = xs[j][hh];
          s += lo(xs[j][hh]) + hi(xs[j][hh]);
        }
        s += __shfl_xor_sync(~0u, s, 1); s += __shfl_xor_sync(~0u, s, 2);
        s *= 1.f / 56.f;
#pragma unroll
        for (int j = 0; j < 7; j++) { const float a = lo(xs[j][hh]) - s, b = hi(xs[j][hh]) - s; q = fmaf(a, a, q); q = fmaf(b, b, q); }
        q += __shfl_xor_sync(~0u, q, 1); q += __shfl_xor_sync(~0u, q, 2);
        if (t == 0) gStat[(size_t)(row0 + w * 16 + hh * 8 + g) * 8 + r] = make_float2(s, q);
      }
      STAMP(6 + layer * 12);
      gather(fl + 32, img);
      STAMP(7 + layer * 12);
    }
    {
      uint32_t hf[28][2];
      {
        float acc[112]; reg_def(acc);
        int prev = 0;
#pragma unroll 1
        for (int st = 0; st < 14; st++) {
          if (!(st & 1)) mbar_wait(barAc + (st >> 1) * 8, apar);
          const uint64_t da = dA + st * 256, db = mkdesc(ring.acquire(), 2048, 512, 2);
          wg_fence();
          mma_ss_224(acc, da, db, st);
          mma_ss_224(acc, da + 128, db + 64, 1);
          wg_commit();
          if (st > 0) { wg_wait<1>(); ring.release(prev, elect); }
          prev = ring.advance();
        }
        load_stats(gStat);
        wg_wait<0>(); reg_fence(acc);
        ring.release(prev, elect);
        STAMP(8 + layer * 12);
        const float2* bs = reinterpret_cast<const float2*>(sg + OFF_B1) + t;
        const float2* cs = reinterpret_cast<const float2*>(sg + OFF_CS + 768) + t;
        const float mr0 = -mean[0] * rstd[0], mr1 = -mean[1] * rstd[1];
#pragma unroll
        for (int j = 0; j < 28; j++) {
          const float2 b = bs[4 * j], s = cs[4 * j];
          const float h0 = fmaxf(fmaf(acc[4 * j], rstd[0], fmaf(s.x, mr0, b.x)), 0.f), h1 = fmaxf(fmaf(acc[4 * j + 1], rstd[0], fmaf(s.y, mr0, b.y)), 0.f);
          const float h2 = fmaxf(fmaf(acc[4 * j + 2], rstd[1], fmaf(s.x, mr1, b.x)), 0.f), h3 = fmaxf(fmaf(acc[4 * j + 3], rstd[1], fmaf(s.y, mr1, b.y)), 0.f);
          hf[j][0] = pack(h0 * h0, h1 * h1); hf[j][1] = pack(h2 * h2, h3 * h3);
        }
      }
      unsigned char* pdst = gP + (size_t)(((G * 2 + c) * 8 + 2 * w) * 8 + r) * 7168 + lane * 8;
      uint2 pk[8] = {};
#pragma unroll 1
      for (int ch = 0; ch < 7; ch++) {
        float acc[32]; reg_def(acc);
        int sl0 = 0, sl1 = 0;
#pragma unroll
        for (int hk = 0; hk < 2; hk++) {
          const uint64_t db = mkdesc(ring.acquire(), 4096, 1024, 1);
          wg_fence();
#pragma unroll
          for (int s = 0; s < 7; s++) { const int ks = hk * 7 + s; mma_rs_64(acc, hf[2 * ks][0], hf[2 * ks][1], hf[2 * ks + 1][0], hf[2 * ks + 1][1], db + s * 128, ks); }
          wg_commit();
          if (hk) sl1 = ring.advance(); else sl0 = ring.advance();
        }
        if (ch > 0) {
#pragma unroll
          for (int i = 0; i < 8; i++) *reinterpret_cast<uint2*>(pdst + (i & 1) * (8 * 7168) + (i >> 1) * 256) = pk[i];
          pdst += 1024;
        }
        wg_wait<1>(); ring.release(sl0, elect);
        wg_wait<0>(); reg_fence(acc); ring.release(sl1, elect);
#pragma unroll
        for (int i = 0; i < 8; i++) {
          const int b = (i >> 1) * 8 + (i & 1) * 2;
          pk[i] = make_uint2(pack(acc[b], acc[b + 1]), pack(acc[b + 4], acc[b + 5]));
        }
      }
#pragma unroll
      for (int i = 0; i < 8; i++) *reinterpret_cast<uint2*>(pdst + (i & 1) * (8 * 7168) + (i >> 1) * 256) = pk[i];
      STAMP(9 + layer * 12);
    }
    {
      uint32_t bx[14];
#pragma unroll
      for (int j = 0; j < 14; j++) bx[j] = __ldg(reinterpret_cast<const uint32_t*>(b2 + w * 112 + j * 8 + 2 * t));
      __syncwarp();
      if (lane == 0) { flag_arrive(fl + (3 + w) * 32); flag_wait(fl + (3 + (r >> 1)) * 32, epoch * 8); }
      __syncwarp();
      STAMP(10 + layer * 12);
      const unsigned char* psrc = gP + (size_t)(((G * 2 + c) * 8 + r) * 8) * 7168 + w * 1792 + lane * 8;
      unsigned char* img = gImg + (size_t)(64 + G * 2 + c) * ABYTES;
      uint2 pv[8][7];
#pragma unroll
      for (int s = 0; s < 8; s++)
#pragma unroll
        for (int i = 0; i < 7; i++) pv[s][i] = ldcg2(psrc + s * 7168 + i * 256);
      const uint32_t off = w * 14336 + r * 128 + lane * 4;
      unsigned char* dst = layer ? reinterpret_cast<unsigned char*>(out + (size_t)(row0 + r * 8 + g) * DM + w * 112 + 2 * t) : img + off;
      float sm = 0.f, q = 0.f;
#pragma unroll
      for (int j = 0; j < 14; j++) {
        float y0 = lo(bx[j]), y1 = hi(bx[j]);
        const uint32_t xo = lds32(abuf + off + j * 1024);
        y0 += lo(xo); y1 += hi(xo);
#pragma unroll
        for (int s = 0; s < 8; s++) { const uint32_t u = (j & 1) ? pv[s][j >> 1].y : pv[s][j >> 1].x; y0 += lo(u); y1 += hi(u); }
        bx[j] = pack(y0, y1);
        *reinterpret_cast<uint32_t*>(dst + j * (layer ? 16 : 1024)) = bx[j];
        sm += lo(bx[j]) + hi(bx[j]);
      }
      if (layer) break;
      sm += __shfl_xor_sync(~0u, sm, 1); sm += __shfl_xor_sync(~0u, sm, 2);
      sm *= 1.f / 112.f;
#pragma unroll
      for (int j = 0; j < 14; j++) { const float a = lo(bx[j]) - sm, b = hi(bx[j]) - sm; q = fmaf(a, a, q); q = fmaf(b, b, q); }
      q += __shfl_xor_sync(~0u, q, 1); q += __shfl_xor_sync(~0u, q, 2);
      if (t < 2) gStat[(size_t)(2048 + row0 + r * 8 + g) * 8 + 2 * w + t] = make_float2(sm, q * 0.5f);
      STAMP(11);
      gather(fl + 64, img);
      STAMP(12);
    }
  }
  STAMP(30);
  if (tid == 0) asm volatile("red.relaxed.gpu.global.add.u32 [%0], 1;" ::"l"(gFlag + FL_DONE * 32) : "memory");
  }
}

typedef CUresult (*EncFn)(CUtensorMap*, CUtensorMapDataType, cuuint32_t, void*, const cuuint64_t*, const cuuint64_t*,
                          const cuuint32_t*, const cuuint32_t*, CUtensorMapInterleave, CUtensorMapSwizzle,
                          CUtensorMapL2promotion, CUtensorMapFloatOOBfill);

void make_map(EncFn enc, CUtensorMap* m, void* p, int rank, uint64_t d0, uint64_t d1, uint64_t d2, uint64_t s1, uint64_t s2,
              uint32_t b0, uint32_t b1, uint32_t b2, CUtensorMapSwizzle sw) {
  cuuint64_t dims[3] = {d0, d1, d2}, strides[2] = {s1, s2};
  cuuint32_t box[3] = {b0, b1, b2}, es[3] = {1, 1, 1};
  enc(m, CU_TENSOR_MAP_DATA_TYPE_BFLOAT16, rank, p, dims, strides, box, es, CU_TENSOR_MAP_INTERLEAVE_NONE, sw,
      CU_TENSOR_MAP_L2_PROMOTION_L2_256B, CU_TENSOR_MAP_FLOAT_OOB_FILL_NONE);
}

}

extern "C" void kernel_launch(void* const* d_in, const int* in_sizes, int n_in, void* d_out, int out_size) {
  static EncFn enc = nullptr;
  if (!enc) {
    cudaDriverEntryPointQueryResult st;
    void* fn = nullptr;
    cudaGetDriverEntryPoint("cuTensorMapEncodeTiled", &fn, cudaEnableDefault, &st);
    enc = (EncFn)fn;
    cudaFuncSetAttribute(fused_kernel, cudaFuncAttributeMaxDynamicSharedMemorySize, SMEM_BYTES);
  }
  CUtensorMap mQKV, mWO, mW1, mW2, mX;
  make_map(enc, &mQKV, d_in[1], 3, 448, 448, 3, 2688, 896, 64, 32, 3, CU_TENSOR_MAP_SWIZZLE_128B);
  make_map(enc, &mWO, d_in[3], 2, 448, 448, 1, 896, 0, 64, 112, 1, CU_TENSOR_MAP_SWIZZLE_128B);
  make_map(enc, &mW1, d_in[5], 3, 32, 448, 56, 3584, 64, 32, 32, 7, CU_TENSOR_MAP_SWIZZLE_64B);
  make_map(enc, &mW2, d_in[7], 2, 448, 1792, 1, 896, 0, 64, 112, 1, CU_TENSOR_MAP_SWIZZLE_128B);
  make_map(enc, &mX, d_in[0], 2, 448, 2048, 1, 896, 0, 64, 64, 1, CU_TENSOR_MAP_SWIZZLE_128B);
  fused_kernel<<<NCTA, 384, SMEM_BYTES, cudaStreamPerThread>>>(
      mQKV, mWO, mW1, mW2, mX, (const __nv_bfloat16*)d_in[0], (const __nv_bfloat16*)d_in[2], (const __nv_bfloat16*)d_in[6],
      (const __nv_bfloat16*)d_in[8], (const __nv_bfloat16*)d_in[1], (const __nv_bfloat16*)d_in[3], (const __nv_bfloat16*)d_in[5],
      (const __nv_bfloat16*)d_in[7], (__nv_bfloat16*)d_out);
}
```

```cpp
#include <cuda_runtime.h>
#include <cuda_bf16.h>
#include <cuda.h>
#include <stdint.h>

namespace {

constexpr int DM = 448, NCTA = 128;
constexpr int ABYTES = 57344;
constexpr int SLOT = 14336, NSLOT = 7;
constexpr int OFF_RING = 2 * ABYTES;
constexpr int OFF_WPHI = OFF_RING + NSLOT * SLOT;
constexpr int OFF_B1 = OFF_WPHI + 8192;
constexpr int OFF_CS = OFF_B1 + 896;
constexpr int OFF_BAR = OFF_CS + 1664;
constexpr int SMEM_BYTES = OFF_BAR + 256 + 1024;
constexpr int TILES_PER_LAYER = 46;

__device__ __align__(1024) unsigned char gP[16 * 2 * 8 * 8 * 7168];
__device__ __align__(1024) unsigned char gImg[3 * 32 * ABYTES];
__device__ __align__(1024) float2 gStat[2 * 2048 * 8];
__device__ __align__(1024) float4 gKV[2 * 8 * 2 * 5 * 128];
__device__ __align__(1024) float4 gCS[8 * 16 * 104];
__device__ __align__(128) unsigned gFlag[(2 * 32 * 7 + 32 + 1) * 32];
#define STAMP(i)

__device__ __forceinline__ uint32_t smem_u32(const void* p) { return (uint32_t)__cvta_generic_to_shared(p); }
__device__ __forceinline__ void mbar_init(uint32_t b, int c) { asm volatile("mbarrier.init.shared::cta.b64 [%0], %1;" ::"r"(b), "r"(c)); }
__device__ __forceinline__ void mbar_expect(uint32_t b, int bytes) { asm volatile("mbarrier.arrive.expect_tx.shared::cta.b64 _, [%0], %1;" ::"r"(b), "r"(bytes) : "memory"); }
__device__ __forceinline__ void mbar_arrive(uint32_t b) { asm volatile("mbarrier.arrive.shared::cta.b64 _, [%0];" ::"r"(b) : "memory"); }
__device__ __forceinline__ void mbar_wait(uint32_t b, int par) {
  uint32_t ok; int n = 0;
  while (true) {
    asm volatile("{.reg .pred p; mbarrier.try_wait.parity.shared::cta.b64 p, [%1], %2; selp.u32 %0,1,0,p;}" : "=r"(ok) : "r"(b), "r"(par) : "memory");
    if (ok) break;
    if (++n > (1 << 22)) break;
  }
}
__device__ __forceinline__ void flag_wait(const unsigned* f, unsigned target) {
  unsigned v; int n = 0;
  while (true) {
    asm volatile("ld.acquire.gpu.global.u32 %0, [%1];" : "=r"(v) : "l"(f) : "memory");
    if ((int)(v - target) >= 0) break;
    if (++n > (1 << 21)) break;
  }
}
__device__ __forceinline__ void flag_arrive(unsigned* f) { asm volatile("red.release.gpu.global.add.u32 [%0], 1;" ::"l"(f) : "memory"); }
__device__ __forceinline__ void fence_async() { asm volatile("fence.proxy.async.global;" ::: "memory"); }
__device__ __forceinline__ void fence_async_smem() { asm volatile("fence.proxy.async.shared::cta;" ::: "memory"); }
template <int ID, int N> __device__ __forceinline__ void bar_sync() { asm volatile("bar.sync %0, %1;" ::"n"(ID), "n"(N) : "memory"); }
__device__ __forceinline__ void bar_wg(int c) { if (c) bar_sync<2, 128>(); else bar_sync<1, 128>(); }
__device__ __forceinline__ void wg_fence() { asm volatile("wgmma.fence.sync.aligned;" ::: "memory"); }
__device__ __forceinline__ void wg_commit() { asm volatile("wgmma.commit_group.sync.aligned;" ::: "memory"); }
template <int N> __device__ __forceinline__ void wg_wait() { asm volatile("wgmma.wait_group.sync.aligned %0;" ::"n"(N) : "memory"); }
template <int N> __device__ __forceinline__ void reg_fence(float (&d)[N]) {
#pragma unroll
  for (int i = 0; i < N; i++) asm volatile("" : "+f"(d[i])::"memory");
}
template <int N> __device__ __forceinline__ void reg_def(float (&d)[N]) {
#pragma unroll
  for (int i = 0; i < N; i++) d[i] = 0.f;
}
__device__ __forceinline__ uint64_t mkdesc(uint32_t addr, uint32_t lbo, uint32_t sbo, uint64_t swz) {
  return (uint64_t)((addr & 0x3FFFF) >> 4) | ((uint64_t)(lbo >> 4) << 16) | ((uint64_t)(sbo >> 4) << 32) | (swz << 62);
}
__device__ __forceinline__ uint32_t pack(float a, float b) {
  uint32_t r; asm("cvt.rn.bf16x2.f32 %0, %1, %2;" : "=r"(r) : "f"(b), "f"(a)); return r;
}
__device__ __forceinline__ float lo(uint32_t u) { return __uint_as_float(u << 16); }
__device__ __forceinline__ float hi(uint32_t u) { return __uint_as_float(u & 0xFFFF0000u); }
__device__ __forceinline__ float ex2(float x) { float y; asm("ex2.approx.ftz.f32 %0, %1;" : "=f"(y) : "f"(x)); return y; }
__device__ __forceinline__ void stsm4(uint32_t a, uint32_t r0, uint32_t r1, uint32_t r2, uint32_t r3) {
  asm volatile("stmatrix.sync.aligned.m8n8.x4.shared.b16 [%0], {%1,%2,%3,%4};" ::"r"(a), "r"(r0), "r"(r1), "r"(r2), "r"(r3) : "memory");
}
__device__ __forceinline__ void tma3(uint32_t dst, const CUtensorMap* m, int c0, int c1, int c2, uint32_t bar) {
  asm volatile("cp.async.bulk.tensor.3d.shared::cluster.global.mbarrier::complete_tx::bytes [%0], [%1, {%3,%4,%5}], [%2];"
               ::"r"(dst), "l"(m), "r"(bar), "r"(c0), "r"(c1), "r"(c2) : "memory");
}
__device__ __forceinline__ void tma2(uint32_t dst, const CUtensorMap* m, int c0, int c1, uint32_t bar) {
  asm volatile("cp.async.bulk.tensor.2d.shared::cluster.global.mbarrier::complete_tx::bytes [%0], [%1, {%3,%4}], [%2];"
               ::"r"(dst), "l"(m), "r"(bar), "r"(c0), "r"(c1) : "memory");
}
__device__ __forceinline__ uint32_t lds32(uint32_t a) { uint32_t v; asm volatile("ld.shared.u32 %0, [%1];" : "=r"(v) : "r"(a) : "memory"); return v; }
__device__ __forceinline__ void bulk_ld(uint32_t dst, const void* src, int bytes, uint32_t bar) {
  asm volatile("cp.async.bulk.shared::cluster.global.mbarrier::complete_tx::bytes [%0], [%1], %2, [%3];" ::"r"(dst), "l"(src), "r"(bytes), "r"(bar) : "memory");
}
__device__ __forceinline__ uint4 ldcg4(const void* p) {
  uint4 v; asm volatile("ld.global.cg.v4.u32 {%0,%1,%2,%3}, [%4];" : "=r"(v.x), "=r"(v.y), "=r"(v.z), "=r"(v.w) : "l"(p) : "memory"); return v;
}

__device__ __forceinline__ uint2 ldcg2(const void* p) {
  uint2 v; asm volatile("ld.global.cg.v2.u32 {%0,%1}, [%2];" : "=r"(v.x), "=r"(v.y) : "l"(p) : "memory"); return v;
}

__device__ __forceinline__ void mma_ss_184(float (&d)[92], uint64_t da, uint64_t db, int acc) {
  asm volatile("{.reg .pred p; setp.ne.b32 p, %94, 0;\n"
    "wgmma.mma_async.sync.aligned.m64n184k16.f32.bf16.bf16 {%0,%1,%2,%3,%4,%5,%6,%7,%8,%9,%10,%11,%12,%13,%14,%15,%16,%17,%18,%19,%20,%21,%22,%23,%24,%25,%26,%27,%28,%29,%30,%31,%32,%33,%34,%35,%36,%37,%38,%39,%40,%41,%42,%43,%44,%45,%46,%47,%48,%49,%50,%51,%52,%53,%54,%55,%56,%57,%58,%59,%60,%61,%62,%63,%64,%65,%66,%67,%68,%69,%70,%71,%72,%73,%74,%75,%76,%77,%78,%79,%80,%81,%82,%83,%84,%85,%86,%87,%88,%89,%90,%91}, %92, %93, p, 1, 1, 0, 1;}\n"
    : "+f"(d[0]),"+f"(d[1]),"+f"(d[2]),"+f"(d[3]),"+f"(d[4]),"+f"(d[5]),"+f"(d[6]),"+f"(d[7]),"+f"(d[8]),"+f"(d[9]),"+f"(d[10]),"+f"(d[11]),"+f"(d[12]),"+f"(d[13]),"+f"(d[14]),"+f"(d[15]),"+f"(d[16]),"+f"(d[17]),"+f"(d[18]),"+f"(d[19]),"+f"(d[20]),"+f"(d[21]),"+f"(d[22]),"+f"(d[23]),"+f"(d[24]),"+f"(d[25]),"+f"(d[26]),"+f"(d[27]),"+f"(d[28]),"+f"(d[29]),"+f"(d[30]),"+f"(d[31]),"+f"(d[32]),"+f"(d[33]),"+f"(d[34]),"+f"(d[35]),"+f"(d[36]),"+f"(d[37]),"+f"(d[38]),"+f"(d[39]),"+f"(d[40]),"+f"(d[41]),"+f"(d[42]),"+f"(d[43]),"+f"(d[44]),"+f"(d[45]),"+f"(d[46]),"+f"(d[47]),"+f"(d[48]),"+f"(d[49]),"+f"(d[50]),"+f"(d[51]),"+f"(d[52]),"+f"(d[53]),"+f"(d[54]),"+f"(d[55]),"+f"(d[56]),"+f"(d[57]),"+f"(d[58]),"+f"(d[59]),"+f"(d[60]),"+f"(d[61]),"+f"(d[62]),"+f"(d[63]),"+f"(d[64]),"+f"(d[65]),"+f"(d[66]),"+f"(d[67]),"+f"(d[68]),"+f"(d[69]),"+f"(d[70]),"+f"(d[71]),"+f"(d[72]),"+f"(d[73]),"+f"(d[74]),"+f"(d[75]),"+f"(d[76]),"+f"(d[77]),"+f"(d[78]),"+f"(d[79]),"+f"(d[80]),"+f"(d[81]),"+f"(d[82]),"+f"(d[83]),"+f"(d[84]),"+f"(d[85]),"+f"(d[86]),"+f"(d[87]),"+f"(d[88]),"+f"(d[89]),"+f"(d[90]),"+f"(d[91])
    : "l"(da), "l"(db), "r"(acc));
}
__device__ __forceinline__ void mma_ss_224(float (&d)[112], uint64_t da, uint64_t db, int acc) {
  asm volatile("{.reg .pred p; setp.ne.b32 p, %114, 0;\n"
    "wgmma.mma_async.sync.aligned.m64n224k16.f32.bf16.bf16 {%0,%1,%2,%3,%4,%5,%6,%7,%8,%9,%10,%11,%12,%13,%14,%15,%16,%17,%18,%19,%20,%21,%22,%23,%24,%25,%26,%27,%28,%29,%30,%31,%32,%33,%34,%35,%36,%37,%38,%39,%40,%41,%42,%43,%44,%45,%46,%47,%48,%49,%50,%51,%52,%53,%54,%55,%56,%57,%58,%59,%60,%61,%62,%63,%64,%65,%66,%67,%68,%69,%70,%71,%72,%73,%74,%75,%76,%77,%78,%79,%80,%81,%82,%83,%84,%85,%86,%87,%88,%89,%90,%91,%92,%93,%94,%95,%96,%97,%98,%99,%100,%101,%102,%103,%104,%105,%106,%107,%108,%109,%110,%111}, %112, %113, p, 1, 1, 0, 1;}\n"
    : "+f"(d[0]),"+f"(d[1]),"+f"(d[2]),"+f"(d[3]),"+f"(d[4]),"+f"(d[5]),"+f"(d[6]),"+f"(d[7]),"+f"(d[8]),"+f"(d[9]),"+f"(d[10]),"+f"(d[11]),"+f"(d[12]),"+f"(d[13]),"+f"(d[14]),"+f"(d[15]),"+f"(d[16]),"+f"(d[17]),"+f"(d[18]),"+f"(d[19]),"+f"(d[20]),"+f"(d[21]),"+f"(d[22]),"+f"(d[23]),"+f"(d[24]),"+f"(d[25]),"+f"(d[26]),"+f"(d[27]),"+f"(d[28]),"+f"(d[29]),"+f"(d[30]),"+f"(d[31]),"+f"(d[32]),"+f"(d[33]),"+f"(d[34]),"+f"(d[35]),"+f"(d[36]),"+f"(d[37]),"+f"(d[38]),"+f"(d[39]),"+f"(d[40]),"+f"(d[41]),"+f"(d[42]),"+f"(d[43]),"+f"(d[44]),"+f"(d[45]),"+f"(d[46]),"+f"(d[47]),"+f"(d[48]),"+f"(d[49]),"+f"(d[50]),"+f"(d[51]),"+f"(d[52]),"+f"(d[53]),"+f"(d[54]),"+f"(d[55]),"+f"(d[56]),"+f"(d[57]),"+f"(d[58]),"+f"(d[59]),"+f"(d[60]),"+f"(d[61]),"+f"(d[62]),"+f"(d[63]),"+f"(d[64]),"+f"(d[65]),"+f"(d[66]),"+f"(d[67]),"+f"(d[68]),"+f"(d[69]),"+f"(d[70]),"+f"(d[71]),"+f"(d[72]),"+f"(d[73]),"+f"(d[74]),"+f"(d[75]),"+f"(d[76]),"+f"(d[77]),"+f"(d[78]),"+f"(d[79]),"+f"(d[80]),"+f"(d[81]),"+f"(d[82]),"+f"(d[83]),"+f"(d[84]),"+f"(d[85]),"+f"(d[86]),"+f"(d[87]),"+f"(d[88]),"+f"(d[89]),"+f"(d[90]),"+f"(d[91]),"+f"(d[92]),"+f"(d[93]),"+f"(d[94]),"+f"(d[95]),"+f"(d[96]),"+f"(d[97]),"+f"(d[98]),"+f"(d[99]),"+f"(d[100]),"+f"(d[101]),"+f"(d[102]),"+f"(d[103]),"+f"(d[104]),"+f"(d[105]),"+f"(d[106]),"+f"(d[107]),"+f"(d[108]),"+f"(d[109]),"+f"(d[110]),"+f"(d[111])
    : "l"(da), "l"(db), "r"(acc));
}
__device__ __forceinline__ void mma_ss_56(float (&d)[28], uint64_t da, uint64_t db, int acc) {
  asm volatile("{.reg .pred p; setp.ne.b32 p, %30, 0;\n"
    "wgmma.mma_async.sync.aligned.m64n56k16.f32.bf16.bf16 {%0,%1,%2,%3,%4,%5,%6,%7,%8,%9,%10,%11,%12,%13,%14,%15,%16,%17,%18,%19,%20,%21,%22,%23,%24,%25,%26,%27}, %28, %29, p, 1, 1, 0, 1;}\n"
    : "+f"(d[0]),"+f"(d[1]),"+f"(d[2]),"+f"(d[3]),"+f"(d[4]),"+f"(d[5]),"+f"(d[6]),"+f"(d[7]),"+f"(d[8]),"+f"(d[9]),"+f"(d[10]),"+f"(d[11]),"+f"(d[12]),"+f"(d[13]),"+f"(d[14]),"+f"(d[15]),"+f"(d[16]),"+f"(d[17]),"+f"(d[18]),"+f"(d[19]),"+f"(d[20]),"+f"(d[21]),"+f"(d[22]),"+f"(d[23]),"+f"(d[24]),"+f"(d[25]),"+f"(d[26]),"+f"(d[27])
    : "l"(da), "l"(db), "r"(acc));
}
__device__ __forceinline__ void mma_rs_56(float (&d)[28], uint32_t a0, uint32_t a1, uint32_t a2, uint32_t a3, uint64_t db, int acc) {
  asm volatile("{.reg .pred p; setp.ne.b32 p, %33, 0;\n"
    "wgmma.mma_async.sync.aligned.m64n56k16.f32.bf16.bf16 {%0,%1,%2,%3,%4,%5,%6,%7,%8,%9,%10,%11,%12,%13,%14,%15,%16,%17,%18,%19,%20,%21,%22,%23,%24,%25,%26,%27}, {%28,%29,%30,%31}, %32, p, 1, 1, 1;}\n"
    : "+f"(d[0]),"+f"(d[1]),"+f"(d[2]),"+f"(d[3]),"+f"(d[4]),"+f"(d[5]),"+f"(d[6]),"+f"(d[7]),"+f"(d[8]),"+f"(d[9]),"+f"(d[10]),"+f"(d[11]),"+f"(d[12]),"+f"(d[13]),"+f"(d[14]),"+f"(d[15]),"+f"(d[16]),"+f"(d[17]),"+f"(d[18]),"+f"(d[19]),"+f"(d[20]),"+f"(d[21]),"+f"(d[22]),"+f"(d[23]),"+f"(d[24]),"+f"(d[25]),"+f"(d[26]),"+f"(d[27])
    : "r"(a0), "r"(a1), "r"(a2), "r"(a3), "l"(db), "r"(acc));
}
__device__ __forceinline__ void mma_ss_64t(float (&d)[32], uint64_t da, uint64_t db, int acc) {
  asm volatile("{.reg .pred p; setp.ne.b32 p, %34, 0;\n"
    "wgmma.mma_async.sync.aligned.m64n64k16.f32.bf16.bf16 {%0,%1,%2,%3,%4,%5,%6,%7,%8,%9,%10,%11,%12,%13,%14,%15,%16,%17,%18,%19,%20,%21,%22,%23,%24,%25,%26,%27,%28,%29,%30,%31}, %32, %33, p, 1, 1, 1, 1;}\n"
    : "+f"(d[0]),"+f"(d[1]),"+f"(d[2]),"+f"(d[3]),"+f"(d[4]),"+f"(d[5]),"+f"(d[6]),"+f"(d[7]),"+f"(d[8]),"+f"(d[9]),"+f"(d[10]),"+f"(d[11]),"+f"(d[12]),"+f"(d[13]),"+f"(d[14]),"+f"(d[15]),"+f"(d[16]),"+f"(d[17]),"+f"(d[18]),"+f"(d[19]),"+f"(d[20]),"+f"(d[21]),"+f"(d[22]),"+f"(d[23]),"+f"(d[24]),"+f"(d[25]),"+f"(d[26]),"+f"(d[27]),"+f"(d[28]),"+f"(d[29]),"+f"(d[30]),"+f"(d[31])
    : "l"(da), "l"(db), "r"(acc));
}
__device__ __forceinline__ void mma_rs_64(float (&d)[32], uint32_t a0, uint32_t a1, uint32_t a2, uint32_t a3, uint64_t db, int acc) {
  asm volatile("{.reg .pred p; setp.ne.b32 p, %37, 0;\n"
    "wgmma.mma_async.sync.aligned.m64n64k16.f32.bf16.bf16 {%0,%1,%2,%3,%4,%5,%6,%7,%8,%9,%10,%11,%12,%13,%14,%15,%16,%17,%18,%19,%20,%21,%22,%23,%24,%25,%26,%27,%28,%29,%30,%31}, {%32,%33,%34,%35}, %36, p, 1, 1, 1;}\n"
    : "+f"(d[0]),"+f"(d[1]),"+f"(d[2]),"+f"(d[3]),"+f"(d[4]),"+f"(d[5]),"+f"(d[6]),"+f"(d[7]),"+f"(d[8]),"+f"(d[9]),"+f"(d[10]),"+f"(d[11]),"+f"(d[12]),"+f"(d[13]),"+f"(d[14]),"+f"(d[15]),"+f"(d[16]),"+f"(d[17]),"+f"(d[18]),"+f"(d[19]),"+f"(d[20]),"+f"(d[21]),"+f"(d[22]),"+f"(d[23]),"+f"(d[24]),"+f"(d[25]),"+f"(d[26]),"+f"(d[27]),"+f"(d[28]),"+f"(d[29]),"+f"(d[30]),"+f"(d[31])
    : "r"(a0), "r"(a1), "r"(a2), "r"(a3), "l"(db), "r"(acc));
}

__device__ __forceinline__ void dual_softmax(const float (&p)[28], uint32_t (&phi)[4][7]) {
  constexpr float L2E = 1.4426950408889634f;
#pragma unroll
  for (int i = 0; i < 4; i++) {
    float mx = p[i], mn = p[i];
#pragma unroll
    for (int j = 1; j < 7; j++) { mx = fmaxf(mx, p[4 * j + i]); mn = fminf(mn, p[4 * j + i]); }
    mx = fmaxf(mx, __shfl_xor_sync(~0u, mx, 1)); mn = fminf(mn, __shfl_xor_sync(~0u, mn, 1));
    mx = fmaxf(mx, __shfl_xor_sync(~0u, mx, 2)); mn = fminf(mn, __shfl_xor_sync(~0u, mn, 2));
    float a[7], b[7], sa = 0.f, sb = 0.f;
    const float mxl = mx * L2E, mnl = mn * L2E;
#pragma unroll
    for (int j = 0; j < 7; j++) {
      a[j] = ex2(fmaf(p[4 * j + i], L2E, -mxl)); b[j] = ex2(fmaf(p[4 * j + i], -L2E, mnl));
      sa += a[j]; sb += b[j];
    }
    sa += __shfl_xor_sync(~0u, sa, 1); sb += __shfl_xor_sync(~0u, sb, 1);
    sa += __shfl_xor_sync(~0u, sa, 2); sb += __shfl_xor_sync(~0u, sb, 2);
    const float ra = __fdividef(1.f, sa), rb = __fdividef(1.f, sb);
#pragma unroll
    for (int j = 0; j < 7; j++) phi[i][j] = pack(a[j] * ra, b[j] * rb);
  }
}

struct Ring {
  uint32_t full, empty, base; int slot, par;
  __device__ __forceinline__ uint32_t acquire() { mbar_wait(full + slot * 8, par); return base + slot * SLOT; }
  __device__ __forceinline__ int advance() { int s = slot; if (++slot == NSLOT) { slot = 0; par ^= 1; } return s; }
  __device__ __forceinline__ void release(int s, bool elect) { if (elect) mbar_arrive(empty + s * 8); }
};
constexpr int FL_KV = 448, FL_ZERO = FL_KV + 16, FL_CS = FL_KV + 24, FL_DONE = FL_KV + 32;

__global__ void __launch_bounds__(384, 1)
fused_kernel(const __grid_constant__ CUtensorMap mQKV, const __grid_constant__ CUtensorMap mWO,
             const __grid_constant__ CUtensorMap mW1, const __grid_constant__ CUtensorMap mW2,
             const __grid_constant__ CUtensorMap mX,
             const __nv_bfloat16* __restrict__ x, const __nv_bfloat16* __restrict__ wphi,
             const __nv_bfloat16* __restrict__ b1, const __nv_bfloat16* __restrict__ b2,
             const __nv_bfloat16* __restrict__ wqkv, const __nv_bfloat16* __restrict__ wo, const __nv_bfloat16* __restrict__ w1,
             const __nv_bfloat16* __restrict__ w2, __nv_bfloat16* __restrict__ out) {
  extern __shared__ unsigned char smem_raw[];
  const uint32_t sb = (smem_u32(smem_raw) + 1023) & ~1023u;
  unsigned char* sg = smem_raw + (sb - smem_u32(smem_raw));
  const int tid = threadIdx.x, lane = tid & 31;
  const int G = blockIdx.x >> 3, r = blockIdx.x & 7;
  const uint32_t barFull = sb + OFF_BAR, barEmpty = barFull + 56, barA = barEmpty + 56, barCS = barA + 112;
  uint32_t wv[7]; uint4 cu[7]; float bv = 0.f;
  const int cch = min(tid >> 2, 48), cp = cch / 7;
  if (tid < 256) {
    const int k0 = G * 28 + (tid & 3) * 7;
    const uint4* src = cch < 21 ? reinterpret_cast<const uint4*>(wqkv + (size_t)k0 * 1344 + cp * 448 + 56 * r) + (cch - 7 * cp)
                                : reinterpret_cast<const uint4*>(w1 + (size_t)k0 * 1792 + 224 * r) + (cch - 21);
#pragma unroll
    for (int i = 0; i < 7; i++) cu[i] = __ldg(src + i * (cch < 21 ? 168 : 224));
#pragma unroll
    for (int i = 0; i < 7; i++)
      wv[i] = __ldg(reinterpret_cast<const unsigned short*>(wphi) + (56 * r + i * 8 + (tid >> 5)) * 28 + min(lane, 27));
    bv = __bfloat162float(b1[224 * r + min(tid, 223)]);
  } else if (tid >= 352) {
    if (lane < 29) mbar_init(barFull + lane * 8, lane == 28 ? 64 : (lane >= 7 && lane < 14 ? 2 : 1));
    asm volatile("fence.mbarrier_init.release.cluster;" ::: "memory");
    fence_async_smem();
    __syncwarp();
    if (lane < 14) {
      const int k = lane >> 1, cc = lane & 1;
      mbar_expect(barA + (cc * 7 + k) * 8, 8192);
      tma2(sb + (cc * 7 + k) * 8192, &mX, 64 * k, G * 128 + 64 * cc, barA + (cc * 7 + k) * 8);
    } else if (lane < 21) {
      const int i = lane - 14;
      mbar_expect(barFull + i * 8, 12288);
      tma3(sb + OFF_RING + i * SLOT, &mQKV, 56 * r, 32 * i, 0, barFull + i * 8);
    } else if (lane < 23) {
      const char* src = lane == 21 ? (const char*)wo + blockIdx.x * 3136 : (const char*)w2 + blockIdx.x * 12544;
      asm volatile("cp.async.bulk.prefetch.L2.global [%0], %1;" ::"l"(src), "r"(lane == 21 ? 3136 : 12544) : "memory");
    }
  }
  __syncthreads();
  const int wgid = __shfl_sync(~0u, tid >> 7, 0);
  if (wgid == 2) {
    asm volatile("setmaxnreg.dec.sync.aligned.u32 40;");
    if (tid == 256) {
      int slot = 0, par = 0;
      for (int it = NSLOT; it < 2 * TILES_PER_LAYER; it++) {
        const int i = it >= TILES_PER_LAYER ? it - TILES_PER_LAYER : it;
        mbar_wait(barEmpty + slot * 8, par);
        const uint32_t dst = sb + OFF_RING + slot * SLOT, fb = barFull + slot * 8;
        mbar_expect(fb, i < 14 ? 12288 : SLOT);
        if (i < 14) tma3(dst, &mQKV, 56 * r, 32 * i, 0, fb);
        else if (i < 18) tma2(dst, &mWO, 56 * r, 112 * (i - 14), fb);
        else if (i < 32) tma3(dst, &mW1, 0, 32 * (i - 18), 7 * r, fb);
        else tma2(dst, &mW2, 64 * ((i - 32) >> 1), 224 * r + 112 * (i & 1), fb);
        if (++slot == NSLOT) { slot = 0; par ^= 1; }
      }
    } else if (tid >= 288 && tid < 352) {
      unsigned ep;
      asm volatile("ld.relaxed.gpu.global.u32 %0, [%1];" : "=r"(ep) : "l"(gFlag + FL_DONE * 32) : "memory");
      const int idx = tid - 288;
      bar_sync<4, 320>();
      if (lane == 0) { flag_arrive(gFlag + (FL_CS + r) * 32); flag_wait(gFlag + (FL_CS + r) * 32, (ep / NCTA + 1) * 32); }
      __syncwarp();
      if (idx < 52) {
#pragma unroll 1
        for (int hh = 0; hh < 2; hh++) {
          float4 a = make_float4(0.f, 0.f, 0.f, 0.f);
#pragma unroll 4
          for (int i = 0; i < 16; i++) { const float4 v = __ldcg(gCS + (r * 16 + i) * 104 + hh * 52 + idx); a.x += v.x; a.y += v.y; a.z += v.z; a.w += v.w; }
          reinterpret_cast<float4*>(sg + OFF_CS)[hh * 52 + idx] = a;
        }
      }
      mbar_arrive(barCS);
    }
  } else {
  asm volatile("setmaxnreg.inc.sync.aligned.u32 232;");
  const int c = wgid, w = (tid >> 5) & 3, g = lane >> 2, t = lane & 3;
  const bool elect = (tid & 127) == 0;
  const uint32_t abuf = sb + c * ABYTES, barAc = barA + c * 56;
  const int row0 = G * 128 + c * 64;
  unsigned epoch;
  asm volatile("ld.relaxed.gpu.global.u32 %0, [%1];" : "=r"(epoch) : "l"(gFlag + FL_DONE * 32) : "memory");
  STAMP(24);
  float mean[2], rstd[2];
  {
    {
      float s[8] = {};
#pragma unroll
      for (int i = 0; i < 7; i++) { s[0] += lo(cu[i].x); s[1] += hi(cu[i].x); s[2] += lo(cu[i].y); s[3] += hi(cu[i].y); s[4] += lo(cu[i].z); s[5] += hi(cu[i].z); s[6] += lo(cu[i].w); s[7] += hi(cu[i].w); }
#pragma unroll
      for (int i = 0; i < 8; i++) { s[i] += __shfl_xor_sync(~0u, s[i], 1); s[i] += __shfl_xor_sync(~0u, s[i], 2); }
      if (t < 2 && tid < 196) gCS[(r * 16 + G) * 104 + (cch < 21 ? cch + cp : cch + 3) * 2 + t] = t ? make_float4(s[4], s[5], s[6], s[7]) : make_float4(s[0], s[1], s[2], s[3]);
      asm volatile("bar.arrive 4, 320;" ::: "memory");
    }
    if (G == 0) {
#pragma unroll 1
      for (int i = tid; i < 2 * 1280; i += 256) gKV[((i >= 1280) * 7 + r) * 1280 + i] = make_float4(0.f, 0.f, 0.f, 0.f);
    }
#pragma unroll
    for (int i = 0; i < 8; i++) {
      const int k = i * 8 + (tid >> 5);
      *reinterpret_cast<uint32_t*>(sg + OFF_WPHI + k * 128 + ((g ^ (k & 7)) << 4) + t * 4) = (i < 7 && lane < 28) ? wv[i % 7] << (k >= 28 ? 16 : 0) : 0u;
    }
    if (tid < 224) reinterpret_cast<float*>(sg + OFF_B1)[tid] = bv;
    fence_async_smem();
    bar_sync<3, 256>();
    epoch = epoch / NCTA + 1;
    if (G == 0 && tid == 0) flag_arrive(gFlag + (FL_ZERO + r) * 32);
  }
  STAMP(0);
  Ring ring{barFull, barEmpty, sb + OFF_RING, 0, 0};
  int apar = 0;
  const uint32_t stsm_off = (w * 16 + ((lane >> 3) & 1) * 8 + (lane & 7)) * 128;
  const uint32_t stsm_hi = lane >> 4;
  const uint64_t dA = mkdesc(abuf, 1024, 128, 0);

  auto gather = [&](unsigned* fl, const unsigned char* img) {
    __syncwarp();
    if (lane == 0) flag_arrive(fl);
    if (w == 0) {
      STAMP(27);
      if (lane == 0) flag_wait(fl, epoch * 32);
      __syncwarp();
      STAMP(28);
      if (lane < 7) { fence_async(); mbar_expect(barAc + lane * 8, 8192); bulk_ld(abuf + lane * 8192, img + lane * 8192, 8192, barAc + lane * 8); }
    }
    __syncwarp();
    apar ^= 1;
  };
  auto slice_off = [&](int j, int hh) -> uint32_t {
    return (7 * r + j) * 1024 + (w * 2 + hh) * 128 + lane * 4;
  };
  uint4 su[2];
  auto load_stats = [&](const float2* st) {
    mbar_wait(barAc, apar);
#pragma unroll
    for (int hh = 0; hh < 2; hh++) su[hh] = ldcg4(st + (size_t)(row0 + w * 16 + hh * 8 + g) * 8 + 2 * t);
  };
  auto finish_stats = [&]() {
#pragma unroll
    for (int hh = 0; hh < 2; hh++) {
      const float m0 = __uint_as_float(su[hh].x), m1 = __uint_as_float(su[hh].z);
      float m = m0 + m1;
      m += __shfl_xor_sync(~0u, m, 1); m += __shfl_xor_sync(~0u, m, 2);
      m *= 0.125f;
      float q = __uint_as_float(su[hh].y) + __uint_as_float(su[hh].w) + 56.f * ((m0 - m) * (m0 - m) + (m1 - m) * (m1 - m));
      q += __shfl_xor_sync(~0u, q, 1); q += __shfl_xor_sync(~0u, q, 2);
      mean[hh] = m; rstd[hh] = rsqrtf(q * (1.f / DM) + 1e-5f);
    }
  };

#pragma unroll 1
  for (int layer = 0; layer < 2; layer++) {
    unsigned* const fl = gFlag + (layer * 32 + G * 2 + c) * 7 * 32;
    uint32_t phiq[4][7], xs[7][2];
    {
      float acc[92]; reg_def(acc);
      const uint64_t dQ = layer ? dA : mkdesc(abuf, 16, 1024, 1);
      const int kstep = layer ? 128 : 2;
      int prev = 0;
      float sh[2] = {0.f, 0.f}, s1[2] = {0.f, 0.f}, s2[2] = {0.f, 0.f};
      if (layer) load_stats(gStat + 2048 * 8);
#pragma unroll 1
      for (int st = 0; st < 14; st++) {
        if (!(st & 1)) mbar_wait(barAc + (st >> 1) * 8, apar);
        const uint64_t da = dQ + (st >> 1) * 512 + (st & 1) * 2 * kstep, db = mkdesc(ring.acquire(), 4096, 1024, 1);
        wg_fence();
        mma_ss_184(acc, da, db, st);
        mma_ss_184(acc, da + kstep, db + 128, 1);
        wg_commit();
        if (layer == 0) {
#pragma unroll
          for (int hh = 0; hh < 2; hh++) {
            const uint4 u = *reinterpret_cast<const uint4*>(sg + c * ABYTES + (st >> 1) * 8192 + (w * 16 + hh * 8 + g) * 128 + ((((st ^ g) & 1) * 4 + t) << 4));
            if (st == 0) sh[hh] = lo(u.x);
            const uint32_t e[4] = {u.x, u.y, u.z, u.w};
#pragma unroll
            for (int z = 0; z < 4; z++) { const float a = lo(e[z]) - sh[hh], b = hi(e[z]) - sh[hh]; s1[hh] += a + b; s2[hh] = fmaf(a, a, fmaf(b, b, s2[hh])); }
          }
        }
        if (st > 0) { wg_wait<1>(); ring.release(prev, elect); }
        prev = ring.advance();
      }
      if (layer == 0) {
#pragma unroll
        for (int hh = 0; hh < 2; hh++) {
          const float d = s1[hh] * (1.f / 112.f), m = sh[hh] + d, q = 0.5f * fmaxf(s2[hh] - d * s1[hh], 0.f);
          su[hh] = make_uint4(__float_as_uint(m), __float_as_uint(q), __float_as_uint(m), __float_as_uint(q));
        }
        mbar_wait(barCS, 0);
      }
      finish_stats();
#pragma unroll
      for (int j = 0; j < 7; j++) {
        const int ci = 7 * r + j;
        const uint32_t a = abuf + (layer ? slice_off(j, 0) : (ci >> 3) * 8192 + (w * 16 + g) * 128 + (((ci & 7) ^ g) << 4) + t * 4);
        xs[j][0] = lds32(a); xs[j][1] = lds32(a + (layer ? 128 : 1024));
      }
      wg_wait<0>(); reg_fence(acc);
      ring.release(prev, elect);
      STAMP(1 + layer * 12);
      uint32_t f[3][14];
      {
        const float2* cs = reinterpret_cast<const float2*>(sg + OFF_CS) + t;
        const float mr0 = -mean[0] * rstd[0], mr1 = -mean[1] * rstd[1];
#pragma unroll
        for (int p = 0; p < 3; p++)
#pragma unroll
          for (int j = 0; j < 7; j++) {
            const float2 s = cs[p * 32 + j * 4];
            const int b = p * 32 + j * 4;
            f[p][2 * j] = pack(fmaf(acc[b], rstd[0], s.x * mr0), fmaf(acc[b + 1], rstd[0], s.y * mr0));
            f[p][2 * j + 1] = pack(fmaf(acc[b + 2], rstd[1], s.x * mr1), fmaf(acc[b + 3], rstd[1], s.y * mr1));
          }
      }
      float pk[28], pq[28]; reg_def(pk); reg_def(pq);
      const uint64_t dW = mkdesc(sb + OFF_WPHI, 4096, 1024, 1);
      wg_fence();
#pragma unroll
      for (int s = 0; s < 4; s++)
        mma_rs_56(pk, f[1][4 * s], f[1][4 * s + 1], s < 3 ? f[1][(4 * s + 2) % 14] : 0u, s < 3 ? f[1][(4 * s + 3) % 14] : 0u, dW + s * 128, s);
      wg_commit();
#pragma unroll
      for (int s = 0; s < 4; s++)
        mma_rs_56(pq, f[0][4 * s], f[0][4 * s + 1], s < 3 ? f[0][(4 * s + 2) % 14] : 0u, s < 3 ? f[0][(4 * s + 3) % 14] : 0u, dW + s * 128, s);
      wg_commit();
      bar_wg(c);
      const uint32_t srow = abuf + stsm_off, ones = t == 0 ? 0x3F803F80u : 0u;
#pragma unroll
      for (int jp = 0; jp < 4; jp++)
        stsm4(srow + 16384 + (((2 * jp + stsm_hi) ^ (lane & 7)) << 4), f[2][4 * jp], f[2][4 * jp + 1],
              jp < 3 ? f[2][(4 * jp + 2) % 14] : ones, jp < 3 ? f[2][(4 * jp + 3) % 14] : ones);
      wg_wait<0>(); reg_fence(pk); reg_fence(pq);
#pragma unroll 1
      for (int pass = 0; pass < 2; pass++) {
        dual_softmax(pk, phiq);
        if (pass) break;
#pragma unroll
        for (int e = 0; e < 2; e++)
#pragma unroll
          for (int jp = 0; jp < 4; jp++)
            stsm4(srow + e * 8192 + (((2 * jp + stsm_hi) ^ (lane & 7)) << 4), phiq[e][2 * jp], phiq[2 + e][2 * jp],
                  jp < 3 ? phiq[e][(2 * jp + 1) % 7] : 0u, jp < 3 ? phiq[2 + e][(2 * jp + 1) % 7] : 0u);
        fence_async_smem();
        bar_sync<3, 256>();
        float kv[32]; reg_def(kv);
        const uint64_t dP = mkdesc(sb + c * 8192, 4096, 1024, 1), dV = mkdesc(sb + 16384, 4096, 1024, 1);
        wg_fence();
#pragma unroll
        for (int s = 0; s < 8; s++) mma_ss_64t(kv, dP + (s >> 2) * (ABYTES / 16) + (s & 3) * 128, dV + (s >> 2) * (ABYTES / 16) + (s & 3) * 128, s);
        wg_commit();
        if (layer == 0 && lane == 0) flag_wait(gFlag + (FL_ZERO + r) * 32, epoch);
        __syncwarp();
        wg_wait<0>(); reg_fence(kv);
        float4* kvg = gKV + ((layer * 8 + r) * 2 + c) * 640 + (tid & 127);
#pragma unroll
        for (int i = 0; i < 5; i++) {
          float v0, v1, v2, v3;
          if (i == 4) { v0 = kv[28]; v1 = kv[29]; v2 = kv[30]; v3 = kv[31]; }
          else { v0 = c ? kv[12 + 4 * i] : kv[4 * i]; v1 = c ? kv[13 + 4 * i] : kv[1 + 4 * i]; v2 = c ? kv[14 + 4 * i] : kv[2 + 4 * i]; v3 = c ? kv[15 + 4 * i] : kv[3 + 4 * i]; }
          const bool use = i == 4 ? t == 0 : (i == 0 ? (c == 0 || t >= 2) : (i == 3 ? (c == 1 || t < 2) : true));
          if (use) asm volatile("red.relaxed.gpu.global.add.v4.f32 [%0], {%1,%2,%3,%4};" ::"l"(kvg + i * 128), "f"(v0), "f"(v1), "f"(v2), "f"(v3) : "memory");
        }
        __syncwarp();
        if (lane == 0) flag_arrive(gFlag + (FL_KV + layer * 8 + r) * 32);
        __syncwarp();
        STAMP(2 + layer * 12);
#pragma unroll
        for (int i = 0; i < 28; i++) pk[i] = pq[i];
      }
    }
    {
      if (elect) flag_wait(gFlag + (FL_KV + layer * 8 + r) * 32, epoch * 128);
      bar_wg(c);
      STAMP(3 + layer * 12);
      const float4* kvg = gKV + (layer * 8 + r) * 1280 + (tid & 127);
      uint4 kk[2][5];
#pragma unroll
      for (int e = 0; e < 2; e++)
#pragma unroll
        for (int i = 0; i < 5; i++) kk[e][i] = ldcg4(kvg + e * 640 + i * 128);
      const uint32_t srow = abuf + 24576 + stsm_off;
#pragma unroll
      for (int e = 0; e < 2; e++) {
        uint32_t f[8][2];
#pragma unroll
        for (int j = 0; j < 8; j++) { f[j][0] = 0u; f[j][1] = 0u; }
#pragma unroll
        for (int i = 0; i < 4; i++) {
          f[i + 3 * e][0] = pack(__uint_as_float(kk[e][i].x), __uint_as_float(kk[e][i].y));
          f[i + 3 * e][1] = pack(__uint_as_float(kk[e][i].z), __uint_as_float(kk[e][i].w));
        }
        f[7][0] = e ? pack(0.f, __uint_as_float(kk[e][4].y)) : pack(__uint_as_float(kk[e][4].x), 0.f);
        f[7][1] = e ? pack(0.f, __uint_as_float(kk[e][4].w)) : pack(__uint_as_float(kk[e][4].z), 0.f);
#pragma unroll
        for (int jp = 0; jp < 4; jp++)
          stsm4(srow + e * 8192 + (((2 * jp + stsm_hi) ^ (lane & 7)) << 4), f[2 * jp][0], f[2 * jp][1], f[2 * jp + 1][0], f[2 * jp + 1][1]);
      }
      fence_async_smem();
      bar_wg(c);
      float num[32]; reg_def(num);
      const uint64_t dK = mkdesc(abuf + 24576, 4096, 1024, 1);
      wg_fence();
#pragma unroll
      for (int e = 0; e < 2; e++)
#pragma unroll
        for (int s = 0; s < 4; s++)
          mma_rs_64(num, phiq[e][2 * s], phiq[2 + e][2 * s], s < 3 ? phiq[e][(2 * s + 1) % 7] : 0u, s < 3 ? phiq[2 + e][(2 * s + 1) % 7] : 0u,
                    dK + e * 512 + s * 128, e + s);
      wg_commit();
      wg_wait<0>(); reg_fence(num);
      float rd[4];
#pragma unroll
      for (int i = 0; i < 4; i++) rd[i] = __fdividef(1.f, __shfl_sync(~0u, num[28 + i], lane & ~3) + 1e-6f);
      unsigned char* img = gImg + (size_t)(G * 2 + c) * ABYTES;
#pragma unroll
      for (int j = 0; j < 7; j++) {
        const bool hb = j > 3 || (j == 3 && t >= 2);
        const float r0 = hb ? rd[1] : rd[0], r1 = hb ? rd[3] : rd[2];
        *reinterpret_cast<uint32_t*>(img + slice_off(j, 0)) = pack(num[4 * j] * r0, num[4 * j + 1] * r0);
        *reinterpret_cast<uint32_t*>(img + slice_off(j, 1)) = pack(num[4 * j + 2] * r1, num[4 * j + 3] * r1);
      }
      STAMP(4 + layer * 12);
      gather(fl, img);
      STAMP(5 + layer * 12);
    }
    {
      float acc[28]; reg_def(acc);
      int prev = 0;
#pragma unroll 1
      for (int st = 0; st < 4; st++) {
        mbar_wait(barAc + (st * 7 + 3) / 4 * 8, apar);
        mbar_wait(barAc + (st * 7 + 6) / 4 * 8, apar);
        const uint64_t db = mkdesc(ring.acquire(), 4096, 1024, 1);
        wg_fence();
#pragma unroll
        for (int s = 0; s < 7; s++) { const int ks = st * 7 + s; mma_ss_56(acc, dA + ks * 128, db + s * 128, ks); }
        wg_commit();
        if (st > 0) { wg_wait<1>(); ring.release(prev, elect); }
        prev = ring.advance();
      }
      wg_wait<0>(); reg_fence(acc);
      ring.release(prev, elect);
      unsigned char* img = gImg + (size_t)(32 + G * 2 + c) * ABYTES;
#pragma unroll
      for (int hh = 0; hh < 2; hh++) {
        float s = 0.f, q = 0.f;
#pragma unroll
        for (int j = 0; j < 7; j++) {
          xs[j][hh] = pack(lo(xs[j][hh]) + acc[4 * j + 2 * hh], hi(xs[j][hh]) + acc[4 * j + 2 * hh + 1]);
          *reinterpret_cast<uint32_t*>(img + slice_off(j, hh)) = xs[j][hh];
          s += lo(xs[j][hh]) + hi(xs[j][hh]);
        }
        s += __shfl_xor_sync(~0u, s, 1); s += __shfl_xor_sync(~0u, s, 2);
        s *= 1.f / 56.f;
#pragma unroll
        for (int j = 0; j < 7; j++) { const float a = lo(xs[j][hh]) - s, b = hi(xs[j][hh]) - s; q = fmaf(a, a, q); q = fmaf(b, b, q); }
        q += __shfl_xor_sync(~0u, q, 1); q += __shfl_xor_sync(~0u, q, 2);
        if (t == 0) gStat[(size_t)(row0 + w * 16 + hh * 8 + g) * 8 + r] = make_float2(s, q);
      }
      STAMP(6 + layer * 12);
      gather(fl + 32, img);
      STAMP(7 + layer * 12);
    }
    {
      uint32_t hf[28][2];
      {
        float acc[112]; reg_def(acc);
        int prev = 0;
        load_stats(gStat);
#pragma unroll 1
        for (int st = 0; st < 14; st++) {
          if (!(st & 1)) mbar_wait(barAc + (st >> 1) * 8, apar);
          const uint64_t da = dA + st * 256, db = mkdesc(ring.acquire(), 2048, 512, 2);
          wg_fence();
          mma_ss_224(acc, da, db, st);
          mma_ss_224(acc, da + 128, db + 64, 1);
          wg_commit();
          if (st > 0) { wg_wait<1>(); ring.release(prev, elect); }
          prev = ring.advance();
        }
        finish_stats();
        wg_wait<0>(); reg_fence(acc);
        ring.release(prev, elect);
        STAMP(8 + layer * 12);
        const float2* bs = reinterpret_cast<const float2*>(sg + OFF_B1) + t;
        const float2* cs = reinterpret_cast<const float2*>(sg + OFF_CS + 768) + t;
        const float mr0 = -mean[0] * rstd[0], mr1 = -mean[1] * rstd[1];
#pragma unroll
        for (int j = 0; j < 28; j++) {
          const float2 b = bs[4 * j], s = cs[4 * j];
          const float h0 = fmaxf(fmaf(acc[4 * j], rstd[0], fmaf(s.x, mr0, b.x)), 0.f), h1 = fmaxf(fmaf(acc[4 * j + 1], rstd[0], fmaf(s.y, mr0, b.y)), 0.f);
          const float h2 = fmaxf(fmaf(acc[4 * j + 2], rstd[1], fmaf(s.x, mr1, b.x)), 0.f), h3 = fmaxf(fmaf(acc[4 * j + 3], rstd[1], fmaf(s.y, mr1, b.y)), 0.f);
          hf[j][0] = pack(h0 * h0, h1 * h1); hf[j][1] = pack(h2 * h2, h3 * h3);
        }
      }
      unsigned char* pdst = gP + (size_t)(((G * 2 + c) * 8 + 2 * w) * 8 + r) * 7168 + lane * 8;
      uint2 pk[8] = {};
#pragma unroll 1
      for (int ch = 0; ch < 7; ch++) {
        float acc[32]; reg_def(acc);
        int sl0 = 0, sl1 = 0;
#pragma unroll
        for (int hk = 0; hk < 2; hk++) {
          const uint64_t db = mkdesc(ring.acquire(), 4096, 1024, 1);
          wg_fence();
#pragma unroll
          for (int s = 0; s < 7; s++) { const int ks = hk * 7 + s; mma_rs_64(acc, hf[2 * ks][0], hf[2 * ks][1], hf[2 * ks + 1][0], hf[2 * ks + 1][1], db + s * 128, ks); }
          wg_commit();
          if (hk) sl1 = ring.advance(); else sl0 = ring.advance();
        }
        if (ch > 0) {
#pragma unroll
          for (int i = 0; i < 8; i++) *reinterpret_cast<uint2*>(pdst + (i & 1) * (8 * 7168) + (i >> 1) * 256) = pk[i];
          pdst += 1024;
        }
        wg_wait<1>(); ring.release(sl0, elect);
        wg_wait<0>(); reg_fence(acc); ring.release(sl1, elect);
#pragma unroll
        for (int i = 0; i < 8; i++) {
          const int b = (i >> 1) * 8 + (i & 1) * 2;
          pk[i] = make_uint2(pack(acc[b], acc[b + 1]), pack(acc[b + 4], acc[b + 5]));
        }
      }
#pragma unroll
      for (int i = 0; i < 8; i++) *reinterpret_cast<uint2*>(pdst + (i & 1) * (8 * 7168) + (i >> 1) * 256) = pk[i];
      STAMP(9 + layer * 12);
    }
    {
      uint32_t bx[14];
#pragma unroll
      for (int j = 0; j < 14; j++) bx[j] = __ldg(reinterpret_cast<const uint32_t*>(b2 + w * 112 + j * 8 + 2 * t));
      __syncwarp();
      if (lane == 0) { flag_arrive(fl + (3 + w) * 32); flag_wait(fl + (3 + (r >> 1)) * 32, epoch * 8); }
      __syncwarp();
      STAMP(10 + layer * 12);
      const unsigned char* psrc = gP + (size_t)(((G * 2 + c) * 8 + r) * 8) * 7168 + w * 1792 + lane * 8;
      unsigned char* img = gImg + (size_t)(64 + G * 2 + c) * ABYTES;
      uint2 pv[8][7];
#pragma unroll
      for (int s = 0; s < 8; s++)
#pragma unroll
        for (int i = 0; i < 7; i++) pv[s][i] = ldcg2(psrc + s * 7168 + i * 256);
      const uint32_t off = w * 14336 + r * 128 + lane * 4;
      unsigned char* dst = layer ? reinterpret_cast<unsigned char*>(out + (size_t)(row0 + r * 8 + g) * DM + w * 112 + 2 * t) : img + off;
      float sm = 0.f, q = 0.f;
#pragma unroll
      for (int j = 0; j < 14; j++) {
        float y0 = lo(bx[j]), y1 = hi(bx[j]);
        const uint32_t xo = lds32(abuf + off + j * 1024);
        y0 += lo(xo); y1 += hi(xo);
#pragma unroll
        for (int s = 0; s < 8; s++) { const uint32_t u = (j & 1) ? pv[s][j >> 1].y : pv[s][j >> 1].x; y0 += lo(u); y1 += hi(u); }
        bx[j] = pack(y0, y1);
        *reinterpret_cast<uint32_t*>(dst + j * (layer ? 16 : 1024)) = bx[j];
        sm += lo(bx[j]) + hi(bx[j]);
      }
      if (layer) break;
      sm += __shfl_xor_sync(~0u, sm, 1); sm += __shfl_xor_sync(~0u, sm, 2);
      sm *= 1.f / 112.f;
#pragma unroll
      for (int j = 0; j < 14; j++) { const float a = lo(bx[j]) - sm, b = hi(bx[j]) - sm; q = fmaf(a, a, q); q = fmaf(b, b, q); }
      q += __shfl_xor_sync(~0u, q, 1); q += __shfl_xor_sync(~0u, q, 2);
      if (t < 2) gStat[(size_t)(2048 + row0 + r * 8 + g) * 8 + 2 * w + t] = make_float2(sm, q * 0.5f);
      STAMP(11);
      gather(fl + 64, img);
      STAMP(12);
    }
  }
  STAMP(30);
  if (tid == 0) asm volatile("red.relaxed.gpu.global.add.u32 [%0], 1;" ::"l"(gFlag + FL_DONE * 32) : "memory");
  }
}

typedef CUresult (*EncFn)(CUtensorMap*, CUtensorMapDataType, cuuint32_t, void*, const cuuint64_t*, const cuuint64_t*,
                          const cuuint32_t*, const cuuint32_t*, CUtensorMapInterleave, CUtensorMapSwizzle,
                          CUtensorMapL2promotion, CUtensorMapFloatOOBfill);

void make_map(EncFn enc, CUtensorMap* m, void* p, int rank, uint64_t d0, uint64_t d1, uint64_t d2, uint64_t s1, uint64_t s2,
              uint32_t b0, uint32_t b1, uint32_t b2, CUtensorMapSwizzle sw) {
  cuuint64_t dims[3] = {d0, d1, d2}, strides[2] = {s1, s2};
  cuuint32_t box[3] = {b0, b1, b2}, es[3] = {1, 1, 1};
  enc(m, CU_TENSOR_MAP_DATA_TYPE_BFLOAT16, rank, p, dims, strides, box, es, CU_TENSOR_MAP_INTERLEAVE_NONE, sw,
      CU_TENSOR_MAP_L2_PROMOTION_L2_128B, CU_TENSOR_MAP_FLOAT_OOB_FILL_NONE);
}

}

extern "C" void kernel_launch(void* const* d_in, const int* in_sizes, int n_in, void* d_out, int out_size) {
  static EncFn enc = nullptr;
  if (!enc) {
    cudaDriverEntryPointQueryResult st;
    void* fn = nullptr;
    cudaGetDriverEntryPoint("cuTensorMapEncodeTiled", &fn, cudaEnableDefault, &st);
    enc = (EncFn)fn;
    cudaFuncSetAttribute(fused_kernel, cudaFuncAttributeMaxDynamicSharedMemorySize, SMEM_BYTES);
  }
  CUtensorMap mQKV, mWO, mW1, mW2, mX;
  make_map(enc, &mQKV, d_in[1], 3, 448, 448, 3, 2688, 896, 64, 32, 3, CU_TENSOR_MAP_SWIZZLE_128B);
  make_map(enc, &mWO, d_in[3], 2, 448, 448, 1, 896, 0, 64, 112, 1, CU_TENSOR_MAP_SWIZZLE_128B);
  make_map(enc, &mW1, d_in[5], 3, 32, 448, 56, 3584, 64, 32, 32, 7, CU_TENSOR_MAP_SWIZZLE_64B);
  make_map(enc, &mW2, d_in[7], 2, 448, 1792, 1, 896, 0, 64, 112, 1, CU_TENSOR_MAP_SWIZZLE_128B);
  make_map(enc, &mX, d_in[0], 2, 448, 2048, 1, 896, 0, 64, 64, 1, CU_TENSOR_MAP_SWIZZLE_128B);
  fused_kernel<<<NCTA, 384, SMEM_BYTES, cudaStreamPerThread>>>(
      mQKV, mWO, mW1, mW2, mX, (const __nv_bfloat16*)d_in[0], (const __nv_bfloat16*)d_in[2], (const __nv_bfloat16*)d_in[6],
      (const __nv_bfloat16*)d_in[8], (const __nv_bfloat16*)d_in[1], (const __nv_bfloat16*)d_in[3], (const __nv_bfloat16*)d_in[5],
      (const __nv_bfloat16*)d_in[7], (__nv_bfloat16*)d_out);
}
```

```cpp
#include <cuda_runtime.h>
#include <cuda_bf16.h>
#include <cuda.h>
#include <stdint.h>

namespace {

constexpr int DM = 448, NCTA = 128;
constexpr int ABYTES = 57344;
constexpr int SLOT = 14336, NSLOT = 7;
constexpr int OFF_RING = 2 * ABYTES;
constexpr int OFF_WPHI = OFF_RING + NSLOT * SLOT;
constexpr int OFF_B1 = OFF_WPHI + 8192;
constexpr int OFF_CS = OFF_B1 + 896;
constexpr int OFF_BAR = OFF_CS + 1664;
constexpr int SMEM_BYTES = OFF_BAR + 256 + 1024;
constexpr int TILES_PER_LAYER = 46;

__device__ __align__(1024) unsigned char gP[16 * 2 * 8 * 8 * 7168];
__device__ __align__(1024) unsigned char gImg[3 * 32 * ABYTES];
__device__ __align__(1024) float2 gStat[2 * 2048 * 8];
__device__ __align__(1024) float4 gKV[2 * 8 * 2 * 5 * 128];
__device__ __align__(1024) float4 gCS[8 * 16 * 104];
__device__ __align__(128) unsigned gFlag[(2 * 32 * 7 + 32 + 1) * 32];
#define STAMP(i)

__device__ __forceinline__ uint32_t smem_u32(const void* p) { return (uint32_t)__cvta_generic_to_shared(p); }
__device__ __forceinline__ void mbar_init(uint32_t b, int c) { asm volatile("mbarrier.init.shared::cta.b64 [%0], %1;" ::"r"(b), "r"(c)); }
__device__ __forceinline__ void mbar_expect(uint32_t b, int bytes) { asm volatile("mbarrier.arrive.expect_tx.shared::cta.b64 _, [%0], %1;" ::"r"(b), "r"(bytes) : "memory"); }
__device__ __forceinline__ void mbar_arrive(uint32_t b) { asm volatile("mbarrier.arrive.shared::cta.b64 _, [%0];" ::"r"(b) : "memory"); }
__device__ __forceinline__ void mbar_wait(uint32_t b, int par) {
  uint32_t ok; int n = 0;
  while (true) {
    asm volatile("{.reg .pred p; mbarrier.try_wait.parity.shared::cta.b64 p, [%1], %2; selp.u32 %0,1,0,p;}" : "=r"(ok) : "r"(b), "r"(par) : "memory");
    if (ok) break;
    if (++n > (1 << 22)) break;
  }
}
__device__ __forceinline__ void flag_wait(const unsigned* f, unsigned target) {
  unsigned v; int n = 0;
  while (true) {
    asm volatile("ld.acquire.gpu.global.u32 %0, [%1];" : "=r"(v) : "l"(f) : "memory");
    if ((int)(v - target) >= 0) break;
    if (++n > (1 << 21)) break;
  }
}
__device__ __forceinline__ void flag_arrive(unsigned* f) { asm volatile("red.release.gpu.global.add.u32 [%0], 1;" ::"l"(f) : "memory"); }
__device__ __forceinline__ void fence_async() { asm volatile("fence.proxy.async.global;" ::: "memory"); }
__device__ __forceinline__ void fence_async_smem() { asm volatile("fence.proxy.async.shared::cta;" ::: "memory"); }
template <int ID, int N> __device__ __forceinline__ void bar_sync() { asm volatile("bar.sync %0, %1;" ::"n"(ID), "n"(N) : "memory"); }
__device__ __forceinline__ void bar_wg(int c) { if (c) bar_sync<2, 128>(); else bar_sync<1, 128>(); }
__device__ __forceinline__ void wg_fence() { asm volatile("wgmma.fence.sync.aligned;" ::: "memory"); }
__device__ __forceinline__ void wg_commit() { asm volatile("wgmma.commit_group.sync.aligned;" ::: "memory"); }
template <int N> __device__ __forceinline__ void wg_wait() { asm volatile("wgmma.wait_group.sync.aligned %0;" ::"n"(N) : "memory"); }
template <int N> __device__ __forceinline__ void reg_fence(float (&d)[N]) {
#pragma unroll
  for (int i = 0; i < N; i++) asm volatile("" : "+f"(d[i])::"memory");
}
template <int N> __device__ __forceinline__ void reg_def(float (&d)[N]) {
#pragma unroll
  for (int i = 0; i < N; i++) d[i] = 0.f;
}
__device__ __forceinline__ uint64_t mkdesc(uint32_t addr, uint32_t lbo, uint32_t sbo, uint64_t swz) {
  return (uint64_t)((addr & 0x3FFFF) >> 4) | ((uint64_t)(lbo >> 4) << 16) | ((uint64_t)(sbo >> 4) << 32) | (swz << 62);
}
__device__ __forceinline__ uint32_t pack(float a, float b) {
  uint32_t r; asm("cvt.rn.bf16x2.f32 %0, %1, %2;" : "=r"(r) : "f"(b), "f"(a)); return r;
}
__device__ __forceinline__ float lo(uint32_t u) { return __uint_as_float(u << 16); }
__device__ __forceinline__ float hi(uint32_t u) { return __uint_as_float(u & 0xFFFF0000u); }
__device__ __forceinline__ float ex2(float x) { float y; asm("ex2.approx.ftz.f32 %0, %1;" : "=f"(y) : "f"(x)); return y; }
__device__ __forceinline__ void stsm4(uint32_t a, uint32_t r0, uint32_t r1, uint32_t r2, uint32_t r3) {
  asm volatile("stmatrix.sync.aligned.m8n8.x4.shared.b16 [%0], {%1,%2,%3,%4};" ::"r"(a), "r"(r0), "r"(r1), "r"(r2), "r"(r3) : "memory");
}
__device__ __forceinline__ void tma3(uint32_t dst, const CUtensorMap* m, int c0, int c1, int c2, uint32_t bar) {
  asm volatile("cp.async.bulk.tensor.3d.shared::cluster.global.mbarrier::complete_tx::bytes [%0], [%1, {%3,%4,%5}], [%2];"
               ::"r"(dst), "l"(m), "r"(bar), "r"(c0), "r"(c1), "r"(c2) : "memory");
}
__device__ __forceinline__ void tma2(uint32_t dst, const CUtensorMap* m, int c0, int c1, uint32_t bar) {
  asm volatile("cp.async.bulk.tensor.2d.shared::cluster.global.mbarrier::complete_tx::bytes [%0], [%1, {%3,%4}], [%2];"
               ::"r"(dst), "l"(m), "r"(bar), "r"(c0), "r"(c1) : "memory");
}
__device__ __forceinline__ uint32_t lds32(uint32_t a) { uint32_t v; asm volatile("ld.shared.u32 %0, [%1];" : "=r"(v) : "r"(a) : "memory"); return v; }
__device__ __forceinline__ void bulk_ld(uint32_t dst, const void* src, int bytes, uint32_t bar) {
  asm volatile("cp.async.bulk.shared::cluster.global.mbarrier::complete_tx::bytes [%0], [%1], %2, [%3];" ::"r"(dst), "l"(src), "r"(bytes), "r"(bar) : "memory");
}
__device__ __forceinline__ uint4 ldcg4(const void* p) {
  uint4 v; asm volatile("ld.global.cg.v4.u32 {%0,%1,%2,%3}, [%4];" : "=r"(v.x), "=r"(v.y), "=r"(v.z), "=r"(v.w) : "l"(p) : "memory"); return v;
}

__device__ __forceinline__ uint2 ldcg2(const void* p) {
  uint2 v; asm volatile("ld.global.cg.v2.u32 {%0,%1}, [%2];" : "=r"(v.x), "=r"(v.y) : "l"(p) : "memory"); return v;
}

__device__ __forceinline__ void mma_ss_184(float (&d)[92], uint64_t da, uint64_t db, int acc) {
  asm volatile("{.reg .pred p; setp.ne.b32 p, %94, 0;\n"
    "wgmma.mma_async.sync.aligned.m64n184k16.f32.bf16.bf16 {%0,%1,%2,%3,%4,%5,%6,%7,%8,%9,%10,%11,%12,%13,%14,%15,%16,%17,%18,%19,%20,%21,%22,%23,%24,%25,%26,%27,%28,%29,%30,%31,%32,%33,%34,%35,%36,%37,%38,%39,%40,%41,%42,%43,%44,%45,%46,%47,%48,%49,%50,%51,%52,%53,%54,%55,%56,%57,%58,%59,%60,%61,%62,%63,%64,%65,%66,%67,%68,%69,%70,%71,%72,%73,%74,%75,%76,%77,%78,%79,%80,%81,%82,%83,%84,%85,%86,%87,%88,%89,%90,%91}, %92, %93, p, 1, 1, 0, 1;}\n"
    : "+f"(d[0]),"+f"(d[1]),"+f"(d[2]),"+f"(d[3]),"+f"(d[4]),"+f"(d[5]),"+f"(d[6]),"+f"(d[7]),"+f"(d[8]),"+f"(d[9]),"+f"(d[10]),"+f"(d[11]),"+f"(d[12]),"+f"(d[13]),"+f"(d[14]),"+f"(d[15]),"+f"(d[16]),"+f"(d[17]),"+f"(d[18]),"+f"(d[19]),"+f"(d[20]),"+f"(d[21]),"+f"(d[22]),"+f"(d[23]),"+f"(d[24]),"+f"(d[25]),"+f"(d[26]),"+f"(d[27]),"+f"(d[28]),"+f"(d[29]),"+f"(d[30]),"+f"(d[31]),"+f"(d[32]),"+f"(d[33]),"+f"(d[34]),"+f"(d[35]),"+f"(d[36]),"+f"(d[37]),"+f"(d[38]),"+f"(d[39]),"+f"(d[40]),"+f"(d[41]),"+f"(d[42]),"+f"(d[43]),"+f"(d[44]),"+f"(d[45]),"+f"(d[46]),"+f"(d[47]),"+f"(d[48]),"+f"(d[49]),"+f"(d[50]),"+f"(d[51]),"+f"(d[52]),"+f"(d[53]),"+f"(d[54]),"+f"(d[55]),"+f"(d[56]),"+f"(d[57]),"+f"(d[58]),"+f"(d[59]),"+f"(d[60]),"+f"(d[61]),"+f"(d[62]),"+f"(d[63]),"+f"(d[64]),"+f"(d[65]),"+f"(d[66]),"+f"(d[67]),"+f"(d[68]),"+f"(d[69]),"+f"(d[70]),"+f"(d[71]),"+f"(d[72]),"+f"(d[73]),"+f"(d[74]),"+f"(d[75]),"+f"(d[76]),"+f"(d[77]),"+f"(d[78]),"+f"(d[79]),"+f"(d[80]),"+f"(d[81]),"+f"(d[82]),"+f"(d[83]),"+f"(d[84]),"+f"(d[85]),"+f"(d[86]),"+f"(d[87]),"+f"(d[88]),"+f"(d[89]),"+f"(d[90]),"+f"(d[91])
    : "l"(da), "l"(db), "r"(acc));
}
__device__ __forceinline__ void mma_ss_224(float (&d)[112], uint64_t da, uint64_t db, int acc) {
  asm volatile("{.reg .pred p; setp.ne.b32 p, %114, 0;\n"
    "wgmma.mma_async.sync.aligned.m64n224k16.f32.bf16.bf16 {%0,%1,%2,%3,%4,%5,%6,%7,%8,%9,%10,%11,%12,%13,%14,%15,%16,%17,%18,%19,%20,%21,%22,%23,%24,%25,%26,%27,%28,%29,%30,%31,%32,%33,%34,%35,%36,%37,%38,%39,%40,%41,%42,%43,%44,%45,%46,%47,%48,%49,%50,%51,%52,%53,%54,%55,%56,%57,%58,%59,%60,%61,%62,%63,%64,%65,%66,%67,%68,%69,%70,%71,%72,%73,%74,%75,%76,%77,%78,%79,%80,%81,%82,%83,%84,%85,%86,%87,%88,%89,%90,%91,%92,%93,%94,%95,%96,%97,%98,%99,%100,%101,%102,%103,%104,%105,%106,%107,%108,%109,%110,%111}, %112, %113, p, 1, 1, 0, 1;}\n"
    : "+f"(d[0]),"+f"(d[1]),"+f"(d[2]),"+f"(d[3]),"+f"(d[4]),"+f"(d[5]),"+f"(d[6]),"+f"(d[7]),"+f"(d[8]),"+f"(d[9]),"+f"(d[10]),"+f"(d[11]),"+f"(d[12]),"+f"(d[13]),"+f"(d[14]),"+f"(d[15]),"+f"(d[16]),"+f"(d[17]),"+f"(d[18]),"+f"(d[19]),"+f"(d[20]),"+f"(d[21]),"+f"(d[22]),"+f"(d[23]),"+f"(d[24]),"+f"(d[25]),"+f"(d[26]),"+f"(d[27]),"+f"(d[28]),"+f"(d[29]),"+f"(d[30]),"+f"(d[31]),"+f"(d[32]),"+f"(d[33]),"+f"(d[34]),"+f"(d[35]),"+f"(d[36]),"+f"(d[37]),"+f"(d[38]),"+f"(d[39]),"+f"(d[40]),"+f"(d[41]),"+f"(d[42]),"+f"(d[43]),"+f"(d[44]),"+f"(d[45]),"+f"(d[46]),"+f"(d[47]),"+f"(d[48]),"+f"(d[49]),"+f"(d[50]),"+f"(d[51]),"+f"(d[52]),"+f"(d[53]),"+f"(d[54]),"+f"(d[55]),"+f"(d[56]),"+f"(d[57]),"+f"(d[58]),"+f"(d[59]),"+f"(d[60]),"+f"(d[61]),"+f"(d[62]),"+f"(d[63]),"+f"(d[64]),"+f"(d[65]),"+f"(d[66]),"+f"(d[67]),"+f"(d[68]),"+f"(d[69]),"+f"(d[70]),"+f"(d[71]),"+f"(d[72]),"+f"(d[73]),"+f"(d[74]),"+f"(d[75]),"+f"(d[76]),"+f"(d[77]),"+f"(d[78]),"+f"(d[79]),"+f"(d[80]),"+f"(d[81]),"+f"(d[82]),"+f"(d[83]),"+f"(d[84]),"+f"(d[85]),"+f"(d[86]),"+f"(d[87]),"+f"(d[88]),"+f"(d[89]),"+f"(d[90]),"+f"(d[91]),"+f"(d[92]),"+f"(d[93]),"+f"(d[94]),"+f"(d[95]),"+f"(d[96]),"+f"(d[97]),"+f"(d[98]),"+f"(d[99]),"+f"(d[100]),"+f"(d[101]),"+f"(d[102]),"+f"(d[103]),"+f"(d[104]),"+f"(d[105]),"+f"(d[106]),"+f"(d[107]),"+f"(d[108]),"+f"(d[109]),"+f"(d[110]),"+f"(d[111])
    : "l"(da), "l"(db), "r"(acc));
}
__device__ __forceinline__ void mma_ss_56(float (&d)[28], uint64_t da, uint64_t db, int acc) {
  asm volatile("{.reg .pred p; setp.ne.b32 p, %30, 0;\n"
    "wgmma.mma_async.sync.aligned.m64n56k16.f32.bf16.bf16 {%0,%1,%2,%3,%4,%5,%6,%7,%8,%9,%10,%11,%12,%13,%14,%15,%16,%17,%18,%19,%20,%21,%22,%23,%24,%25,%26,%27}, %28, %29, p, 1, 1, 0, 1;}\n"
    : "+f"(d[0]),"+f"(d[1]),"+f"(d[2]),"+f"(d[3]),"+f"(d[4]),"+f"(d[5]),"+f"(d[6]),"+f"(d[7]),"+f"(d[8]),"+f"(d[9]),"+f"(d[10]),"+f"(d[11]),"+f"(d[12]),"+f"(d[13]),"+f"(d[14]),"+f"(d[15]),"+f"(d[16]),"+f"(d[17]),"+f"(d[18]),"+f"(d[19]),"+f"(d[20]),"+f"(d[21]),"+f"(d[22]),"+f"(d[23]),"+f"(d[24]),"+f"(d[25]),"+f"(d[26]),"+f"(d[27])
    : "l"(da), "l"(db), "r"(acc));
}
__device__ __forceinline__ void mma_rs_56(float (&d)[28], uint32_t a0, uint32_t a1, uint32_t a2, uint32_t a3, uint64_t db, int acc) {
  asm volatile("{.reg .pred p; setp.ne.b32 p, %33, 0;\n"
    "wgmma.mma_async.sync.aligned.m64n56k16.f32.bf16.bf16 {%0,%1,%2,%3,%4,%5,%6,%7,%8,%9,%10,%11,%12,%13,%14,%15,%16,%17,%18,%19,%20,%21,%22,%23,%24,%25,%26,%27}, {%28,%29,%30,%31}, %32, p, 1, 1, 1;}\n"
    : "+f"(d[0]),"+f"(d[1]),"+f"(d[2]),"+f"(d[3]),"+f"(d[4]),"+f"(d[5]),"+f"(d[6]),"+f"(d[7]),"+f"(d[8]),"+f"(d[9]),"+f"(d[10]),"+f"(d[11]),"+f"(d[12]),"+f"(d[13]),"+f"(d[14]),"+f"(d[15]),"+f"(d[16]),"+f"(d[17]),"+f"(d[18]),"+f"(d[19]),"+f"(d[20]),"+f"(d[21]),"+f"(d[22]),"+f"(d[23]),"+f"(d[24]),"+f"(d[25]),"+f"(d[26]),"+f"(d[27])
    : "r"(a0), "r"(a1), "r"(a2), "r"(a3), "l"(db), "r"(acc));
}
__device__ __forceinline__ void mma_ss_64t(float (&d)[32], uint64_t da, uint64_t db, int acc) {
  asm volatile("{.reg .pred p; setp.ne.b32 p, %34, 0;\n"
    "wgmma.mma_async.sync.aligned.m64n64k16.f32.bf16.bf16 {%0,%1,%2,%3,%4,%5,%6,%7,%8,%9,%10,%11,%12,%13,%14,%15,%16,%17,%18,%19,%20,%21,%22,%23,%24,%25,%26,%27,%28,%29,%30,%31}, %32, %33, p, 1, 1, 1, 1;}\n"
    : "+f"(d[0]),"+f"(d[1]),"+f"(d[2]),"+f"(d[3]),"+f"(d[4]),"+f"(d[5]),"+f"(d[6]),"+f"(d[7]),"+f"(d[8]),"+f"(d[9]),"+f"(d[10]),"+f"(d[11]),"+f"(d[12]),"+f"(d[13]),"+f"(d[14]),"+f"(d[15]),"+f"(d[16]),"+f"(d[17]),"+f"(d[18]),"+f"(d[19]),"+f"(d[20]),"+f"(d[21]),"+f"(d[22]),"+f"(d[23]),"+f"(d[24]),"+f"(d[25]),"+f"(d[26]),"+f"(d[27]),"+f"(d[28]),"+f"(d[29]),"+f"(d[30]),"+f"(d[31])
    : "l"(da), "l"(db), "r"(acc));
}
__device__ __forceinline__ void mma_rs_64(float (&d)[32], uint32_t a0, uint32_t a1, uint32_t a2, uint32_t a3, uint64_t db, int acc) {
  asm volatile("{.reg .pred p; setp.ne.b32 p, %37, 0;\n"
    "wgmma.mma_async.sync.aligned.m64n64k16.f32.bf16.bf16 {%0,%1,%2,%3,%4,%5,%6,%7,%8,%9,%10,%11,%12,%13,%14,%15,%16,%17,%18,%19,%20,%21,%22,%23,%24,%25,%26,%27,%28,%29,%30,%31}, {%32,%33,%34,%35}, %36, p, 1, 1, 1;}\n"
    : "+f"(d[0]),"+f"(d[1]),"+f"(d[2]),"+f"(d[3]),"+f"(d[4]),"+f"(d[5]),"+f"(d[6]),"+f"(d[7]),"+f"(d[8]),"+f"(d[9]),"+f"(d[10]),"+f"(d[11]),"+f"(d[12]),"+f"(d[13]),"+f"(d[14]),"+f"(d[15]),"+f"(d[16]),"+f"(d[17]),"+f"(d[18]),"+f"(d[19]),"+f"(d[20]),"+f"(d[21]),"+f"(d[22]),"+f"(d[23]),"+f"(d[24]),"+f"(d[25]),"+f"(d[26]),"+f"(d[27]),"+f"(d[28]),"+f"(d[29]),"+f"(d[30]),"+f"(d[31])
    : "r"(a0), "r"(a1), "r"(a2), "r"(a3), "l"(db), "r"(acc));
}

__device__ __forceinline__ void dual_softmax(const float (&p)[28], uint32_t (&phi)[4][7]) {
  constexpr float L2E = 1.4426950408889634f;
#pragma unroll
  for (int i = 0; i < 4; i++) {
    float mx = p[i], mn = p[i];
#pragma unroll
    for (int j = 1; j < 7; j++) { mx = fmaxf(mx, p[4 * j + i]); mn = fminf(mn, p[4 * j + i]); }
    mx = fmaxf(mx, __shfl_xor_sync(~0u, mx, 1)); mn = fminf(mn, __shfl_xor_sync(~0u, mn, 1));
    mx = fmaxf(mx, __shfl_xor_sync(~0u, mx, 2)); mn = fminf(mn, __shfl_xor_sync(~0u, mn, 2));
    float a[7], b[7], sa = 0.f, sb = 0.f;
    const float mxl = mx * L2E, mnl = mn * L2E;
#pragma unroll
    for (int j = 0; j < 7; j++) {
      a[j] = ex2(fmaf(p[4 * j + i], L2E, -mxl)); b[j] = ex2(fmaf(p[4 * j + i], -L2E, mnl));
      sa += a[j]; sb += b[j];
    }
    sa += __shfl_xor_sync(~0u, sa, 1); sb += __shfl_xor_sync(~0u, sb, 1);
    sa += __shfl_xor_sync(~0u, sa, 2); sb += __shfl_xor_sync(~0u, sb, 2);
    const float ra = __fdividef(1.f, sa), rb = __fdividef(1.f, sb);
#pragma unroll
    for (int j = 0; j < 7; j++) phi[i][j] = pack(a[j] * ra, b[j] * rb);
  }
}

struct Ring {
  uint32_t full, empty, base; int slot, par;
  __device__ __forceinline__ uint32_t acquire() { mbar_wait(full + slot * 8, par); return base + slot * SLOT; }
  __device__ __forceinline__ int advance() { int s = slot; if (++slot == NSLOT) { slot = 0; par ^= 1; } return s; }
  __device__ __forceinline__ void release(int s, bool elect) { if (elect) mbar_arrive(empty + s * 8); }
};
constexpr int FL_KV = 448, FL_CS = FL_KV + 16, FL_DONE = FL_KV + 32;

__global__ void __launch_bounds__(384, 1)
fused_kernel(const __grid_constant__ CUtensorMap mQKV, const __grid_constant__ CUtensorMap mWO,
             const __grid_constant__ CUtensorMap mW1, const __grid_constant__ CUtensorMap mW2,
             const __grid_constant__ CUtensorMap mX,
             const __nv_bfloat16* __restrict__ x, const __nv_bfloat16* __restrict__ wphi,
             const __nv_bfloat16* __restrict__ b1, const __nv_bfloat16* __restrict__ b2,
             const __nv_bfloat16* __restrict__ wqkv, const __nv_bfloat16* __restrict__ wo, const __nv_bfloat16* __restrict__ w1,
             const __nv_bfloat16* __restrict__ w2, __nv_bfloat16* __restrict__ out) {
  extern __shared__ unsigned char smem_raw[];
  const uint32_t sb = (smem_u32(smem_raw) + 1023) & ~1023u;
  unsigned char* sg = smem_raw + (sb - smem_u32(smem_raw));
  const int tid = threadIdx.x, lane = tid & 31;
  const int G = blockIdx.x >> 3, r = blockIdx.x & 7;
  const uint32_t barFull = sb + OFF_BAR, barEmpty = barFull + 56, barA = barEmpty + 56, barCS = barA + 112;
  if (tid >= 256 && tid < 288) {
    if (lane < 30) mbar_init(barFull + lane * 8, lane >= 28 ? 96 : (lane >= 7 && lane < 14 ? 2 : 1));
    asm volatile("fence.mbarrier_init.release.cluster;" ::: "memory");
    fence_async_smem();
    __syncwarp();
    if (lane < 14) {
      const int k = lane >> 1, cc = lane & 1;
      mbar_expect(barA + (cc * 7 + k) * 8, 8192);
      tma2(sb + (cc * 7 + k) * 8192, &mX, 64 * k, G * 128 + 64 * cc, barA + (cc * 7 + k) * 8);
    } else if (lane < 21) {
      const int i = lane - 14;
      mbar_expect(barFull + i * 8, 12288);
      tma3(sb + OFF_RING + i * SLOT, &mQKV, 56 * r, 32 * i, 0, barFull + i * 8);
    }
  }
  __syncthreads();
  const int wgid = __shfl_sync(~0u, tid >> 7, 0);
  if (wgid == 2) {
    asm volatile("setmaxnreg.dec.sync.aligned.u32 56;");
    if (tid == 256) {
      int slot = 0, par = 0;
      for (int it = NSLOT; it < 2 * TILES_PER_LAYER; it++) {
        const int i = it >= TILES_PER_LAYER ? it - TILES_PER_LAYER : it;
        mbar_wait(barEmpty + slot * 8, par);
        const uint32_t dst = sb + OFF_RING + slot * SLOT, fb = barFull + slot * 8;
        mbar_expect(fb, i < 14 ? 12288 : SLOT);
        if (i < 14) tma3(dst, &mQKV, 56 * r, 32 * i, 0, fb);
        else if (i < 18) tma2(dst, &mWO, 56 * r, 112 * (i - 14), fb);
        else if (i < 32) tma3(dst, &mW1, 0, 32 * (i - 18), 7 * r, fb);
        else tma2(dst, &mW2, 64 * ((i - 32) >> 1), 224 * r + 112 * (i & 1), fb);
        if (++slot == NSLOT) { slot = 0; par ^= 1; }
      }
    } else if (tid >= 288) {
      unsigned ep;
      asm volatile("ld.relaxed.gpu.global.u32 %0, [%1];" : "=r"(ep) : "l"(gFlag + FL_DONE * 32) : "memory");
      const int idx = tid - 288;
#pragma unroll 1
      for (int ps = 0; ps < 3; ps++) {
        const int nch = ps ? 14 : 21, ch = min(idx >> 2, nch - 1), p = ch / 7, k0 = G * 28 + (idx & 3) * 7;
        const uint4* src = ps ? reinterpret_cast<const uint4*>(w1 + (size_t)k0 * 1792 + 224 * r) + (ps - 1) * 14 + ch
                              : reinterpret_cast<const uint4*>(wqkv + (size_t)k0 * 1344 + p * 448 + 56 * r) + (ch - 7 * p);
        uint4 cu[7];
#pragma unroll
        for (int i = 0; i < 7; i++) cu[i] = __ldg(src + i * (ps ? 224 : 168));
        float s[8] = {};
#pragma unroll
        for (int i = 0; i < 7; i++) { s[0] += lo(cu[i].x); s[1] += hi(cu[i].x); s[2] += lo(cu[i].y); s[3] += hi(cu[i].y); s[4] += lo(cu[i].z); s[5] += hi(cu[i].z); s[6] += lo(cu[i].w); s[7] += hi(cu[i].w); }
#pragma unroll
        for (int i = 0; i < 8; i++) { s[i] += __shfl_xor_sync(~0u, s[i], 1); s[i] += __shfl_xor_sync(~0u, s[i], 2); }
        if ((idx & 3) < 2 && idx < nch * 4)
          gCS[(r * 16 + G) * 104 + (ps ? 10 + ps * 14 + ch : ch + p) * 2 + (idx & 1)] = (idx & 1) ? make_float4(s[4], s[5], s[6], s[7]) : make_float4(s[0], s[1], s[2], s[3]);
        if (ps == 0 && G == 0) {
#pragma unroll 1
          for (int i = idx; i < 2 * 1280; i += 96) gKV[((i >= 1280) * 7 + r) * 1280 + i] = make_float4(0.f, 0.f, 0.f, 0.f);
        }
        if (ps == 1) continue;
        unsigned* f = gFlag + (FL_CS + (ps >> 1) * 8 + r) * 32;
        __syncwarp();
        if (lane == 0) { flag_arrive(f); flag_wait(f, (ep / NCTA + 1) * 48); }
        __syncwarp();
#pragma unroll 1
        for (int j = idx + ps * 48; j < (ps ? 208 : 96); j += 96) {
          float2 v[16], a = make_float2(0.f, 0.f);
#pragma unroll
          for (int i = 0; i < 16; i++) v[i] = __ldcg(reinterpret_cast<const float2*>(gCS + (r * 16 + i) * 104) + j);
#pragma unroll
          for (int i = 0; i < 16; i++) { a.x += v[i].x; a.y += v[i].y; }
          reinterpret_cast<float2*>(sg + OFF_CS)[j] = a;
        }
        mbar_arrive(barCS + (ps >> 1) * 8);
        if (ps == 0 && idx < 2) {
          const char* pf = idx ? (const char*)w2 + blockIdx.x * 12544 : (const char*)wo + blockIdx.x * 3136;
          asm volatile("cp.async.bulk.prefetch.L2.global [%0], %1;" ::"l"(pf), "r"(idx ? 12544 : 3136) : "memory");
        }
      }
    }
  } else {
  asm volatile("setmaxnreg.inc.sync.aligned.u32 224;");
  const int c = wgid, w = (tid >> 5) & 3, g = lane >> 2, t = lane & 3;
  const bool elect = (tid & 127) == 0;
  const uint32_t abuf = sb + c * ABYTES, barAc = barA + c * 56;
  const int row0 = G * 128 + c * 64;
  unsigned epoch;
  asm volatile("ld.relaxed.gpu.global.u32 %0, [%1];" : "=r"(epoch) : "l"(gFlag + FL_DONE * 32) : "memory");
  STAMP(24);
  float mean[2], rstd[2];
  uint32_t wv[7];
#pragma unroll
  for (int i = 0; i < 7; i++)
    wv[i] = __ldg(reinterpret_cast<const unsigned short*>(wphi) + (56 * r + i * 8 + (tid >> 5)) * 28 + min(lane, 27));
  const uint32_t bv = __ldg(reinterpret_cast<const unsigned short*>(b1) + 224 * r + min(tid, 223));
  STAMP(0);
  Ring ring{barFull, barEmpty, sb + OFF_RING, 0, 0};
  int apar = 0;
  const uint32_t stsm_off = (w * 16 + ((lane >> 3) & 1) * 8 + (lane & 7)) * 128;
  const uint32_t stsm_hi = lane >> 4;
  const uint64_t dA = mkdesc(abuf, 1024, 128, 0);

  auto gather = [&](unsigned* fl, const unsigned char* img) {
    __syncwarp();
    if (lane == 0) flag_arrive(fl);
    if (w == 0) {
      STAMP(27);
      if (lane == 0) flag_wait(fl, epoch * 32);
      __syncwarp();
      STAMP(28);
      if (lane < 7) { fence_async(); mbar_expect(barAc + lane * 8, 8192); bulk_ld(abuf + lane * 8192, img + lane * 8192, 8192, barAc + lane * 8); }
    }
    __syncwarp();
    apar ^= 1;
  };
  auto slice_off = [&](int j, int hh) -> uint32_t {
    return (7 * r + j) * 1024 + (w * 2 + hh) * 128 + lane * 4;
  };
  uint4 su[2];
  auto load_stats = [&](const float2* st) {
    mbar_wait(barAc, apar);
#pragma unroll
    for (int hh = 0; hh < 2; hh++) su[hh] = ldcg4(st + (size_t)(row0 + w * 16 + hh * 8 + g) * 8 + 2 * t);
  };
  auto finish_stats = [&]() {
#pragma unroll
    for (int hh = 0; hh < 2; hh++) {
      const float m0 = __uint_as_float(su[hh].x), m1 = __uint_as_float(su[hh].z);
      float m = m0 + m1;
      m += __shfl_xor_sync(~0u, m, 1); m += __shfl_xor_sync(~0u, m, 2);
      m *= 0.125f;
      float q = __uint_as_float(su[hh].y) + __uint_as_float(su[hh].w) + 56.f * ((m0 - m) * (m0 - m) + (m1 - m) * (m1 - m));
      q += __shfl_xor_sync(~0u, q, 1); q += __shfl_xor_sync(~0u, q, 2);
      mean[hh] = m; rstd[hh] = rsqrtf(q * (1.f / DM) + 1e-5f);
    }
  };

#pragma unroll 1
  for (int layer = 0; layer < 2; layer++) {
    unsigned* const fl = gFlag + (layer * 32 + G * 2 + c) * 7 * 32;
    uint32_t phiq[4][7], xs[7][2];
    {
      float acc[92]; reg_def(acc);
      const uint64_t dQ = layer ? dA : mkdesc(abuf, 16, 1024, 1);
      const int kstep = layer ? 128 : 2;
      int prev = 0;
      float sh[2] = {0.f, 0.f}, s1[2] = {0.f, 0.f}, s2[2] = {0.f, 0.f};
      if (layer) load_stats(gStat + 2048 * 8);
#pragma unroll 1
      for (int st = 0; st < 14; st++) {
        if (!(st & 1)) mbar_wait(barAc + (st >> 1) * 8, apar);
        const uint64_t da = dQ + (st >> 1) * 512 + (st & 1) * 2 * kstep, db = mkdesc(ring.acquire(), 4096, 1024, 1);
        wg_fence();
        mma_ss_184(acc, da, db, st);
        mma_ss_184(acc, da + kstep, db + 128, 1);
        wg_commit();
        if (layer == 0) {
#pragma unroll
          for (int hh = 0; hh < 2; hh++) {
            const uint4 u = *reinterpret_cast<const uint4*>(sg + c * ABYTES + (st >> 1) * 8192 + (w * 16 + hh * 8 + g) * 128 + ((((st ^ g) & 1) * 4 + t) << 4));
            if (st == 0) sh[hh] = lo(u.x);
            const uint32_t e[4] = {u.x, u.y, u.z, u.w};
#pragma unroll
            for (int z = 0; z < 4; z++) { const float a = lo(e[z]) - sh[hh], b = hi(e[z]) - sh[hh]; s1[hh] += a + b; s2[hh] = fmaf(a, a, fmaf(b, b, s2[hh])); }
          }
        }
        if (st > 0) { wg_wait<1>(); ring.release(prev, elect); }
        prev = ring.advance();
      }
      if (layer == 0) {
#pragma unroll
        for (int hh = 0; hh < 2; hh++) {
          const float d = s1[hh] * (1.f / 112.f), m = sh[hh] + d, q = 0.5f * fmaxf(s2[hh] - d * s1[hh], 0.f);
          su[hh] = make_uint4(__float_as_uint(m), __float_as_uint(q), __float_as_uint(m), __float_as_uint(q));
        }
#pragma unroll
        for (int i = 0; i < 8; i++) {
          const int k = i * 8 + (tid >> 5);
          *reinterpret_cast<uint32_t*>(sg + OFF_WPHI + k * 128 + ((g ^ (k & 7)) << 4) + t * 4) = (i < 7 && lane < 28) ? wv[i % 7] << (k >= 28 ? 16 : 0) : 0u;
        }
        if (tid < 224) reinterpret_cast<uint32_t*>(sg + OFF_B1)[tid] = bv << 16;
        fence_async_smem();
        bar_sync<3, 256>();
        epoch = epoch / NCTA + 1;
        STAMP(25);
        mbar_wait(barCS, 0);
      }
      finish_stats();
#pragma unroll
      for (int j = 0; j < 7; j++) {
        const int ci = 7 * r + j;
        const uint32_t a = abuf + (layer ? slice_off(j, 0) : (ci >> 3) * 8192 + (w * 16 + g) * 128 + (((ci & 7) ^ g) << 4) + t * 4);
        xs[j][0] = lds32(a); xs[j][1] = lds32(a + (layer ? 128 : 1024));
      }
      wg_wait<0>(); reg_fence(acc);
      ring.release(prev, elect);
      STAMP(1 + layer * 12);
      uint32_t f[3][14];
      {
        const float2* cs = reinterpret_cast<const float2*>(sg + OFF_CS) + t;
        const float mr0 = -mean[0] * rstd[0], mr1 = -mean[1] * rstd[1];
#pragma unroll
        for (int p = 0; p < 3; p++)
#pragma unroll
          for (int j = 0; j < 7; j++) {
            const float2 s = cs[p * 32 + j * 4];
            const int b = p * 32 + j * 4;
            f[p][2 * j] = pack(fmaf(acc[b], rstd[0], s.x * mr0), fmaf(acc[b + 1], rstd[0], s.y * mr0));
            f[p][2 * j + 1] = pack(fmaf(acc[b + 2], rstd[1], s.x * mr1), fmaf(acc[b + 3], rstd[1], s.y * mr1));
          }
      }
      float pk[28], pq[28]; reg_def(pk); reg_def(pq);
      const uint64_t dW = mkdesc(sb + OFF_WPHI, 4096, 1024, 1);
      wg_fence();
#pragma unroll
      for (int s = 0; s < 4; s++)
        mma_rs_56(pk, f[1][4 * s], f[1][4 * s + 1], s < 3 ? f[1][(4 * s + 2) % 14] : 0u, s < 3 ? f[1][(4 * s + 3) % 14] : 0u, dW + s * 128, s);
      wg_commit();
#pragma unroll
      for (int s = 0; s < 4; s++)
        mma_rs_56(pq, f[0][4 * s], f[0][4 * s + 1], s < 3 ? f[0][(4 * s + 2) % 14] : 0u, s < 3 ? f[0][(4 * s + 3) % 14] : 0u, dW + s * 128, s);
      wg_commit();
      bar_wg(c);
      const uint32_t srow = abuf + stsm_off, ones = t == 0 ? 0x3F803F80u : 0u;
#pragma unroll
      for (int jp = 0; jp < 4; jp++)
        stsm4(srow + 16384 + (((2 * jp + stsm_hi) ^ (lane & 7)) << 4), f[2][4 * jp], f[2][4 * jp + 1],
              jp < 3 ? f[2][(4 * jp + 2) % 14] : ones, jp < 3 ? f[2][(4 * jp + 3) % 14] : ones);
      wg_wait<0>(); reg_fence(pk); reg_fence(pq);
#pragma unroll 1
      for (int pass = 0; pass < 2; pass++) {
        dual_softmax(pk, phiq);
        if (pass) break;
#pragma unroll
        for (int e = 0; e < 2; e++)
#pragma unroll
          for (int jp = 0; jp < 4; jp++)
            stsm4(srow + e * 8192 + (((2 * jp + stsm_hi) ^ (lane & 7)) << 4), phiq[e][2 * jp], phiq[2 + e][2 * jp],
                  jp < 3 ? phiq[e][(2 * jp + 1) % 7] : 0u, jp < 3 ? phiq[2 + e][(2 * jp + 1) % 7] : 0u);
        fence_async_smem();
        bar_sync<3, 256>();
        float kv[32]; reg_def(kv);
        const uint64_t dP = mkdesc(sb + c * 8192, 4096, 1024, 1), dV = mkdesc(sb + 16384, 4096, 1024, 1);
        wg_fence();
#pragma unroll
        for (int s = 0; s < 8; s++) mma_ss_64t(kv, dP + (s >> 2) * (ABYTES / 16) + (s & 3) * 128, dV + (s >> 2) * (ABYTES / 16) + (s & 3) * 128, s);
        wg_commit();
        wg_wait<0>(); reg_fence(kv);
        float4* kvg = gKV + ((layer * 8 + r) * 2 + c) * 640 + (tid & 127);
#pragma unroll
        for (int i = 0; i < 5; i++) {
          float v0, v1, v2, v3;
          if (i == 4) { v0 = kv[28]; v1 = kv[29]; v2 = kv[30]; v3 = kv[31]; }
          else { v0 = c ? kv[12 + 4 * i] : kv[4 * i]; v1 = c ? kv[13 + 4 * i] : kv[1 + 4 * i]; v2 = c ? kv[14 + 4 * i] : kv[2 + 4 * i]; v3 = c ? kv[15 + 4 * i] : kv[3 + 4 * i]; }
          const bool use = i == 4 ? t == 0 : (i == 0 ? (c == 0 || t >= 2) : (i == 3 ? (c == 1 || t < 2) : true));
          if (use) asm volatile("red.relaxed.gpu.global.add.v4.f32 [%0], {%1,%2,%3,%4};" ::"l"(kvg + i * 128), "f"(v0), "f"(v1), "f"(v2), "f"(v3) : "memory");
        }
        __syncwarp();
        if (lane == 0) flag_arrive(gFlag + (FL_KV + layer * 8 + r) * 32);
        __syncwarp();
        STAMP(2 + layer * 12);
#pragma unroll
        for (int i = 0; i < 28; i++) pk[i] = pq[i];
      }
    }
    {
      if (elect) flag_wait(gFlag + (FL_KV + layer * 8 + r) * 32, epoch * 128);
      bar_wg(c);
      STAMP(3 + layer * 12);
      const float4* kvg = gKV + (layer * 8 + r) * 1280 + (tid & 127);
      uint4 kk[2][5];
#pragma unroll
      for (int e = 0; e < 2; e++)
#pragma unroll
        for (int i = 0; i < 5; i++) kk[e][i] = ldcg4(kvg + e * 640 + i * 128);
      const uint32_t srow = abuf + 24576 + stsm_off;
#pragma unroll
      for (int e = 0; e < 2; e++) {
        uint32_t f[8][2];
#pragma unroll
        for (int j = 0; j < 8; j++) { f[j][0] = 0u; f[j][1] = 0u; }
#pragma unroll
        for (int i = 0; i < 4; i++) {
          f[i + 3 * e][0] = pack(__uint_as_float(kk[e][i].x), __uint_as_float(kk[e][i].y));
          f[i + 3 * e][1] = pack(__uint_as_float(kk[e][i].z), __uint_as_float(kk[e][i].w));
        }
        f[7][0] = e ? pack(0.f, __uint_as_float(kk[e][4].y)) : pack(__uint_as_float(kk[e][4].x), 0.f);
        f[7][1] = e ? pack(0.f, __uint_as_float(kk[e][4].w)) : pack(__uint_as_float(kk[e][4].z), 0.f);
#pragma unroll
        for (int jp = 0; jp < 4; jp++)
          stsm4(srow + e * 8192 + (((2 * jp + stsm_hi) ^ (lane & 7)) << 4), f[2 * jp][0], f[2 * jp][1], f[2 * jp + 1][0], f[2 * jp + 1][1]);
      }
      fence_async_smem();
      bar_wg(c);
      float num[32]; reg_def(num);
      const uint64_t dK = mkdesc(abuf + 24576, 4096, 1024, 1);
      wg_fence();
#pragma unroll
      for (int e = 0; e < 2; e++)
#pragma unroll
        for (int s = 0; s < 4; s++)
          mma_rs_64(num, phiq[e][2 * s], phiq[2 + e][2 * s], s < 3 ? phiq[e][(2 * s + 1) % 7] : 0u, s < 3 ? phiq[2 + e][(2 * s + 1) % 7] : 0u,
                    dK + e * 512 + s * 128, e + s);
      wg_commit();
      wg_wait<0>(); reg_fence(num);
      float rd[4];
#pragma unroll
      for (int i = 0; i < 4; i++) rd[i] = __fdividef(1.f, __shfl_sync(~0u, num[28 + i], lane & ~3) + 1e-6f);
      unsigned char* img = gImg + (size_t)(G * 2 + c) * ABYTES;
#pragma unroll
      for (int j = 0; j < 7; j++) {
        const bool hb = j > 3 || (j == 3 && t >= 2);
        const float r0 = hb ? rd[1] : rd[0], r1 = hb ? rd[3] : rd[2];
        *reinterpret_cast<uint32_t*>(img + slice_off(j, 0)) = pack(num[4 * j] * r0, num[4 * j + 1] * r0);
        *reinterpret_cast<uint32_t*>(img + slice_off(j, 1)) = pack(num[4 * j + 2] * r1, num[4 * j + 3] * r1);
      }
      STAMP(4 + layer * 12);
      gather(fl, img);
      STAMP(5 + layer * 12);
    }
    {
      float acc[28]; reg_def(acc);
      int prev = 0;
#pragma unroll 1
      for (int st = 0; st < 4; st++) {
        mbar_wait(barAc + (st * 7 + 3) / 4 * 8, apar);
        mbar_wait(barAc + (st * 7 + 6) / 4 * 8, apar);
        const uint64_t db = mkdesc(ring.acquire(), 4096, 1024, 1);
        wg_fence();
#pragma unroll
        for (int s = 0; s < 7; s++) { const int ks = st * 7 + s; mma_ss_56(acc, dA + ks * 128, db + s * 128, ks); }
        wg_commit();
        if (st > 0) { wg_wait<1>(); ring.release(prev, elect); }
        prev = ring.advance();
      }
      wg_wait<0>(); reg_fence(acc);
      ring.release(prev, elect);
      unsigned char* img = gImg + (size_t)(32 + G * 2 + c) * ABYTES;
#pragma unroll
      for (int hh = 0; hh < 2; hh++) {
        float s = 0.f, q = 0.f;
#pragma unroll
        for (int j = 0; j < 7; j++) {
          xs[j][hh] = pack(lo(xs[j][hh]) + acc[4 * j + 2 * hh], hi(xs[j][hh]) + acc[4 * j + 2 * hh + 1]);
          *reinterpret_cast<uint32_t*>(img + slice_off(j, hh)) = xs[j][hh];
          s += lo(xs[j][hh]) + hi(xs[j][hh]);
        }
        s += __shfl_xor_sync(~0u, s, 1); s += __shfl_xor_sync(~0u, s, 2);
        s *= 1.f / 56.f;
#pragma unroll
        for (int j = 0; j < 7; j++) { const float a = lo(xs[j][hh]) - s, b = hi(xs[j][hh]) - s; q = fmaf(a, a, q); q = fmaf(b, b, q); }
        q += __shfl_xor_sync(~0u, q, 1); q += __shfl_xor_sync(~0u, q, 2);
        if (t == 0) gStat[(size_t)(row0 + w * 16 + hh * 8 + g) * 8 + r] = make_float2(s, q);
      }
      STAMP(6 + layer * 12);
      gather(fl + 32, img);
      STAMP(7 + layer * 12);
    }
    {
      uint32_t hf[28][2];
      {
        float acc[112]; reg_def(acc);
        int prev = 0;
        load_stats(gStat);
#pragma unroll 1
        for (int st = 0; st < 14; st++) {
          if (!(st & 1)) mbar_wait(barAc + (st >> 1) * 8, apar);
          const uint64_t da = dA + st * 256, db = mkdesc(ring.acquire(), 2048, 512, 2);
          wg_fence();
          mma_ss_224(acc, da, db, st);
          mma_ss_224(acc, da + 128, db + 64, 1);
          wg_commit();
          if (st > 0) { wg_wait<1>(); ring.release(prev, elect); }
          prev = ring.advance();
        }
        finish_stats();
        mbar_wait(barCS + 8, 0);
        wg_wait<0>(); reg_fence(acc);
        ring.release(prev, elect);
        STAMP(8 + layer * 12);
        const float2* bs = reinterpret_cast<const float2*>(sg + OFF_B1) + t;
        const float2* cs = reinterpret_cast<const float2*>(sg + OFF_CS + 768) + t;
        const float mr0 = -mean[0] * rstd[0], mr1 = -mean[1] * rstd[1];
#pragma unroll
        for (int j = 0; j < 28; j++) {
          const float2 b = bs[4 * j], s = cs[4 * j];
          const float h0 = fmaxf(fmaf(acc[4 * j], rstd[0], fmaf(s.x, mr0, b.x)), 0.f), h1 = fmaxf(fmaf(acc[4 * j + 1], rstd[0], fmaf(s.y, mr0, b.y)), 0.f);
          const float h2 = fmaxf(fmaf(acc[4 * j + 2], rstd[1], fmaf(s.x, mr1, b.x)), 0.f), h3 = fmaxf(fmaf(acc[4 * j + 3], rstd[1], fmaf(s.y, mr1, b.y)), 0.f);
          hf[j][0] = pack(h0 * h0, h1 * h1); hf[j][1] = pack(h2 * h2, h3 * h3);
        }
      }
      unsigned char* pdst = gP + (size_t)(((G * 2 + c) * 8 + 2 * w) * 8 + r) * 7168 + lane * 8;
      uint2 pk[8] = {};
#pragma unroll 1
      for (int ch = 0; ch < 7; ch++) {
        float acc[32]; reg_def(acc);
        int sl0 = 0, sl1 = 0;
#pragma unroll
        for (int hk = 0; hk < 2; hk++) {
          const uint64_t db = mkdesc(ring.acquire(), 4096, 1024, 1);
          wg_fence();
#pragma unroll
          for (int s = 0; s < 7; s++) { const int ks = hk * 7 + s; mma_rs_64(acc, hf[2 * ks][0], hf[2 * ks][1], hf[2 * ks + 1][0], hf[2 * ks + 1][1], db + s * 128, ks); }
          wg_commit();
          if (hk) sl1 = ring.advance(); else sl0 = ring.advance();
        }
        if (ch > 0) {
#pragma unroll
          for (int i = 0; i < 8; i++) *reinterpret_cast<uint2*>(pdst + (i & 1) * (8 * 7168) + (i >> 1) * 256) = pk[i];
          pdst += 1024;
        }
        wg_wait<1>(); ring.release(sl0, elect);
        wg_wait<0>(); reg_fence(acc); ring.release(sl1, elect);
#pragma unroll
        for (int i = 0; i < 8; i++) {
          const int b = (i >> 1) * 8 + (i & 1) * 2;
          pk[i] = make_uint2(pack(acc[b], acc[b + 1]), pack(acc[b + 4], acc[b + 5]));
        }
      }
#pragma unroll
      for (int i = 0; i < 8; i++) *reinterpret_cast<uint2*>(pdst + (i & 1) * (8 * 7168) + (i >> 1) * 256) = pk[i];
      STAMP(9 + layer * 12);
    }
    {
      uint32_t bx[14];
#pragma unroll
      for (int j = 0; j < 14; j++) bx[j] = __ldg(reinterpret_cast<const uint32_t*>(b2 + w * 112 + j * 8 + 2 * t));
      __syncwarp();
      if (lane == 0) { flag_arrive(fl + (3 + w) * 32); flag_wait(fl + (3 + (r >> 1)) * 32, epoch * 8); }
      __syncwarp();
      STAMP(10 + layer * 12);
      const unsigned char* psrc = gP + (size_t)(((G * 2 + c) * 8 + r) * 8) * 7168 + w * 1792 + lane * 8;
      unsigned char* img = gImg + (size_t)(64 + G * 2 + c) * ABYTES;
      uint2 pv[8][7];
#pragma unroll
      for (int s = 0; s < 8; s++)
#pragma unroll
        for (int i = 0; i < 7; i++) pv[s][i] = ldcg2(psrc + s * 7168 + i * 256);
      const uint32_t off = w * 14336 + r * 128 + lane * 4;
      unsigned char* dst = layer ? reinterpret_cast<unsigned char*>(out + (size_t)(row0 + r * 8 + g) * DM + w * 112 + 2 * t) : img + off;
      float sm = 0.f, q = 0.f;
#pragma unroll
      for (int j = 0; j < 14; j++) {
        float y0 = lo(bx[j]), y1 = hi(bx[j]);
        const uint32_t xo = lds32(abuf + off + j * 1024);
        y0 += lo(xo); y1 += hi(xo);
#pragma unroll
        for (int s = 0; s < 8; s++) { const uint32_t u = (j & 1) ? pv[s][j >> 1].y : pv[s][j >> 1].x; y0 += lo(u); y1 += hi(u); }
        bx[j] = pack(y0, y1);
        *reinterpret_cast<uint32_t*>(dst + j * (layer ? 16 : 1024)) = bx[j];
        sm += lo(bx[j]) + hi(bx[j]);
      }
      if (layer) break;
      sm += __shfl_xor_sync(~0u, sm, 1); sm += __shfl_xor_sync(~0u, sm, 2);
      sm *= 1.f / 112.f;
#pragma unroll
      for (int j = 0; j < 14; j++) { const float a = lo(bx[j]) - sm, b = hi(bx[j]) - sm; q = fmaf(a, a, q); q = fmaf(b, b, q); }
      q += __shfl_xor_sync(~0u, q, 1); q += __shfl_xor_sync(~0u, q, 2);
      if (t < 2) gStat[(size_t)(2048 + row0 + r * 8 + g) * 8 + 2 * w + t] = make_float2(sm, q * 0.5f);
      STAMP(11);
      gather(fl + 64, img);
      STAMP(12);
    }
  }
  STAMP(30);
  if (tid == 0) asm volatile("red.relaxed.gpu.global.add.u32 [%0], 1;" ::"l"(gFlag + FL_DONE * 32) : "memory");
  }
}

typedef CUresult (*EncFn)(CUtensorMap*, CUtensorMapDataType, cuuint32_t, void*, const cuuint64_t*, const cuuint64_t*,
                          const cuuint32_t*, const cuuint32_t*, CUtensorMapInterleave, CUtensorMapSwizzle,
                          CUtensorMapL2promotion, CUtensorMapFloatOOBfill);

void make_map(EncFn enc, CUtensorMap* m, void* p, int rank, uint64_t d0, uint64_t d1, uint64_t d2, uint64_t s1, uint64_t s2,
              uint32_t b0, uint32_t b1, uint32_t b2, CUtensorMapSwizzle sw) {
  cuuint64_t dims[3] = {d0, d1, d2}, strides[2] = {s1, s2};
  cuuint32_t box[3] = {b0, b1, b2}, es[3] = {1, 1, 1};
  enc(m, CU_TENSOR_MAP_DATA_TYPE_BFLOAT16, rank, p, dims, strides, box, es, CU_TENSOR_MAP_INTERLEAVE_NONE, sw,
      CU_TENSOR_MAP_L2_PROMOTION_L2_128B, CU_TENSOR_MAP_FLOAT_OOB_FILL_NONE);
}

}

extern "C" void kernel_launch(void* const* d_in, const int* in_sizes, int n_in, void* d_out, int out_size) {
  static EncFn enc = nullptr;
  if (!enc) {
    cudaDriverEntryPointQueryResult st;
    void* fn = nullptr;
    cudaGetDriverEntryPoint("cuTensorMapEncodeTiled", &fn, cudaEnableDefault, &st);
    enc = (EncFn)fn;
    cudaFuncSetAttribute(fused_kernel, cudaFuncAttributeMaxDynamicSharedMemorySize, SMEM_BYTES);
  }
  CUtensorMap mQKV, mWO, mW1, mW2, mX;
  make_map(enc, &mQKV, d_in[1], 3, 448, 448, 3, 2688, 896, 64, 32, 3, CU_TENSOR_MAP_SWIZZLE_128B);
  make_map(enc, &mWO, d_in[3], 2, 448, 448, 1, 896, 0, 64, 112, 1, CU_TENSOR_MAP_SWIZZLE_128B);
  make_map(enc, &mW1, d_in[5], 3, 32, 448, 56, 3584, 64, 32, 32, 7, CU_TENSOR_MAP_SWIZZLE_64B);
  make_map(enc, &mW2, d_in[7], 2, 448, 1792, 1, 896, 0, 64, 112, 1, CU_TENSOR_MAP_SWIZZLE_128B);
  make_map(enc, &mX, d_in[0], 2, 448, 2048, 1, 896, 0, 64, 64, 1, CU_TENSOR_MAP_SWIZZLE_128B);
  fused_kernel<<<NCTA, 384, SMEM_BYTES, cudaStreamPerThread>>>(
      mQKV, mWO, mW1, mW2, mX, (const __nv_bfloat16*)d_in[0], (const __nv_bfloat16*)d_in[2], (const __nv_bfloat16*)d_in[6],
      (const __nv_bfloat16*)d_in[8], (const __nv_bfloat16*)d_in[1], (const __nv_bfloat16*)d_in[3], (const __nv_bfloat16*)d_in[5],
      (const __nv_bfloat16*)d_in[7], (__nv_bfloat16*)d_out);
}
```

```cpp
#include <cuda_runtime.h>
#include <cuda_bf16.h>
#include <cuda.h>
#include <stdint.h>

namespace {

constexpr int DM = 448, NCTA = 128;
constexpr int ABYTES = 57344;
constexpr int SLOT = 14336, NSLOT = 7;
constexpr int OFF_RING = 2 * ABYTES;
constexpr int OFF_WPHI = OFF_RING + NSLOT * SLOT;
constexpr int OFF_B1 = OFF_WPHI + 8192;
constexpr int OFF_CS = OFF_B1 + 896;
constexpr int OFF_ST = OFF_CS + 1664;
constexpr int OFF_BAR = OFF_ST + 1024;
constexpr int SMEM_BYTES = OFF_BAR + 256 + 1024;
constexpr int TILES_PER_LAYER = 46;

__device__ __align__(1024) unsigned char gP[16 * 2 * 8 * 8 * 7168];
__device__ __align__(1024) unsigned char gImg[3 * 32 * ABYTES];
__device__ __align__(1024) float2 gStat[2 * 2048 * 8];
__device__ __align__(1024) float4 gKV[2 * 8 * 2 * 5 * 128];
__device__ __align__(1024) float4 gCS[8 * 16 * 104];
__device__ __align__(128) unsigned gFlag[(2 * 32 * 7 + 32 + 1 + 16) * 32];
#define STAMP(i)

__device__ __forceinline__ uint32_t smem_u32(const void* p) { return (uint32_t)__cvta_generic_to_shared(p); }
__device__ __forceinline__ void mbar_init(uint32_t b, int c) { asm volatile("mbarrier.init.shared::cta.b64 [%0], %1;" ::"r"(b), "r"(c)); }
__device__ __forceinline__ void mbar_expect(uint32_t b, int bytes) { asm volatile("mbarrier.arrive.expect_tx.shared::cta.b64 _, [%0], %1;" ::"r"(b), "r"(bytes) : "memory"); }
__device__ __forceinline__ void mbar_arrive(uint32_t b) { asm volatile("mbarrier.arrive.shared::cta.b64 _, [%0];" ::"r"(b) : "memory"); }
__device__ __forceinline__ void mbar_wait(uint32_t b, int par) {
  uint32_t ok; int n = 0;
  while (true) {
    asm volatile("{.reg .pred p; mbarrier.try_wait.parity.shared::cta.b64 p, [%1], %2; selp.u32 %0,1,0,p;}" : "=r"(ok) : "r"(b), "r"(par) : "memory");
    if (ok) break;
    if (++n > (1 << 22)) break;
  }
}
__device__ __forceinline__ void flag_wait(const unsigned* f, unsigned target) {
  unsigned v; int n = 0;
  while (true) {
    asm volatile("ld.acquire.gpu.global.u32 %0, [%1];" : "=r"(v) : "l"(f) : "memory");
    if ((int)(v - target) >= 0) break;
    if (++n > (1 << 21)) break;
  }
}
__device__ __forceinline__ void flag_arrive(unsigned* f) { asm volatile("red.release.gpu.global.add.u32 [%0], 1;" ::"l"(f) : "memory"); }
__device__ __forceinline__ void fence_async() { asm volatile("fence.proxy.async.global;" ::: "memory"); }
__device__ __forceinline__ void fence_async_smem() { asm volatile("fence.proxy.async.shared::cta;" ::: "memory"); }
template <int ID, int N> __device__ __forceinline__ void bar_sync() { asm volatile("bar.sync %0, %1;" ::"n"(ID), "n"(N) : "memory"); }
__device__ __forceinline__ void bar_wg(int c) { if (c) bar_sync<2, 128>(); else bar_sync<1, 128>(); }
__device__ __forceinline__ void wg_fence() { asm volatile("wgmma.fence.sync.aligned;" ::: "memory"); }
__device__ __forceinline__ void wg_commit() { asm volatile("wgmma.commit_group.sync.aligned;" ::: "memory"); }
template <int N> __device__ __forceinline__ void wg_wait() { asm volatile("wgmma.wait_group.sync.aligned %0;" ::"n"(N) : "memory"); }
template <int N> __device__ __forceinline__ void reg_fence(float (&d)[N]) {
#pragma unroll
  for (int i = 0; i < N; i++) asm volatile("" : "+f"(d[i])::"memory");
}
template <int N> __device__ __forceinline__ void reg_def(float (&d)[N]) {
#pragma unroll
  for (int i = 0; i < N; i++) d[i] = 0.f;
}
__device__ __forceinline__ uint64_t mkdesc(uint32_t addr, uint32_t lbo, uint32_t sbo, uint64_t swz) {
  return (uint64_t)((addr & 0x3FFFF) >> 4) | ((uint64_t)(lbo >> 4) << 16) | ((uint64_t)(sbo >> 4) << 32) | (swz << 62);
}
__device__ __forceinline__ uint32_t pack(float a, float b) {
  uint32_t r; asm("cvt.rn.bf16x2.f32 %0, %1, %2;" : "=r"(r) : "f"(b), "f"(a)); return r;
}
__device__ __forceinline__ float lo(uint32_t u) { return __uint_as_float(u << 16); }
__device__ __forceinline__ float hi(uint32_t u) { return __uint_as_float(u & 0xFFFF0000u); }
__device__ __forceinline__ float ex2(float x) { float y; asm("ex2.approx.ftz.f32 %0, %1;" : "=f"(y) : "f"(x)); return y; }
__device__ __forceinline__ void stsm4(uint32_t a, uint32_t r0, uint32_t r1, uint32_t r2, uint32_t r3) {
  asm volatile("stmatrix.sync.aligned.m8n8.x4.shared.b16 [%0], {%1,%2,%3,%4};" ::"r"(a), "r"(r0), "r"(r1), "r"(r2), "r"(r3) : "memory");
}
__device__ __forceinline__ void tma3(uint32_t dst, const CUtensorMap* m, int c0, int c1, int c2, uint32_t bar) {
  asm volatile("cp.async.bulk.tensor.3d.shared::cluster.global.mbarrier::complete_tx::bytes [%0], [%1, {%3,%4,%5}], [%2];"
               ::"r"(dst), "l"(m), "r"(bar), "r"(c0), "r"(c1), "r"(c2) : "memory");
}
__device__ __forceinline__ void tma2(uint32_t dst, const CUtensorMap* m, int c0, int c1, uint32_t bar) {
  asm volatile("cp.async.bulk.tensor.2d.shared::cluster.global.mbarrier::complete_tx::bytes [%0], [%1, {%3,%4}], [%2];"
               ::"r"(dst), "l"(m), "r"(bar), "r"(c0), "r"(c1) : "memory");
}
__device__ __forceinline__ uint32_t lds32(uint32_t a) { uint32_t v; asm volatile("ld.shared.u32 %0, [%1];" : "=r"(v) : "r"(a) : "memory"); return v; }
__device__ __forceinline__ void bulk_ld(uint32_t dst, const void* src, int bytes, uint32_t bar) {
  asm volatile("cp.async.bulk.shared::cluster.global.mbarrier::complete_tx::bytes [%0], [%1], %2, [%3];" ::"r"(dst), "l"(src), "r"(bytes), "r"(bar) : "memory");
}
__device__ __forceinline__ uint4 ldcg4(const void* p) {
  uint4 v; asm volatile("ld.global.cg.v4.u32 {%0,%1,%2,%3}, [%4];" : "=r"(v.x), "=r"(v.y), "=r"(v.z), "=r"(v.w) : "l"(p) : "memory"); return v;
}

__device__ __forceinline__ uint2 ldcg2(const void* p) {
  uint2 v; asm volatile("ld.global.cg.v2.u32 {%0,%1}, [%2];" : "=r"(v.x), "=r"(v.y) : "l"(p) : "memory"); return v;
}

__device__ __forceinline__ void mma_ss_184(float (&d)[92], uint64_t da, uint64_t db, int acc) {
  asm volatile("{.reg .pred p; setp.ne.b32 p, %94, 0;\n"
    "wgmma.mma_async.sync.aligned.m64n184k16.f32.bf16.bf16 {%0,%1,%2,%3,%4,%5,%6,%7,%8,%9,%10,%11,%12,%13,%14,%15,%16,%17,%18,%19,%20,%21,%22,%23,%24,%25,%26,%27,%28,%29,%30,%31,%32,%33,%34,%35,%36,%37,%38,%39,%40,%41,%42,%43,%44,%45,%46,%47,%48,%49,%50,%51,%52,%53,%54,%55,%56,%57,%58,%59,%60,%61,%62,%63,%64,%65,%66,%67,%68,%69,%70,%71,%72,%73,%74,%75,%76,%77,%78,%79,%80,%81,%82,%83,%84,%85,%86,%87,%88,%89,%90,%91}, %92, %93, p, 1, 1, 0, 1;}\n"
    : "+f"(d[0]),"+f"(d[1]),"+f"(d[2]),"+f"(d[3]),"+f"(d[4]),"+f"(d[5]),"+f"(d[6]),"+f"(d[7]),"+f"(d[8]),"+f"(d[9]),"+f"(d[10]),"+f"(d[11]),"+f"(d[12]),"+f"(d[13]),"+f"(d[14]),"+f"(d[15]),"+f"(d[16]),"+f"(d[17]),"+f"(d[18]),"+f"(d[19]),"+f"(d[20]),"+f"(d[21]),"+f"(d[22]),"+f"(d[23]),"+f"(d[24]),"+f"(d[25]),"+f"(d[26]),"+f"(d[27]),"+f"(d[28]),"+f"(d[29]),"+f"(d[30]),"+f"(d[31]),"+f"(d[32]),"+f"(d[33]),"+f"(d[34]),"+f"(d[35]),"+f"(d[36]),"+f"(d[37]),"+f"(d[38]),"+f"(d[39]),"+f"(d[40]),"+f"(d[41]),"+f"(d[42]),"+f"(d[43]),"+f"(d[44]),"+f"(d[45]),"+f"(d[46]),"+f"(d[47]),"+f"(d[48]),"+f"(d[49]),"+f"(d[50]),"+f"(d[51]),"+f"(d[52]),"+f"(d[53]),"+f"(d[54]),"+f"(d[55]),"+f"(d[56]),"+f"(d[57]),"+f"(d[58]),"+f"(d[59]),"+f"(d[60]),"+f"(d[61]),"+f"(d[62]),"+f"(d[63]),"+f"(d[64]),"+f"(d[65]),"+f"(d[66]),"+f"(d[67]),"+f"(d[68]),"+f"(d[69]),"+f"(d[70]),"+f"(d[71]),"+f"(d[72]),"+f"(d[73]),"+f"(d[74]),"+f"(d[75]),"+f"(d[76]),"+f"(d[77]),"+f"(d[78]),"+f"(d[79]),"+f"(d[80]),"+f"(d[81]),"+f"(d[82]),"+f"(d[83]),"+f"(d[84]),"+f"(d[85]),"+f"(d[86]),"+f"(d[87]),"+f"(d[88]),"+f"(d[89]),"+f"(d[90]),"+f"(d[91])
    : "l"(da), "l"(db), "r"(acc));
}
__device__ __forceinline__ void mma_ss_224(float (&d)[112], uint64_t da, uint64_t db, int acc) {
  asm volatile("{.reg .pred p; setp.ne.b32 p, %114, 0;\n"
    "wgmma.mma_async.sync.aligned.m64n224k16.f32.bf16.bf16 {%0,%1,%2,%3,%4,%5,%6,%7,%8,%9,%10,%11,%12,%13,%14,%15,%16,%17,%18,%19,%20,%21,%22,%23,%24,%25,%26,%27,%28,%29,%30,%31,%32,%33,%34,%35,%36,%37,%38,%39,%40,%41,%42,%43,%44,%45,%46,%47,%48,%49,%50,%51,%52,%53,%54,%55,%56,%57,%58,%59,%60,%61,%62,%63,%64,%65,%66,%67,%68,%69,%70,%71,%72,%73,%74,%75,%76,%77,%78,%79,%80,%81,%82,%83,%84,%85,%86,%87,%88,%89,%90,%91,%92,%93,%94,%95,%96,%97,%98,%99,%100,%101,%102,%103,%104,%105,%106,%107,%108,%109,%110,%111}, %112, %113, p, 1, 1, 0, 1;}\n"
    : "+f"(d[0]),"+f"(d[1]),"+f"(d[2]),"+f"(d[3]),"+f"(d[4]),"+f"(d[5]),"+f"(d[6]),"+f"(d[7]),"+f"(d[8]),"+f"(d[9]),"+f"(d[10]),"+f"(d[11]),"+f"(d[12]),"+f"(d[13]),"+f"(d[14]),"+f"(d[15]),"+f"(d[16]),"+f"(d[17]),"+f"(d[18]),"+f"(d[19]),"+f"(d[20]),"+f"(d[21]),"+f"(d[22]),"+f"(d[23]),"+f"(d[24]),"+f"(d[25]),"+f"(d[26]),"+f"(d[27]),"+f"(d[28]),"+f"(d[29]),"+f"(d[30]),"+f"(d[31]),"+f"(d[32]),"+f"(d[33]),"+f"(d[34]),"+f"(d[35]),"+f"(d[36]),"+f"(d[37]),"+f"(d[38]),"+f"(d[39]),"+f"(d[40]),"+f"(d[41]),"+f"(d[42]),"+f"(d[43]),"+f"(d[44]),"+f"(d[45]),"+f"(d[46]),"+f"(d[47]),"+f"(d[48]),"+f"(d[49]),"+f"(d[50]),"+f"(d[51]),"+f"(d[52]),"+f"(d[53]),"+f"(d[54]),"+f"(d[55]),"+f"(d[56]),"+f"(d[57]),"+f"(d[58]),"+f"(d[59]),"+f"(d[60]),"+f"(d[61]),"+f"(d[62]),"+f"(d[63]),"+f"(d[64]),"+f"(d[65]),"+f"(d[66]),"+f"(d[67]),"+f"(d[68]),"+f"(d[69]),"+f"(d[70]),"+f"(d[71]),"+f"(d[72]),"+f"(d[73]),"+f"(d[74]),"+f"(d[75]),"+f"(d[76]),"+f"(d[77]),"+f"(d[78]),"+f"(d[79]),"+f"(d[80]),"+f"(d[81]),"+f"(d[82]),"+f"(d[83]),"+f"(d[84]),"+f"(d[85]),"+f"(d[86]),"+f"(d[87]),"+f"(d[88]),"+f"(d[89]),"+f"(d[90]),"+f"(d[91]),"+f"(d[92]),"+f"(d[93]),"+f"(d[94]),"+f"(d[95]),"+f"(d[96]),"+f"(d[97]),"+f"(d[98]),"+f"(d[99]),"+f"(d[100]),"+f"(d[101]),"+f"(d[102]),"+f"(d[103]),"+f"(d[104]),"+f"(d[105]),"+f"(d[106]),"+f"(d[107]),"+f"(d[108]),"+f"(d[109]),"+f"(d[110]),"+f"(d[111])
    : "l"(da), "l"(db), "r"(acc));
}
__device__ __forceinline__ void mma_ss_56(float (&d)[28], uint64_t da, uint64_t db, int acc) {
  asm volatile("{.reg .pred p; setp.ne.b32 p, %30, 0;\n"
    "wgmma.mma_async.sync.aligned.m64n56k16.f32.bf16.bf16 {%0,%1,%2,%3,%4,%5,%6,%7,%8,%9,%10,%11,%12,%13,%14,%15,%16,%17,%18,%19,%20,%21,%22,%23,%24,%25,%26,%27}, %28, %29, p, 1, 1, 0, 1;}\n"
    : "+f"(d[0]),"+f"(d[1]),"+f"(d[2]),"+f"(d[3]),"+f"(d[4]),"+f"(d[5]),"+f"(d[6]),"+f"(d[7]),"+f"(d[8]),"+f"(d[9]),"+f"(d[10]),"+f"(d[11]),"+f"(d[12]),"+f"(d[13]),"+f"(d[14]),"+f"(d[15]),"+f"(d[16]),"+f"(d[17]),"+f"(d[18]),"+f"(d[19]),"+f"(d[20]),"+f"(d[21]),"+f"(d[22]),"+f"(d[23]),"+f"(d[24]),"+f"(d[25]),"+f"(d[26]),"+f"(d[27])
    : "l"(da), "l"(db), "r"(acc));
}
__device__ __forceinline__ void mma_rs_56(float (&d)[28], uint32_t a0, uint32_t a1, uint32_t a2, uint32_t a3, uint64_t db, int acc) {
  asm volatile("{.reg .pred p; setp.ne.b32 p, %33, 0;\n"
    "wgmma.mma_async.sync.aligned.m64n56k16.f32.bf16.bf16 {%0,%1,%2,%3,%4,%5,%6,%7,%8,%9,%10,%11,%12,%13,%14,%15,%16,%17,%18,%19,%20,%21,%22,%23,%24,%25,%26,%27}, {%28,%29,%30,%31}, %32, p, 1, 1, 1;}\n"
    : "+f"(d[0]),"+f"(d[1]),"+f"(d[2]),"+f"(d[3]),"+f"(d[4]),"+f"(d[5]),"+f"(d[6]),"+f"(d[7]),"+f"(d[8]),"+f"(d[9]),"+f"(d[10]),"+f"(d[11]),"+f"(d[12]),"+f"(d[13]),"+f"(d[14]),"+f"(d[15]),"+f"(d[16]),"+f"(d[17]),"+f"(d[18]),"+f"(d[19]),"+f"(d[20]),"+f"(d[21]),"+f"(d[22]),"+f"(d[23]),"+f"(d[24]),"+f"(d[25]),"+f"(d[26]),"+f"(d[27])
    : "r"(a0), "r"(a1), "r"(a2), "r"(a3), "l"(db), "r"(acc));
}
__device__ __forceinline__ void mma_ss_64t(float (&d)[32], uint64_t da, uint64_t db, int acc) {
  asm volatile("{.reg .pred p; setp.ne.b32 p, %34, 0;\n"
    "wgmma.mma_async.sync.aligned.m64n64k16.f32.bf16.bf16 {%0,%1,%2,%3,%4,%5,%6,%7,%8,%9,%10,%11,%12,%13,%14,%15,%16,%17,%18,%19,%20,%21,%22,%23,%24,%25,%26,%27,%28,%29,%30,%31}, %32, %33, p, 1, 1, 1, 1;}\n"
    : "+f"(d[0]),"+f"(d[1]),"+f"(d[2]),"+f"(d[3]),"+f"(d[4]),"+f"(d[5]),"+f"(d[6]),"+f"(d[7]),"+f"(d[8]),"+f"(d[9]),"+f"(d[10]),"+f"(d[11]),"+f"(d[12]),"+f"(d[13]),"+f"(d[14]),"+f"(d[15]),"+f"(d[16]),"+f"(d[17]),"+f"(d[18]),"+f"(d[19]),"+f"(d[20]),"+f"(d[21]),"+f"(d[22]),"+f"(d[23]),"+f"(d[24]),"+f"(d[25]),"+f"(d[26]),"+f"(d[27]),"+f"(d[28]),"+f"(d[29]),"+f"(d[30]),"+f"(d[31])
    : "l"(da), "l"(db), "r"(acc));
}
__device__ __forceinline__ void mma_rs_64(float (&d)[32], uint32_t a0, uint32_t a1, uint32_t a2, uint32_t a3, uint64_t db, int acc) {
  asm volatile("{.reg .pred p; setp.ne.b32 p, %37, 0;\n"
    "wgmma.mma_async.sync.aligned.m64n64k16.f32.bf16.bf16 {%0,%1,%2,%3,%4,%5,%6,%7,%8,%9,%10,%11,%12,%13,%14,%15,%16,%17,%18,%19,%20,%21,%22,%23,%24,%25,%26,%27,%28,%29,%30,%31}, {%32,%33,%34,%35}, %36, p, 1, 1, 1;}\n"
    : "+f"(d[0]),"+f"(d[1]),"+f"(d[2]),"+f"(d[3]),"+f"(d[4]),"+f"(d[5]),"+f"(d[6]),"+f"(d[7]),"+f"(d[8]),"+f"(d[9]),"+f"(d[10]),"+f"(d[11]),"+f"(d[12]),"+f"(d[13]),"+f"(d[14]),"+f"(d[15]),"+f"(d[16]),"+f"(d[17]),"+f"(d[18]),"+f"(d[19]),"+f"(d[20]),"+f"(d[21]),"+f"(d[22]),"+f"(d[23]),"+f"(d[24]),"+f"(d[25]),"+f"(d[26]),"+f"(d[27]),"+f"(d[28]),"+f"(d[29]),"+f"(d[30]),"+f"(d[31])
    : "r"(a0), "r"(a1), "r"(a2), "r"(a3), "l"(db), "r"(acc));
}

__device__ __forceinline__ void dual_softmax(const float (&p)[28], uint32_t (&phi)[4][7]) {
  constexpr float L2E = 1.4426950408889634f;
#pragma unroll
  for (int i = 0; i < 4; i++) {
    float mx = p[i], mn = p[i];
#pragma unroll
    for (int j = 1; j < 7; j++) { mx = fmaxf(mx, p[4 * j + i]); mn = fminf(mn, p[4 * j + i]); }
    mx = fmaxf(mx, __shfl_xor_sync(~0u, mx, 1)); mn = fminf(mn, __shfl_xor_sync(~0u, mn, 1));
    mx = fmaxf(mx, __shfl_xor_sync(~0u, mx, 2)); mn = fminf(mn, __shfl_xor_sync(~0u, mn, 2));
    float a[7], b[7], sa = 0.f, sb = 0.f;
    const float mxl = mx * L2E, mnl = mn * L2E;
#pragma unroll
    for (int j = 0; j < 7; j++) {
      a[j] = ex2(fmaf(p[4 * j + i], L2E, -mxl)); b[j] = ex2(fmaf(p[4 * j + i], -L2E, mnl));
      sa += a[j]; sb += b[j];
    }
    sa += __shfl_xor_sync(~0u, sa, 1); sb += __shfl_xor_sync(~0u, sb, 1);
    sa += __shfl_xor_sync(~0u, sa, 2); sb += __shfl_xor_sync(~0u, sb, 2);
    const float ra = __fdividef(1.f, sa), rb = __fdividef(1.f, sb);
#pragma unroll
    for (int j = 0; j < 7; j++) phi[i][j] = pack(a[j] * ra, b[j] * rb);
  }
}

struct Ring {
  uint32_t full, empty, base; int slot, par;
  __device__ __forceinline__ uint32_t acquire() { mbar_wait(full + slot * 8, par); return base + slot * SLOT; }
  __device__ __forceinline__ int advance() { int s = slot; if (++slot == NSLOT) { slot = 0; par ^= 1; } return s; }
  __device__ __forceinline__ void release(int s, bool elect) { if (elect) mbar_arrive(empty + s * 8); }
};
constexpr int FL_KV = 448, FL_CS = FL_KV + 16, FL_DONE = FL_KV + 32, FL_XS = FL_KV + 33;

__global__ void __launch_bounds__(384, 1)
fused_kernel(const __grid_constant__ CUtensorMap mQKV, const __grid_constant__ CUtensorMap mWO,
             const __grid_constant__ CUtensorMap mW1, const __grid_constant__ CUtensorMap mW2,
             const __grid_constant__ CUtensorMap mX,
             const __nv_bfloat16* __restrict__ x, const __nv_bfloat16* __restrict__ wphi,
             const __nv_bfloat16* __restrict__ b1, const __nv_bfloat16* __restrict__ b2,
             const __nv_bfloat16* __restrict__ wqkv, const __nv_bfloat16* __restrict__ wo, const __nv_bfloat16* __restrict__ w1,
             const __nv_bfloat16* __restrict__ w2, __nv_bfloat16* __restrict__ out) {
  extern __shared__ unsigned char smem_raw[];
  const uint32_t sb = (smem_u32(smem_raw) + 1023) & ~1023u;
  unsigned char* sg = smem_raw + (sb - smem_u32(smem_raw));
  const int tid = threadIdx.x, lane = tid & 31;
  const int G = blockIdx.x >> 3, r = blockIdx.x & 7;
  const uint32_t barFull = sb + OFF_BAR, barEmpty = barFull + 56, barA = barEmpty + 56, barCS = barA + 112;
  if (tid >= 256 && tid < 288) {
    if (lane < 30) mbar_init(barFull + lane * 8, lane >= 28 ? 96 : (lane >= 7 && lane < 14 ? 2 : 1));
    asm volatile("fence.mbarrier_init.release.cluster;" ::: "memory");
  } else if (tid == 288) {
    asm volatile("prefetch.tensormap [%0];" ::"l"(&mX) : "memory");
    asm volatile("prefetch.tensormap [%0];" ::"l"(&mQKV) : "memory");
  }
  __syncthreads();
  const int wgid = __shfl_sync(~0u, tid >> 7, 0);
  if (wgid == 2) {
    asm volatile("setmaxnreg.dec.sync.aligned.u32 56;");
    if (tid < 288) {
    if (lane < 14) {
        const int k = lane >> 1, cc = lane & 1;
        mbar_expect(barA + (cc * 7 + k) * 8, 8192);
        tma2(sb + (cc * 7 + k) * 8192, &mX, 64 * k, G * 128 + 64 * cc, barA + (cc * 7 + k) * 8);
      } else if (lane < 21) {
        const int i = lane - 14;
        mbar_expect(barFull + i * 8, 12288);
        tma3(sb + OFF_RING + i * SLOT, &mQKV, 56 * r, 32 * i, 0, barFull + i * 8);
      }
    }
    if (tid == 256) {
      int slot = 0, par = 0;
      for (int it = NSLOT; it < 2 * TILES_PER_LAYER; it++) {
        const int i = it >= TILES_PER_LAYER ? it - TILES_PER_LAYER : it;
        mbar_wait(barEmpty + slot * 8, par);
        const uint32_t dst = sb + OFF_RING + slot * SLOT, fb = barFull + slot * 8;
        mbar_expect(fb, i < 14 ? 12288 : SLOT);
        if (i < 14) tma3(dst, &mQKV, 56 * r, 32 * i, 0, fb);
        else if (i < 18) tma2(dst, &mWO, 56 * r, 112 * (i - 14), fb);
        else if (i < 32) tma3(dst, &mW1, 0, 32 * (i - 18), 7 * r, fb);
        else tma2(dst, &mW2, 64 * ((i - 32) >> 1), 224 * r + 112 * (i & 1), fb);
        if (++slot == NSLOT) { slot = 0; par ^= 1; }
      }
    } else if (tid >= 288) {
      unsigned ep;
      asm volatile("ld.relaxed.gpu.global.u32 %0, [%1];" : "=r"(ep) : "l"(gFlag + FL_DONE * 32) : "memory");
      const int idx = tid - 288;
#pragma unroll 1
      for (int ps = 0; ps < 3; ps++) {
        const int nch = ps ? 14 : 21, ch = min(idx >> 2, nch - 1), p = ch / 7, k0 = G * 28 + (idx & 3) * 7;
        const uint4* src = ps ? reinterpret_cast<const uint4*>(w1 + (size_t)k0 * 1792 + 224 * r) + (ps - 1) * 14 + ch
                              : reinterpret_cast<const uint4*>(wqkv + (size_t)k0 * 1344 + p * 448 + 56 * r) + (ch - 7 * p);
        uint4 cu[7];
#pragma unroll
        for (int i = 0; i < 7; i++) cu[i] = __ldg(src + i * (ps ? 224 : 168));
        float s[8] = {};
#pragma unroll
        for (int i = 0; i < 7; i++) { s[0] += lo(cu[i].x); s[1] += hi(cu[i].x); s[2] += lo(cu[i].y); s[3] += hi(cu[i].y); s[4] += lo(cu[i].z); s[5] += hi(cu[i].z); s[6] += lo(cu[i].w); s[7] += hi(cu[i].w); }
#pragma unroll
        for (int i = 0; i < 8; i++) { s[i] += __shfl_xor_sync(~0u, s[i], 1); s[i] += __shfl_xor_sync(~0u, s[i], 2); }
        if ((idx & 3) < 2 && idx < nch * 4)
          gCS[(r * 16 + G) * 104 + (ps ? 10 + ps * 14 + ch : ch + p) * 2 + (idx & 1)] = (idx & 1) ? make_float4(s[4], s[5], s[6], s[7]) : make_float4(s[0], s[1], s[2], s[3]);
        if (ps == 0 && G == 0) {
#pragma unroll 1
          for (int i = idx; i < 2 * 1280; i += 96) gKV[((i >= 1280) * 7 + r) * 1280 + i] = make_float4(0.f, 0.f, 0.f, 0.f);
        }
        if (ps == 1) continue;
        unsigned* f = gFlag + (FL_CS + (ps >> 1) * 8 + r) * 32;
        if (ps == 0) bar_sync<4, 352>(); else __syncwarp();
        if (lane == 0) {
          flag_arrive(f);
          if (ps == 0) { asm volatile("red.relaxed.gpu.global.add.u32 [%0], 1;" ::"l"(gFlag + (FL_XS + G) * 32) : "memory"); flag_wait(gFlag + (FL_XS + G) * 32, (ep / NCTA + 1) * 24); }
          flag_wait(f, (ep / NCTA + 1) * 48);
        }
        __syncwarp();
        if (ps == 0) {
#pragma unroll 1
          for (int j = idx; j < 128; j += 96) {
            float4 v[4];
#pragma unroll
            for (int i = 0; i < 4; i++) v[i] = __ldcg(reinterpret_cast<const float4*>(gStat + (size_t)(2048 + G * 128 + j) * 8) + i);
            float m = 0.f, q = 0.f;
#pragma unroll
            for (int i = 0; i < 4; i++) m += v[i].x + v[i].z;
            m *= 0.125f;
#pragma unroll
            for (int i = 0; i < 4; i++) q += v[i].y + v[i].w + 56.f * ((v[i].x - m) * (v[i].x - m) + (v[i].z - m) * (v[i].z - m));
            reinterpret_cast<float2*>(sg + OFF_ST)[j] = make_float2(m, rsqrtf(q * (1.f / DM) + 1e-5f));
          }
        }
#pragma unroll 1
        for (int j = idx + ps * 48; j < (ps ? 208 : 96); j += 96) {
          float2 v[16], a = make_float2(0.f, 0.f);
#pragma unroll
          for (int i = 0; i < 16; i++) v[i] = __ldcg(reinterpret_cast<const float2*>(gCS + (r * 16 + i) * 104) + j);
#pragma unroll
          for (int i = 0; i < 16; i++) { a.x += v[i].x; a.y += v[i].y; }
          reinterpret_cast<float2*>(sg + OFF_CS)[j] = a;
        }
        mbar_arrive(barCS + (ps >> 1) * 8);
        if (ps == 0 && idx < 2) {
          const char* pf = idx ? (const char*)w2 + blockIdx.x * 12544 : (const char*)wo + blockIdx.x * 3136;
          asm volatile("cp.async.bulk.prefetch.L2.global [%0], %1;" ::"l"(pf), "r"(idx ? 12544 : 3136) : "memory");
        }
      }
    }
  } else {
  asm volatile("setmaxnreg.inc.sync.aligned.u32 224;");
  const int c = wgid, w = (tid >> 5) & 3, g = lane >> 2, t = lane & 3;
  const bool elect = (tid & 127) == 0;
  const uint32_t abuf = sb + c * ABYTES, barAc = barA + c * 56;
  const int row0 = G * 128 + c * 64;
  unsigned epoch;
  asm volatile("ld.relaxed.gpu.global.u32 %0, [%1];" : "=r"(epoch) : "l"(gFlag + FL_DONE * 32) : "memory");
  STAMP(24);
  float mean[2], rstd[2];
  uint32_t wv[7];
#pragma unroll
  for (int i = 0; i < 7; i++)
    wv[i] = __ldg(reinterpret_cast<const unsigned short*>(wphi) + (56 * r + i * 8 + (tid >> 5)) * 28 + min(lane, 27));
  const uint32_t bv = __ldg(reinterpret_cast<const unsigned short*>(b1) + 224 * r + min(tid, 223));
  if (w < 2) {
    const int row = row0 + r * 8 + ((tid & 63) >> 3);
    uint4 v[7];
#pragma unroll
    for (int k = 0; k < 7; k++) v[k] = __ldg(reinterpret_cast<const uint4*>(x + (size_t)row * DM) + (lane & 7) * 7 + k);
    float sm = 0.f, q = 0.f;
#pragma unroll
    for (int k = 0; k < 7; k++) sm += (lo(v[k].x) + hi(v[k].x)) + (lo(v[k].y) + hi(v[k].y)) + (lo(v[k].z) + hi(v[k].z)) + (lo(v[k].w) + hi(v[k].w));
    sm *= 1.f / 56.f;
#pragma unroll
    for (int k = 0; k < 7; k++) {
      const uint32_t e[4] = {v[k].x, v[k].y, v[k].z, v[k].w};
#pragma unroll
      for (int z = 0; z < 4; z++) { const float a = lo(e[z]) - sm, b = hi(e[z]) - sm; q = fmaf(a, a, fmaf(b, b, q)); }
    }
    gStat[(size_t)(2048 + row) * 8 + (lane & 7)] = make_float2(sm, q);
  }
  asm volatile("bar.arrive 4, 352;" ::: "memory");
  STAMP(0);
  Ring ring{barFull, barEmpty, sb + OFF_RING, 0, 0};
  int apar = 0;
  const uint32_t stsm_off = (w * 16 + ((lane >> 3) & 1) * 8 + (lane & 7)) * 128;
  const uint32_t stsm_hi = lane >> 4;
  const uint64_t dA = mkdesc(abuf, 1024, 128, 0);

  auto gather = [&](unsigned* fl, const unsigned char* img) {
    __syncwarp();
    if (lane == 0) flag_arrive(fl);
    if (w == 0) {
      STAMP(27);
      if (lane == 0) flag_wait(fl, epoch * 32);
      __syncwarp();
      STAMP(28);
      if (lane < 7) { fence_async(); mbar_expect(barAc + lane * 8, 8192); bulk_ld(abuf + lane * 8192, img + lane * 8192, 8192, barAc + lane * 8); }
    }
    __syncwarp();
    apar ^= 1;
  };
  auto slice_off = [&](int j, int hh) -> uint32_t {
    return (7 * r + j) * 1024 + (w * 2 + hh) * 128 + lane * 4;
  };
  uint4 su[2] = {};
  auto load_stats = [&](const float2* st) {
    mbar_wait(barAc, apar);
#pragma unroll
    for (int hh = 0; hh < 2; hh++) su[hh] = ldcg4(st + (size_t)(row0 + w * 16 + hh * 8 + g) * 8 + 2 * t);
  };
  auto finish_stats = [&]() {
#pragma unroll
    for (int hh = 0; hh < 2; hh++) {
      const float m0 = __uint_as_float(su[hh].x), m1 = __uint_as_float(su[hh].z);
      float m = m0 + m1;
      m += __shfl_xor_sync(~0u, m, 1); m += __shfl_xor_sync(~0u, m, 2);
      m *= 0.125f;
      float q = __uint_as_float(su[hh].y) + __uint_as_float(su[hh].w) + 56.f * ((m0 - m) * (m0 - m) + (m1 - m) * (m1 - m));
      q += __shfl_xor_sync(~0u, q, 1); q += __shfl_xor_sync(~0u, q, 2);
      mean[hh] = m; rstd[hh] = rsqrtf(q * (1.f / DM) + 1e-5f);
    }
  };

#pragma unroll 1
  for (int layer = 0; layer < 2; layer++) {
    unsigned* const fl = gFlag + (layer * 32 + G * 2 + c) * 7 * 32;
    uint32_t phiq[4][7], xs[7][2];
    {
      float acc[92]; reg_def(acc);
      const uint64_t dQ = layer ? dA : mkdesc(abuf, 16, 1024, 1);
      const int kstep = layer ? 128 : 2;
      int prev = 0;
      if (layer) load_stats(gStat + 2048 * 8);
#pragma unroll 1
      for (int st = 0; st < 14; st++) {
        if (!(st & 1)) mbar_wait(barAc + (st >> 1) * 8, apar);
        const uint64_t da = dQ + (st >> 1) * 512 + (st & 1) * 2 * kstep, db = mkdesc(ring.acquire(), 4096, 1024, 1);
        wg_fence();
        mma_ss_184(acc, da, db, st);
        mma_ss_184(acc, da + kstep, db + 128, 1);
        wg_commit();
        if (st > 0) { wg_wait<1>(); ring.release(prev, elect); }
        prev = ring.advance();
      }
      if (layer == 0) {
#pragma unroll
        for (int i = 0; i < 8; i++) {
          const int k = i * 8 + (tid >> 5);
          *reinterpret_cast<uint32_t*>(sg + OFF_WPHI + k * 128 + ((g ^ (k & 7)) << 4) + t * 4) = (i < 7 && lane < 28) ? wv[i % 7] << (k >= 28 ? 16 : 0) : 0u;
        }
        if (tid < 224) reinterpret_cast<uint32_t*>(sg + OFF_B1)[tid] = bv << 16;
        fence_async_smem();
        bar_sync<3, 256>();
        epoch = epoch / NCTA + 1;
        STAMP(25);
        mbar_wait(barCS, 0);
#pragma unroll
        for (int hh = 0; hh < 2; hh++) { const float2 v = reinterpret_cast<const float2*>(sg + OFF_ST)[c * 64 + w * 16 + hh * 8 + g]; mean[hh] = v.x; rstd[hh] = v.y; }
      } else {
        finish_stats();
      }
#pragma unroll
      for (int j = 0; j < 7; j++) {
        const int ci = 7 * r + j;
        const uint32_t a = abuf + (layer ? slice_off(j, 0) : (ci >> 3) * 8192 + (w * 16 + g) * 128 + (((ci & 7) ^ g) << 4) + t * 4);
        xs[j][0] = lds32(a); xs[j][1] = lds32(a + (layer ? 128 : 1024));
      }
      wg_wait<0>(); reg_fence(acc);
      ring.release(prev, elect);
      STAMP(1 + layer * 12);
      uint32_t f[3][14];
      {
        const float2* cs = reinterpret_cast<const float2*>(sg + OFF_CS) + t;
        const float mr0 = -mean[0] * rstd[0], mr1 = -mean[1] * rstd[1];
#pragma unroll
        for (int p = 0; p < 3; p++)
#pragma unroll
          for (int j = 0; j < 7; j++) {
            const float2 s = cs[p * 32 + j * 4];
            const int b = p * 32 + j * 4;
            f[p][2 * j] = pack(fmaf(acc[b], rstd[0], s.x * mr0), fmaf(acc[b + 1], rstd[0], s.y * mr0));
            f[p][2 * j + 1] = pack(fmaf(acc[b + 2], rstd[1], s.x * mr1), fmaf(acc[b + 3], rstd[1], s.y * mr1));
          }
      }
      float pk[28], pq[28]; reg_def(pk); reg_def(pq);
      const uint64_t dW = mkdesc(sb + OFF_WPHI, 4096, 1024, 1);
      wg_fence();
#pragma unroll
      for (int s = 0; s < 4; s++)
        mma_rs_56(pk, f[1][4 * s], f[1][4 * s + 1], s < 3 ? f[1][(4 * s + 2) % 14] : 0u, s < 3 ? f[1][(4 * s + 3) % 14] : 0u, dW + s * 128, s);
      wg_commit();
#pragma unroll
      for (int s = 0; s < 4; s++)
        mma_rs_56(pq, f[0][4 * s], f[0][4 * s + 1], s < 3 ? f[0][(4 * s + 2) % 14] : 0u, s < 3 ? f[0][(4 * s + 3) % 14] : 0u, dW + s * 128, s);
      wg_commit();
      bar_wg(c);
      const uint32_t srow = abuf + stsm_off, ones = t == 0 ? 0x3F803F80u : 0u;
#pragma unroll
      for (int jp = 0; jp < 4; jp++)
        stsm4(srow + 16384 + (((2 * jp + stsm_hi) ^ (lane & 7)) << 4), f[2][4 * jp], f[2][4 * jp + 1],
              jp < 3 ? f[2][(4 * jp + 2) % 14] : ones, jp < 3 ? f[2][(4 * jp + 3) % 14] : ones);
      wg_wait<0>(); reg_fence(pk); reg_fence(pq);
#pragma unroll 1
      for (int pass = 0; pass < 2; pass++) {
        dual_softmax(pk, phiq);
        if (pass) break;
#pragma unroll
        for (int e = 0; e < 2; e++)
#pragma unroll
          for (int jp = 0; jp < 4; jp++)
            stsm4(srow + e * 8192 + (((2 * jp + stsm_hi) ^ (lane & 7)) << 4), phiq[e][2 * jp], phiq[2 + e][2 * jp],
                  jp < 3 ? phiq[e][(2 * jp + 1) % 7] : 0u, jp < 3 ? phiq[2 + e][(2 * jp + 1) % 7] : 0u);
        fence_async_smem();
        bar_sync<3, 256>();
        float kv[32]; reg_def(kv);
        const uint64_t dP = mkdesc(sb + c * 8192, 4096, 1024, 1), dV = mkdesc(sb + 16384, 4096, 1024, 1);
        wg_fence();
#pragma unroll
        for (int s = 0; s < 8; s++) mma_ss_64t(kv, dP + (s >> 2) * (ABYTES / 16) + (s & 3) * 128, dV + (s >> 2) * (ABYTES / 16) + (s & 3) * 128, s);
        wg_commit();
        wg_wait<0>(); reg_fence(kv);
        float4* kvg = gKV + ((layer * 8 + r) * 2 + c) * 640 + (tid & 127);
#pragma unroll
        for (int i = 0; i < 5; i++) {
          float v0, v1, v2, v3;
          if (i == 4) { v0 = kv[28]; v1 = kv[29]; v2 = kv[30]; v3 = kv[31]; }
          else { v0 = c ? kv[12 + 4 * i] : kv[4 * i]; v1 = c ? kv[13 + 4 * i] : kv[1 + 4 * i]; v2 = c ? kv[14 + 4 * i] : kv[2 + 4 * i]; v3 = c ? kv[15 + 4 * i] : kv[3 + 4 * i]; }
          const bool use = i == 4 ? t == 0 : (i == 0 ? (c == 0 || t >= 2) : (i == 3 ? (c == 1 || t < 2) : true));
          if (use) asm volatile("red.relaxed.gpu.global.add.v4.f32 [%0], {%1,%2,%3,%4};" ::"l"(kvg + i * 128), "f"(v0), "f"(v1), "f"(v2), "f"(v3) : "memory");
        }
        __syncwarp();
        if (lane == 0) flag_arrive(gFlag + (FL_KV + layer * 8 + r) * 32);
        __syncwarp();
        STAMP(2 + layer * 12);
#pragma unroll
        for (int i = 0; i < 28; i++) pk[i] = pq[i];
      }
    }
    {
      if (elect) flag_wait(gFlag + (FL_KV + layer * 8 + r) * 32, epoch * 128);
      bar_wg(c);
      STAMP(3 + layer * 12);
      const float4* kvg = gKV + (layer * 8 + r) * 1280 + (tid & 127);
      uint4 kk[2][5];
#pragma unroll
      for (int e = 0; e < 2; e++)
#pragma unroll
        for (int i = 0; i < 5; i++) kk[e][i] = ldcg4(kvg + e * 640 + i * 128);
      const uint32_t srow = abuf + 24576 + stsm_off;
#pragma unroll
      for (int e = 0; e < 2; e++) {
        uint32_t f[8][2];
#pragma unroll
        for (int j = 0; j < 8; j++) { f[j][0] = 0u; f[j][1] = 0u; }
#pragma unroll
        for (int i = 0; i < 4; i++) {
          f[i + 3 * e][0] = pack(__uint_as_float(kk[e][i].x), __uint_as_float(kk[e][i].y));
          f[i + 3 * e][1] = pack(__uint_as_float(kk[e][i].z), __uint_as_float(kk[e][i].w));
        }
        f[7][0] = e ? pack(0.f, __uint_as_float(kk[e][4].y)) : pack(__uint_as_float(kk[e][4].x), 0.f);
        f[7][1] = e ? pack(0.f, __uint_as_float(kk[e][4].w)) : pack(__uint_as_float(kk[e][4].z), 0.f);
#pragma unroll
        for (int jp = 0; jp < 4; jp++)
          stsm4(srow + e * 8192 + (((2 * jp + stsm_hi) ^ (lane & 7)) << 4), f[2 * jp][0], f[2 * jp][1], f[2 * jp + 1][0], f[2 * jp + 1][1]);
      }
      fence_async_smem();
      bar_wg(c);
      float num[32]; reg_def(num);
      const uint64_t dK = mkdesc(abuf + 24576, 4096, 1024, 1);
      wg_fence();
#pragma unroll
      for (int e = 0; e < 2; e++)
#pragma unroll
        for (int s = 0; s < 4; s++)
          mma_rs_64(num, phiq[e][2 * s], phiq[2 + e][2 * s], s < 3 ? phiq[e][(2 * s + 1) % 7] : 0u, s < 3 ? phiq[2 + e][(2 * s + 1) % 7] : 0u,
                    dK + e * 512 + s * 128, e + s);
      wg_commit();
      wg_wait<0>(); reg_fence(num);
      float rd[4];
#pragma unroll
      for (int i = 0; i < 4; i++) rd[i] = __fdividef(1.f, __shfl_sync(~0u, num[28 + i], lane & ~3) + 1e-6f);
      unsigned char* img = gImg + (size_t)(G * 2 + c) * ABYTES;
#pragma unroll
      for (int j = 0; j < 7; j++) {
        const bool hb = j > 3 || (j == 3 && t >= 2);
        const float r0 = hb ? rd[1] : rd[0], r1 = hb ? rd[3] : rd[2];
        *reinterpret_cast<uint32_t*>(img + slice_off(j, 0)) = pack(num[4 * j] * r0, num[4 * j + 1] * r0);
        *reinterpret_cast<uint32_t*>(img + slice_off(j, 1)) = pack(num[4 * j + 2] * r1, num[4 * j + 3] * r1);
      }
      STAMP(4 + layer * 12);
      gather(fl, img);
      STAMP(5 + layer * 12);
    }
    {
      float acc[28]; reg_def(acc);
      int prev = 0;
#pragma unroll 1
      for (int st = 0; st < 4; st++) {
        mbar_wait(barAc + (st * 7 + 3) / 4 * 8, apar);
        mbar_wait(barAc + (st * 7 + 6) / 4 * 8, apar);
        const uint64_t db = mkdesc(ring.acquire(), 4096, 1024, 1);
        wg_fence();
#pragma unroll
        for (int s = 0; s < 7; s++) { const int ks = st * 7 + s; mma_ss_56(acc, dA + ks * 128, db + s * 128, ks); }
        wg_commit();
        if (st > 0) { wg_wait<1>(); ring.release(prev, elect); }
        prev = ring.advance();
      }
      wg_wait<0>(); reg_fence(acc);
      ring.release(prev, elect);
      unsigned char* img = gImg + (size_t)(32 + G * 2 + c) * ABYTES;
#pragma unroll
      for (int hh = 0; hh < 2; hh++) {
        float s = 0.f, q = 0.f;
#pragma unroll
        for (int j = 0; j < 7; j++) {
          xs[j][hh] = pack(lo(xs[j][hh]) + acc[4 * j + 2 * hh], hi(xs[j][hh]) + acc[4 * j + 2 * hh + 1]);
          *reinterpret_cast<uint32_t*>(img + slice_off(j, hh)) = xs[j][hh];
          s += lo(xs[j][hh]) + hi(xs[j][hh]);
        }
        s += __shfl_xor_sync(~0u, s, 1); s += __shfl_xor_sync(~0u, s, 2);
        s *= 1.f / 56.f;
#pragma unroll
        for (int j = 0; j < 7; j++) { const float a = lo(xs[j][hh]) - s, b = hi(xs[j][hh]) - s; q = fmaf(a, a, q); q = fmaf(b, b, q); }
        q += __shfl_xor_sync(~0u, q, 1); q += __shfl_xor_sync(~0u, q, 2);
        if (t == 0) gStat[(size_t)(row0 + w * 16 + hh * 8 + g) * 8 + r] = make_float2(s, q);
      }
      STAMP(6 + layer * 12);
      gather(fl + 32, img);
      STAMP(7 + layer * 12);
    }
    {
      uint32_t hf[28][2];
      {
        float acc[112]; reg_def(acc);
        int prev = 0;
        load_stats(gStat);
#pragma unroll 1
        for (int st = 0; st < 14; st++) {
          if (!(st & 1)) mbar_wait(barAc + (st >> 1) * 8, apar);
          const uint64_t da = dA + st * 256, db = mkdesc(ring.acquire(), 2048, 512, 2);
          wg_fence();
          mma_ss_224(acc, da, db, st);
          mma_ss_224(acc, da + 128, db + 64, 1);
          wg_commit();
          if (st > 0) { wg_wait<1>(); ring.release(prev, elect); }
          prev = ring.advance();
        }
        finish_stats();
        mbar_wait(barCS + 8, 0);
        wg_wait<0>(); reg_fence(acc);
        ring.release(prev, elect);
        STAMP(8 + layer * 12);
        const float2* bs = reinterpret_cast<const float2*>(sg + OFF_B1) + t;
        const float2* cs = reinterpret_cast<const float2*>(sg + OFF_CS + 768) + t;
        const float mr0 = -mean[0] * rstd[0], mr1 = -mean[1] * rstd[1];
#pragma unroll
        for (int j = 0; j < 28; j++) {
          const float2 b = bs[4 * j], s = cs[4 * j];
          const float h0 = fmaxf(fmaf(acc[4 * j], rstd[0], fmaf(s.x, mr0, b.x)), 0.f), h1 = fmaxf(fmaf(acc[4 * j + 1], rstd[0], fmaf(s.y, mr0, b.y)), 0.f);
          const float h2 = fmaxf(fmaf(acc[4 * j + 2], rstd[1], fmaf(s.x, mr1, b.x)), 0.f), h3 = fmaxf(fmaf(acc[4 * j + 3], rstd[1], fmaf(s.y, mr1, b.y)), 0.f);
          hf[j][0] = pack(h0 * h0, h1 * h1); hf[j][1] = pack(h2 * h2, h3 * h3);
        }
      }
      unsigned char* pdst = gP + (size_t)(((G * 2 + c) * 8 + 2 * w) * 8 + r) * 7168 + lane * 8;
      uint2 pk[8] = {};
#pragma unroll 1
      for (int ch = 0; ch < 7; ch++) {
        float acc[32]; reg_def(acc);
        int sl0 = 0, sl1 = 0;
#pragma unroll
        for (int hk = 0; hk < 2; hk++) {
          const uint64_t db = mkdesc(ring.acquire(), 4096, 1024, 1);
          wg_fence();
#pragma unroll
          for (int s = 0; s < 7; s++) { const int ks = hk * 7 + s; mma_rs_64(acc, hf[2 * ks][0], hf[2 * ks][1], hf[2 * ks + 1][0], hf[2 * ks + 1][1], db + s * 128, ks); }
          wg_commit();
          if (hk) sl1 = ring.advance(); else sl0 = ring.advance();
        }
        if (ch > 0) {
#pragma unroll
          for (int i = 0; i < 8; i++) *reinterpret_cast<uint2*>(pdst + (i & 1) * (8 * 7168) + (i >> 1) * 256) = pk[i];
          pdst += 1024;
        }
        wg_wait<1>(); ring.release(sl0, elect);
        wg_wait<0>(); reg_fence(acc); ring.release(sl1, elect);
#pragma unroll
        for (int i = 0; i < 8; i++) {
          const int b = (i >> 1) * 8 + (i & 1) * 2;
          pk[i] = make_uint2(pack(acc[b], acc[b + 1]), pack(acc[b + 4], acc[b + 5]));
        }
      }
#pragma unroll
      for (int i = 0; i < 8; i++) *reinterpret_cast<uint2*>(pdst + (i & 1) * (8 * 7168) + (i >> 1) * 256) = pk[i];
      STAMP(9 + layer * 12);
    }
    {
      uint32_t bx[14];
#pragma unroll
      for (int j = 0; j < 14; j++) bx[j] = __ldg(reinterpret_cast<const uint32_t*>(b2 + w * 112 + j * 8 + 2 * t));
      __syncwarp();
      if (lane == 0) { flag_arrive(fl + (3 + w) * 32); flag_wait(fl + (3 + (r >> 1)) * 32, epoch * 8); }
      __syncwarp();
      STAMP(10 + layer * 12);
      const unsigned char* psrc = gP + (size_t)(((G * 2 + c) * 8 + r) * 8) * 7168 + w * 1792 + lane * 8;
      unsigned char* img = gImg + (size_t)(64 + G * 2 + c) * ABYTES;
      uint2 pv[8][7];
#pragma unroll
      for (int s = 0; s < 8; s++)
#pragma unroll
        for (int i = 0; i < 7; i++) pv[s][i] = ldcg2(psrc + s * 7168 + i * 256);
      const uint32_t off = w * 14336 + r * 128 + lane * 4;
      unsigned char* dst = layer ? reinterpret_cast<unsigned char*>(out + (size_t)(row0 + r * 8 + g) * DM + w * 112 + 2 * t) : img + off;
      float sm = 0.f, q = 0.f;
#pragma unroll
      for (int j = 0; j < 14; j++) {
        float y0 = lo(bx[j]), y1 = hi(bx[j]);
        const uint32_t xo = lds32(abuf + off + j * 1024);
        y0 += lo(xo); y1 += hi(xo);
#pragma unroll
        for (int s = 0; s < 8; s++) { const uint32_t u = (j & 1) ? pv[s][j >> 1].y : pv[s][j >> 1].x; y0 += lo(u); y1 += hi(u); }
        bx[j] = pack(y0, y1);
        *reinterpret_cast<uint32_t*>(dst + j * (layer ? 16 : 1024)) = bx[j];
        sm += lo(bx[j]) + hi(bx[j]);
      }
      if (layer) break;
      sm += __shfl_xor_sync(~0u, sm, 1); sm += __shfl_xor_sync(~0u, sm, 2);
      sm *= 1.f / 112.f;
#pragma unroll
      for (int j = 0; j < 14; j++) { const float a = lo(bx[j]) - sm, b = hi(bx[j]) - sm; q = fmaf(a, a, q); q = fmaf(b, b, q); }
      q += __shfl_xor_sync(~0u, q, 1); q += __shfl_xor_sync(~0u, q, 2);
      if (t < 2) gStat[(size_t)(2048 + row0 + r * 8 + g) * 8 + 2 * w + t] = make_float2(sm, q * 0.5f);
      STAMP(11);
      gather(fl + 64, img);
      STAMP(12);
    }
  }
  STAMP(30);
  if (tid == 0) asm volatile("red.relaxed.gpu.global.add.u32 [%0], 1;" ::"l"(gFlag + FL_DONE * 32) : "memory");
  }
}

typedef CUresult (*EncFn)(CUtensorMap*, CUtensorMapDataType, cuuint32_t, void*, const cuuint64_t*, const cuuint64_t*,
                          const cuuint32_t*, const cuuint32_t*, CUtensorMapInterleave, CUtensorMapSwizzle,
                          CUtensorMapL2promotion, CUtensorMapFloatOOBfill);

void make_map(EncFn enc, CUtensorMap* m, void* p, int rank, uint64_t d0, uint64_t d1, uint64_t d2, uint64_t s1, uint64_t s2,
              uint32_t b0, uint32_t b1, uint32_t b2, CUtensorMapSwizzle sw) {
  cuuint64_t dims[3] = {d0, d1, d2}, strides[2] = {s1, s2};
  cuuint32_t box[3] = {b0, b1, b2}, es[3] = {1, 1, 1};
  enc(m, CU_TENSOR_MAP_DATA_TYPE_BFLOAT16, rank, p, dims, strides, box, es, CU_TENSOR_MAP_INTERLEAVE_NONE, sw,
      CU_TENSOR_MAP_L2_PROMOTION_L2_128B, CU_TENSOR_MAP_FLOAT_OOB_FILL_NONE);
}

}

extern "C" void kernel_launch(void* const* d_in, const int* in_sizes, int n_in, void* d_out, int out_size) {
  static EncFn enc = nullptr;
  if (!enc) {
    cudaDriverEntryPointQueryResult st;
    void* fn = nullptr;
    cudaGetDriverEntryPoint("cuTensorMapEncodeTiled", &fn, cudaEnableDefault, &st);
    enc = (EncFn)fn;
    cudaFuncSetAttribute(fused_kernel, cudaFuncAttributeMaxDynamicSharedMemorySize, SMEM_BYTES);
  }
  CUtensorMap mQKV, mWO, mW1, mW2, mX;
  make_map(enc, &mQKV, d_in[1], 3, 448, 448, 3, 2688, 896, 64, 32, 3, CU_TENSOR_MAP_SWIZZLE_128B);
  make_map(enc, &mWO, d_in[3], 2, 448, 448, 1, 896, 0, 64, 112, 1, CU_TENSOR_MAP_SWIZZLE_128B);
  make_map(enc, &mW1, d_in[5], 3, 32, 448, 56, 3584, 64, 32, 32, 7, CU_TENSOR_MAP_SWIZZLE_64B);
  make_map(enc, &mW2, d_in[7], 2, 448, 1792, 1, 896, 0, 64, 112, 1, CU_TENSOR_MAP_SWIZZLE_128B);
  make_map(enc, &mX, d_in[0], 2, 448, 2048, 1, 896, 0, 64, 64, 1, CU_TENSOR_MAP_SWIZZLE_128B);
  fused_kernel<<<NCTA, 384, SMEM_BYTES, cudaStreamPerThread>>>(
      mQKV, mWO, mW1, mW2, mX, (const __nv_bfloat16*)d_in[0], (const __nv_bfloat16*)d_in[2], (const __nv_bfloat16*)d_in[6],
      (const __nv_bfloat16*)d_in[8], (const __nv_bfloat16*)d_in[1], (const __nv_bfloat16*)d_in[3], (const __nv_bfloat16*)d_in[5],
      (const __nv_bfloat16*)d_in[7], (__nv_bfloat16*)d_out);
}
```

```cpp
#include <cuda_runtime.h>
#include <cuda_bf16.h>
#include <cuda.h>
#include <stdint.h>

namespace {

constexpr int DM = 448, NCTA = 128;
constexpr int ABYTES = 57344;
constexpr int SLOT = 14336, NSLOT = 7;
constexpr int OFF_RING = 2 * ABYTES;
constexpr int OFF_WPHI = OFF_RING + NSLOT * SLOT;
constexpr int OFF_B1 = OFF_WPHI + 8192;
constexpr int OFF_CS = OFF_B1 + 896;
constexpr int OFF_BAR = OFF_CS + 1664;
constexpr int SMEM_BYTES = OFF_BAR + 256 + 1024;
constexpr int TILES_PER_LAYER = 46;

__device__ __align__(1024) unsigned char gP[16 * 2 * 8 * 8 * 7168];
__device__ __align__(1024) unsigned char gImg[3 * 32 * ABYTES];
__device__ __align__(1024) float2 gStat[2 * 2048 * 8];
__device__ __align__(1024) float4 gKV[2 * 8 * 2 * 5 * 128];
__device__ __align__(1024) float4 gCS[8 * 16 * 104];
__device__ __align__(128) unsigned gFlag[(2 * 32 * 7 + 32 + 1 + 16) * 32];
#define STAMP(i)

__device__ __forceinline__ uint32_t smem_u32(const void* p) { return (uint32_t)__cvta_generic_to_shared(p); }
__device__ __forceinline__ void mbar_init(uint32_t b, int c) { asm volatile("mbarrier.init.shared::cta.b64 [%0], %1;" ::"r"(b), "r"(c)); }
__device__ __forceinline__ void mbar_expect(uint32_t b, int bytes) { asm volatile("mbarrier.arrive.expect_tx.shared::cta.b64 _, [%0], %1;" ::"r"(b), "r"(bytes) : "memory"); }
__device__ __forceinline__ void mbar_arrive(uint32_t b) { asm volatile("mbarrier.arrive.shared::cta.b64 _, [%0];" ::"r"(b) : "memory"); }
__device__ __forceinline__ void mbar_wait(uint32_t b, int par) {
  uint32_t ok; int n = 0;
  while (true) {
    asm volatile("{.reg .pred p; mbarrier.try_wait.parity.shared::cta.b64 p, [%1], %2; selp.u32 %0,1,0,p;}" : "=r"(ok) : "r"(b), "r"(par) : "memory");
    if (ok) break;
    if (++n > (1 << 22)) break;
  }
}
__device__ __forceinline__ void flag_wait(const unsigned* f, unsigned target) {
  unsigned v; int n = 0;
  while (true) {
    asm volatile("ld.acquire.gpu.global.u32 %0, [%1];" : "=r"(v) : "l"(f) : "memory");
    if ((int)(v - target) >= 0) break;
    if (++n > (1 << 21)) break;
  }
}
__device__ __forceinline__ void flag_arrive(unsigned* f) { asm volatile("red.release.gpu.global.add.u32 [%0], 1;" ::"l"(f) : "memory"); }
__device__ __forceinline__ void fence_async() { asm volatile("fence.proxy.async.global;" ::: "memory"); }
__device__ __forceinline__ void fence_async_smem() { asm volatile("fence.proxy.async.shared::cta;" ::: "memory"); }
template <int ID, int N> __device__ __forceinline__ void bar_sync() { asm volatile("bar.sync %0, %1;" ::"n"(ID), "n"(N) : "memory"); }
__device__ __forceinline__ void bar_wg(int c) { if (c) bar_sync<2, 128>(); else bar_sync<1, 128>(); }
__device__ __forceinline__ void wg_fence() { asm volatile("wgmma.fence.sync.aligned;" ::: "memory"); }
__device__ __forceinline__ void wg_commit() { asm volatile("wgmma.commit_group.sync.aligned;" ::: "memory"); }
template <int N> __device__ __forceinline__ void wg_wait() { asm volatile("wgmma.wait_group.sync.aligned %0;" ::"n"(N) : "memory"); }
template <int N> __device__ __forceinline__ void reg_fence(float (&d)[N]) {
#pragma unroll
  for (int i = 0; i < N; i++) asm volatile("" : "+f"(d[i])::"memory");
}
template <int N> __device__ __forceinline__ void reg_def(float (&d)[N]) {
#pragma unroll
  for (int i = 0; i < N; i++) d[i] = 0.f;
}
__device__ __forceinline__ uint64_t mkdesc(uint32_t addr, uint32_t lbo, uint32_t sbo, uint64_t swz) {
  return (uint64_t)((addr & 0x3FFFF) >> 4) | ((uint64_t)(lbo >> 4) << 16) | ((uint64_t)(sbo >> 4) << 32) | (swz << 62);
}
__device__ __forceinline__ uint32_t pack(float a, float b) {
  uint32_t r; asm("cvt.rn.bf16x2.f32 %0, %1, %2;" : "=r"(r) : "f"(b), "f"(a)); return r;
}
__device__ __forceinline__ float lo(uint32_t u) { return __uint_as_float(u << 16); }
__device__ __forceinline__ float hi(uint32_t u) { return __uint_as_float(u & 0xFFFF0000u); }
__device__ __forceinline__ float ex2(float x) { float y; asm("ex2.approx.ftz.f32 %0, %1;" : "=f"(y) : "f"(x)); return y; }
__device__ __forceinline__ void stsm4(uint32_t a, uint32_t r0, uint32_t r1, uint32_t r2, uint32_t r3) {
  asm volatile("stmatrix.sync.aligned.m8n8.x4.shared.b16 [%0], {%1,%2,%3,%4};" ::"r"(a), "r"(r0), "r"(r1), "r"(r2), "r"(r3) : "memory");
}
__device__ __forceinline__ void tma3(uint32_t dst, const CUtensorMap* m, int c0, int c1, int c2, uint32_t bar) {
  asm volatile("cp.async.bulk.tensor.3d.shared::cluster.global.mbarrier::complete_tx::bytes [%0], [%1, {%3,%4,%5}], [%2];"
               ::"r"(dst), "l"(m), "r"(bar), "r"(c0), "r"(c1), "r"(c2) : "memory");
}
__device__ __forceinline__ void tma2(uint32_t dst, const CUtensorMap* m, int c0, int c1, uint32_t bar) {
  asm volatile("cp.async.bulk.tensor.2d.shared::cluster.global.mbarrier::complete_tx::bytes [%0], [%1, {%3,%4}], [%2];"
               ::"r"(dst), "l"(m), "r"(bar), "r"(c0), "r"(c1) : "memory");
}
__device__ __forceinline__ uint32_t lds32(uint32_t a) { uint32_t v; asm volatile("ld.shared.u32 %0, [%1];" : "=r"(v) : "r"(a) : "memory"); return v; }
__device__ __forceinline__ void bulk_ld(uint32_t dst, const void* src, int bytes, uint32_t bar) {
  asm volatile("cp.async.bulk.shared::cluster.global.mbarrier::complete_tx::bytes [%0], [%1], %2, [%3];" ::"r"(dst), "l"(src), "r"(bytes), "r"(bar) : "memory");
}
__device__ __forceinline__ uint4 ldcg4(const void* p) {
  uint4 v; asm volatile("ld.global.cg.v4.u32 {%0,%1,%2,%3}, [%4];" : "=r"(v.x), "=r"(v.y), "=r"(v.z), "=r"(v.w) : "l"(p) : "memory"); return v;
}

__device__ __forceinline__ uint2 ldcg2(const void* p) {
  uint2 v; asm volatile("ld.global.cg.v2.u32 {%0,%1}, [%2];" : "=r"(v.x), "=r"(v.y) : "l"(p) : "memory"); return v;
}

__device__ __forceinline__ void mma_ss_184(float (&d)[92], uint64_t da, uint64_t db, int acc) {
  asm volatile("{.reg .pred p; setp.ne.b32 p, %94, 0;\n"
    "wgmma.mma_async.sync.aligned.m64n184k16.f32.bf16.bf16 {%0,%1,%2,%3,%4,%5,%6,%7,%8,%9,%10,%11,%12,%13,%14,%15,%16,%17,%18,%19,%20,%21,%22,%23,%24,%25,%26,%27,%28,%29,%30,%31,%32,%33,%34,%35,%36,%37,%38,%39,%40,%41,%42,%43,%44,%45,%46,%47,%48,%49,%50,%51,%52,%53,%54,%55,%56,%57,%58,%59,%60,%61,%62,%63,%64,%65,%66,%67,%68,%69,%70,%71,%72,%73,%74,%75,%76,%77,%78,%79,%80,%81,%82,%83,%84,%85,%86,%87,%88,%89,%90,%91}, %92, %93, p, 1, 1, 0, 1;}\n"
    : "+f"(d[0]),"+f"(d[1]),"+f"(d[2]),"+f"(d[3]),"+f"(d[4]),"+f"(d[5]),"+f"(d[6]),"+f"(d[7]),"+f"(d[8]),"+f"(d[9]),"+f"(d[10]),"+f"(d[11]),"+f"(d[12]),"+f"(d[13]),"+f"(d[14]),"+f"(d[15]),"+f"(d[16]),"+f"(d[17]),"+f"(d[18]),"+f"(d[19]),"+f"(d[20]),"+f"(d[21]),"+f"(d[22]),"+f"(d[23]),"+f"(d[24]),"+f"(d[25]),"+f"(d[26]),"+f"(d[27]),"+f"(d[28]),"+f"(d[29]),"+f"(d[30]),"+f"(d[31]),"+f"(d[32]),"+f"(d[33]),"+f"(d[34]),"+f"(d[35]),"+f"(d[36]),"+f"(d[37]),"+f"(d[38]),"+f"(d[39]),"+f"(d[40]),"+f"(d[41]),"+f"(d[42]),"+f"(d[43]),"+f"(d[44]),"+f"(d[45]),"+f"(d[46]),"+f"(d[47]),"+f"(d[48]),"+f"(d[49]),"+f"(d[50]),"+f"(d[51]),"+f"(d[52]),"+f"(d[53]),"+f"(d[54]),"+f"(d[55]),"+f"(d[56]),"+f"(d[57]),"+f"(d[58]),"+f"(d[59]),"+f"(d[60]),"+f"(d[61]),"+f"(d[62]),"+f"(d[63]),"+f"(d[64]),"+f"(d[65]),"+f"(d[66]),"+f"(d[67]),"+f"(d[68]),"+f"(d[69]),"+f"(d[70]),"+f"(d[71]),"+f"(d[72]),"+f"(d[73]),"+f"(d[74]),"+f"(d[75]),"+f"(d[76]),"+f"(d[77]),"+f"(d[78]),"+f"(d[79]),"+f"(d[80]),"+f"(d[81]),"+f"(d[82]),"+f"(d[83]),"+f"(d[84]),"+f"(d[85]),"+f"(d[86]),"+f"(d[87]),"+f"(d[88]),"+f"(d[89]),"+f"(d[90]),"+f"(d[91])
    : "l"(da), "l"(db), "r"(acc));
}
__device__ __forceinline__ void mma_ss_224(float (&d)[112], uint64_t da, uint64_t db, int acc) {
  asm volatile("{.reg .pred p; setp.ne.b32 p, %114, 0;\n"
    "wgmma.mma_async.sync.aligned.m64n224k16.f32.bf16.bf16 {%0,%1,%2,%3,%4,%5,%6,%7,%8,%9,%10,%11,%12,%13,%14,%15,%16,%17,%18,%19,%20,%21,%22,%23,%24,%25,%26,%27,%28,%29,%30,%31,%32,%33,%34,%35,%36,%37,%38,%39,%40,%41,%42,%43,%44,%45,%46,%47,%48,%49,%50,%51,%52,%53,%54,%55,%56,%57,%58,%59,%60,%61,%62,%63,%64,%65,%66,%67,%68,%69,%70,%71,%72,%73,%74,%75,%76,%77,%78,%79,%80,%81,%82,%83,%84,%85,%86,%87,%88,%89,%90,%91,%92,%93,%94,%95,%96,%97,%98,%99,%100,%101,%102,%103,%104,%105,%106,%107,%108,%109,%110,%111}, %112, %113, p, 1, 1, 0, 1;}\n"
    : "+f"(d[0]),"+f"(d[1]),"+f"(d[2]),"+f"(d[3]),"+f"(d[4]),"+f"(d[5]),"+f"(d[6]),"+f"(d[7]),"+f"(d[8]),"+f"(d[9]),"+f"(d[10]),"+f"(d[11]),"+f"(d[12]),"+f"(d[13]),"+f"(d[14]),"+f"(d[15]),"+f"(d[16]),"+f"(d[17]),"+f"(d[18]),"+f"(d[19]),"+f"(d[20]),"+f"(d[21]),"+f"(d[22]),"+f"(d[23]),"+f"(d[24]),"+f"(d[25]),"+f"(d[26]),"+f"(d[27]),"+f"(d[28]),"+f"(d[29]),"+f"(d[30]),"+f"(d[31]),"+f"(d[32]),"+f"(d[33]),"+f"(d[34]),"+f"(d[35]),"+f"(d[36]),"+f"(d[37]),"+f"(d[38]),"+f"(d[39]),"+f"(d[40]),"+f"(d[41]),"+f"(d[42]),"+f"(d[43]),"+f"(d[44]),"+f"(d[45]),"+f"(d[46]),"+f"(d[47]),"+f"(d[48]),"+f"(d[49]),"+f"(d[50]),"+f"(d[51]),"+f"(d[52]),"+f"(d[53]),"+f"(d[54]),"+f"(d[55]),"+f"(d[56]),"+f"(d[57]),"+f"(d[58]),"+f"(d[59]),"+f"(d[60]),"+f"(d[61]),"+f"(d[62]),"+f"(d[63]),"+f"(d[64]),"+f"(d[65]),"+f"(d[66]),"+f"(d[67]),"+f"(d[68]),"+f"(d[69]),"+f"(d[70]),"+f"(d[71]),"+f"(d[72]),"+f"(d[73]),"+f"(d[74]),"+f"(d[75]),"+f"(d[76]),"+f"(d[77]),"+f"(d[78]),"+f"(d[79]),"+f"(d[80]),"+f"(d[81]),"+f"(d[82]),"+f"(d[83]),"+f"(d[84]),"+f"(d[85]),"+f"(d[86]),"+f"(d[87]),"+f"(d[88]),"+f"(d[89]),"+f"(d[90]),"+f"(d[91]),"+f"(d[92]),"+f"(d[93]),"+f"(d[94]),"+f"(d[95]),"+f"(d[96]),"+f"(d[97]),"+f"(d[98]),"+f"(d[99]),"+f"(d[100]),"+f"(d[101]),"+f"(d[102]),"+f"(d[103]),"+f"(d[104]),"+f"(d[105]),"+f"(d[106]),"+f"(d[107]),"+f"(d[108]),"+f"(d[109]),"+f"(d[110]),"+f"(d[111])
    : "l"(da), "l"(db), "r"(acc));
}
__device__ __forceinline__ void mma_ss_56(float (&d)[28], uint64_t da, uint64_t db, int acc) {
  asm volatile("{.reg .pred p; setp.ne.b32 p, %30, 0;\n"
    "wgmma.mma_async.sync.aligned.m64n56k16.f32.bf16.bf16 {%0,%1,%2,%3,%4,%5,%6,%7,%8,%9,%10,%11,%12,%13,%14,%15,%16,%17,%18,%19,%20,%21,%22,%23,%24,%25,%26,%27}, %28, %29, p, 1, 1, 0, 1;}\n"
    : "+f"(d[0]),"+f"(d[1]),"+f"(d[2]),"+f"(d[3]),"+f"(d[4]),"+f"(d[5]),"+f"(d[6]),"+f"(d[7]),"+f"(d[8]),"+f"(d[9]),"+f"(d[10]),"+f"(d[11]),"+f"(d[12]),"+f"(d[13]),"+f"(d[14]),"+f"(d[15]),"+f"(d[16]),"+f"(d[17]),"+f"(d[18]),"+f"(d[19]),"+f"(d[20]),"+f"(d[21]),"+f"(d[22]),"+f"(d[23]),"+f"(d[24]),"+f"(d[25]),"+f"(d[26]),"+f"(d[27])
    : "l"(da), "l"(db), "r"(acc));
}
__device__ __forceinline__ void mma_rs_56(float (&d)[28], uint32_t a0, uint32_t a1, uint32_t a2, uint32_t a3, uint64_t db, int acc) {
  asm volatile("{.reg .pred p; setp.ne.b32 p, %33, 0;\n"
    "wgmma.mma_async.sync.aligned.m64n56k16.f32.bf16.bf16 {%0,%1,%2,%3,%4,%5,%6,%7,%8,%9,%10,%11,%12,%13,%14,%15,%16,%17,%18,%19,%20,%21,%22,%23,%24,%25,%26,%27}, {%28,%29,%30,%31}, %32, p, 1, 1, 1;}\n"
    : "+f"(d[0]),"+f"(d[1]),"+f"(d[2]),"+f"(d[3]),"+f"(d[4]),"+f"(d[5]),"+f"(d[6]),"+f"(d[7]),"+f"(d[8]),"+f"(d[9]),"+f"(d[10]),"+f"(d[11]),"+f"(d[12]),"+f"(d[13]),"+f"(d[14]),"+f"(d[15]),"+f"(d[16]),"+f"(d[17]),"+f"(d[18]),"+f"(d[19]),"+f"(d[20]),"+f"(d[21]),"+f"(d[22]),"+f"(d[23]),"+f"(d[24]),"+f"(d[25]),"+f"(d[26]),"+f"(d[27])
    : "r"(a0), "r"(a1), "r"(a2), "r"(a3), "l"(db), "r"(acc));
}
__device__ __forceinline__ void mma_ss_64t(float (&d)[32], uint64_t da, uint64_t db, int acc) {
  asm volatile("{.reg .pred p; setp.ne.b32 p, %34, 0;\n"
    "wgmma.mma_async.sync.aligned.m64n64k16.f32.bf16.bf16 {%0,%1,%2,%3,%4,%5,%6,%7,%8,%9,%10,%11,%12,%13,%14,%15,%16,%17,%18,%19,%20,%21,%22,%23,%24,%25,%26,%27,%28,%29,%30,%31}, %32, %33, p, 1, 1, 1, 1;}\n"
    : "+f"(d[0]),"+f"(d[1]),"+f"(d[2]),"+f"(d[3]),"+f"(d[4]),"+f"(d[5]),"+f"(d[6]),"+f"(d[7]),"+f"(d[8]),"+f"(d[9]),"+f"(d[10]),"+f"(d[11]),"+f"(d[12]),"+f"(d[13]),"+f"(d[14]),"+f"(d[15]),"+f"(d[16]),"+f"(d[17]),"+f"(d[18]),"+f"(d[19]),"+f"(d[20]),"+f"(d[21]),"+f"(d[22]),"+f"(d[23]),"+f"(d[24]),"+f"(d[25]),"+f"(d[26]),"+f"(d[27]),"+f"(d[28]),"+f"(d[29]),"+f"(d[30]),"+f"(d[31])
    : "l"(da), "l"(db), "r"(acc));
}
__device__ __forceinline__ void mma_rs_64(float (&d)[32], uint32_t a0, uint32_t a1, uint32_t a2, uint32_t a3, uint64_t db, int acc) {
  asm volatile("{.reg .pred p; setp.ne.b32 p, %37, 0;\n"
    "wgmma.mma_async.sync.aligned.m64n64k16.f32.bf16.bf16 {%0,%1,%2,%3,%4,%5,%6,%7,%8,%9,%10,%11,%12,%13,%14,%15,%16,%17,%18,%19,%20,%21,%22,%23,%24,%25,%26,%27,%28,%29,%30,%31}, {%32,%33,%34,%35}, %36, p, 1, 1, 1;}\n"
    : "+f"(d[0]),"+f"(d[1]),"+f"(d[2]),"+f"(d[3]),"+f"(d[4]),"+f"(d[5]),"+f"(d[6]),"+f"(d[7]),"+f"(d[8]),"+f"(d[9]),"+f"(d[10]),"+f"(d[11]),"+f"(d[12]),"+f"(d[13]),"+f"(d[14]),"+f"(d[15]),"+f"(d[16]),"+f"(d[17]),"+f"(d[18]),"+f"(d[19]),"+f"(d[20]),"+f"(d[21]),"+f"(d[22]),"+f"(d[23]),"+f"(d[24]),"+f"(d[25]),"+f"(d[26]),"+f"(d[27]),"+f"(d[28]),"+f"(d[29]),"+f"(d[30]),"+f"(d[31])
    : "r"(a0), "r"(a1), "r"(a2), "r"(a3), "l"(db), "r"(acc));
}

__device__ __forceinline__ void dual_softmax(const float (&p)[28], uint32_t (&phi)[4][7]) {
  constexpr float L2E = 1.4426950408889634f;
#pragma unroll
  for (int i = 0; i < 4; i++) {
    float mx = p[i], mn = p[i];
#pragma unroll
    for (int j = 1; j < 7; j++) { mx = fmaxf(mx, p[4 * j + i]); mn = fminf(mn, p[4 * j + i]); }
    mx = fmaxf(mx, __shfl_xor_sync(~0u, mx, 1)); mn = fminf(mn, __shfl_xor_sync(~0u, mn, 1));
    mx = fmaxf(mx, __shfl_xor_sync(~0u, mx, 2)); mn = fminf(mn, __shfl_xor_sync(~0u, mn, 2));
    float a[7], b[7], sa = 0.f, sb = 0.f;
    const float mxl = mx * L2E, mnl = mn * L2E;
#pragma unroll
    for (int j = 0; j < 7; j++) {
      a[j] = ex2(fmaf(p[4 * j + i], L2E, -mxl)); b[j] = ex2(fmaf(p[4 * j + i], -L2E, mnl));
      sa += a[j]; sb += b[j];
    }
    sa += __shfl_xor_sync(~0u, sa, 1); sb += __shfl_xor_sync(~0u, sb, 1);
    sa += __shfl_xor_sync(~0u, sa, 2); sb += __shfl_xor_sync(~0u, sb, 2);
    const float ra = __fdividef(1.f, sa), rb = __fdividef(1.f, sb);
#pragma unroll
    for (int j = 0; j < 7; j++) phi[i][j] = pack(a[j] * ra, b[j] * rb);
  }
}

struct Ring {
  uint32_t full, empty, base; int slot, par;
  __device__ __forceinline__ uint32_t acquire() { mbar_wait(full + slot * 8, par); return base + slot * SLOT; }
  __device__ __forceinline__ int advance() { int s = slot; if (++slot == NSLOT) { slot = 0; par ^= 1; } return s; }
  __device__ __forceinline__ void release(int s, bool elect) { if (elect) mbar_arrive(empty + s * 8); }
};
constexpr int FL_KV = 448, FL_CS = FL_KV + 16, FL_DONE = FL_KV + 32, FL_XS = FL_KV + 33;

__global__ void __launch_bounds__(384, 1)
fused_kernel(const __grid_constant__ CUtensorMap mQKV, const __grid_constant__ CUtensorMap mWO,
             const __grid_constant__ CUtensorMap mW1, const __grid_constant__ CUtensorMap mW2,
             const __grid_constant__ CUtensorMap mX,
             const __nv_bfloat16* __restrict__ x, const __nv_bfloat16* __restrict__ wphi,
             const __nv_bfloat16* __restrict__ b1, const __nv_bfloat16* __restrict__ b2,
             const __nv_bfloat16* __restrict__ wqkv, const __nv_bfloat16* __restrict__ wo, const __nv_bfloat16* __restrict__ w1,
             const __nv_bfloat16* __restrict__ w2, __nv_bfloat16* __restrict__ out) {
  extern __shared__ unsigned char smem_raw[];
  const uint32_t sb = (smem_u32(smem_raw) + 1023) & ~1023u;
  unsigned char* sg = smem_raw + (sb - smem_u32(smem_raw));
  const int tid = threadIdx.x, lane = tid & 31;
  const int G = blockIdx.x >> 3, r = blockIdx.x & 7;
  const uint32_t barFull = sb + OFF_BAR, barEmpty = barFull + 56, barA = barEmpty + 56, barCS = barA + 112;
  uint4 cu[7] = {};
  if (tid >= 256 && tid < 288) {
    if (lane < 30) mbar_init(barFull + lane * 8, lane >= 28 ? 96 : (lane >= 7 && lane < 14 ? 2 : 1));
    asm volatile("fence.mbarrier_init.release.cluster;" ::: "memory");
  } else if (tid >= 288) {
    const int ch = min((tid - 288) >> 2, 20), p = ch / 7;
    const uint4* src = reinterpret_cast<const uint4*>(wqkv + (size_t)(G * 28 + (tid & 3) * 7) * 1344 + p * 448 + 56 * r) + (ch - 7 * p);
#pragma unroll
    for (int i = 0; i < 7; i++) cu[i] = __ldg(src + i * 168);
  }
  __syncthreads();
  const int wgid = __shfl_sync(~0u, tid >> 7, 0);
  if (wgid == 2) {
    asm volatile("setmaxnreg.dec.sync.aligned.u32 56;");
    if (tid < 288) {
    if (lane < 14) {
        const int k = lane >> 1, cc = lane & 1;
        mbar_expect(barA + (cc * 7 + k) * 8, 8192);
        tma2(sb + (cc * 7 + k) * 8192, &mX, 64 * k, G * 128 + 64 * cc, barA + (cc * 7 + k) * 8);
      } else if (lane < 21) {
        const int i = lane - 14;
        mbar_expect(barFull + i * 8, 12288);
        tma3(sb + OFF_RING + i * SLOT, &mQKV, 56 * r, 32 * i, 0, barFull + i * 8);
      }
    }
    if (tid == 256) {
      int slot = 0, par = 0;
      for (int it = NSLOT; it < 2 * TILES_PER_LAYER; it++) {
        const int i = it >= TILES_PER_LAYER ? it - TILES_PER_LAYER : it;
        mbar_wait(barEmpty + slot * 8, par);
        const uint32_t dst = sb + OFF_RING + slot * SLOT, fb = barFull + slot * 8;
        mbar_expect(fb, i < 14 ? 12288 : SLOT);
        if (i < 14) tma3(dst, &mQKV, 56 * r, 32 * i, 0, fb);
        else if (i < 18) tma2(dst, &mWO, 56 * r, 112 * (i - 14), fb);
        else if (i < 32) tma3(dst, &mW1, 0, 32 * (i - 18), 7 * r, fb);
        else tma2(dst, &mW2, 64 * ((i - 32) >> 1), 224 * r + 112 * (i & 1), fb);
        if (++slot == NSLOT) { slot = 0; par ^= 1; }
      }
    } else if (tid >= 288) {
      unsigned ep;
      asm volatile("ld.relaxed.gpu.global.u32 %0, [%1];" : "=r"(ep) : "l"(gFlag + FL_DONE * 32) : "memory");
      const int idx = tid - 288;
#pragma unroll 1
      for (int ps = 0; ps < 3; ps++) {
        const int nch = ps ? 14 : 21, ch = min(idx >> 2, nch - 1), p = ch / 7, k0 = G * 28 + (idx & 3) * 7;
        if (ps) {
          const uint4* src = reinterpret_cast<const uint4*>(w1 + (size_t)k0 * 1792 + 224 * r) + (ps - 1) * 14 + ch;
#pragma unroll
          for (int i = 0; i < 7; i++) cu[i] = __ldg(src + i * 224);
        }
        float s[8] = {};
#pragma unroll
        for (int i = 0; i < 7; i++) { s[0] += lo(cu[i].x); s[1] += hi(cu[i].x); s[2] += lo(cu[i].y); s[3] += hi(cu[i].y); s[4] += lo(cu[i].z); s[5] += hi(cu[i].z); s[6] += lo(cu[i].w); s[7] += hi(cu[i].w); }
#pragma unroll
        for (int i = 0; i < 8; i++) { s[i] += __shfl_xor_sync(~0u, s[i], 1); s[i] += __shfl_xor_sync(~0u, s[i], 2); }
        if ((idx & 3) < 2 && idx < nch * 4)
          gCS[(r * 16 + G) * 104 + (ps ? 10 + ps * 14 + ch : ch + p) * 2 + (idx & 1)] = (idx & 1) ? make_float4(s[4], s[5], s[6], s[7]) : make_float4(s[0], s[1], s[2], s[3]);
        if (ps == 0 && G == 0) {
#pragma unroll 1
          for (int i = idx; i < 2 * 1280; i += 96) gKV[((i >= 1280) * 7 + r) * 1280 + i] = make_float4(0.f, 0.f, 0.f, 0.f);
        }
        if (ps == 1) continue;
        unsigned* f = gFlag + (FL_CS + (ps >> 1) * 8 + r) * 32;
        __syncwarp();
        if (lane == 0) { flag_arrive(f); flag_wait(f, (ep / NCTA + 1) * 48); }
        __syncwarp();
#pragma unroll 1
        for (int j = idx + ps * 48; j < (ps ? 208 : 96); j += 96) {
          float2 v[16], a = make_float2(0.f, 0.f);
#pragma unroll
          for (int i = 0; i < 16; i++) v[i] = __ldcg(reinterpret_cast<const float2*>(gCS + (r * 16 + i) * 104) + j);
#pragma unroll
          for (int i = 0; i < 16; i++) { a.x += v[i].x; a.y += v[i].y; }
          reinterpret_cast<float2*>(sg + OFF_CS)[j] = a;
        }
        mbar_arrive(barCS + (ps >> 1) * 8);
        if (ps == 0 && idx < 2) {
          const char* pf = idx ? (const char*)w2 + blockIdx.x * 12544 : (const char*)wo + blockIdx.x * 3136;
          asm volatile("cp.async.bulk.prefetch.L2.global [%0], %1;" ::"l"(pf), "r"(idx ? 12544 : 3136) : "memory");
        }
      }
    }
  } else {
  asm volatile("setmaxnreg.inc.sync.aligned.u32 224;");
  const int c = wgid, w = (tid >> 5) & 3, g = lane >> 2, t = lane & 3;
  const bool elect = (tid & 127) == 0;
  const uint32_t abuf = sb + c * ABYTES, barAc = barA + c * 56;
  const int row0 = G * 128 + c * 64;
  unsigned epoch;
  asm volatile("ld.relaxed.gpu.global.u32 %0, [%1];" : "=r"(epoch) : "l"(gFlag + FL_DONE * 32) : "memory");
  STAMP(24);
  float mean[2], rstd[2];
  uint32_t wv[7];
#pragma unroll
  for (int i = 0; i < 7; i++)
    wv[i] = __ldg(reinterpret_cast<const unsigned short*>(wphi) + (56 * r + i * 8 + (tid >> 5)) * 28 + min(lane, 27));
  const uint32_t bv = __ldg(reinterpret_cast<const unsigned short*>(b1) + 224 * r + min(tid, 223));
  uint4 su[2];
  {
    float sh[2] = {0.f, 0.f}, s1[2] = {0.f, 0.f}, s2[2] = {0.f, 0.f};
#pragma unroll 1
    for (int k = 0; k < 7; k++) {
      mbar_wait(barAc + k * 8, 0);
#pragma unroll
      for (int i = 0; i < 4; i++) {
        const int hh = i >> 1;
        const uint4 u = *reinterpret_cast<const uint4*>(sg + c * ABYTES + k * 8192 + (w * 16 + hh * 8 + g) * 128 + ((((i ^ g) & 1) * 4 + t) << 4));
        if (k == 0 && !(i & 1)) sh[hh] = lo(u.x);
        const uint32_t e[4] = {u.x, u.y, u.z, u.w};
#pragma unroll
        for (int z = 0; z < 4; z++) { const float a = lo(e[z]) - sh[hh], b = hi(e[z]) - sh[hh]; s1[hh] += a + b; s2[hh] = fmaf(a, a, fmaf(b, b, s2[hh])); }
      }
    }
#pragma unroll
    for (int hh = 0; hh < 2; hh++) {
      const float d = s1[hh] * (1.f / 112.f), m = sh[hh] + d, q = 0.5f * fmaxf(s2[hh] - d * s1[hh], 0.f);
      su[hh] = make_uint4(__float_as_uint(m), __float_as_uint(q), __float_as_uint(m), __float_as_uint(q));
    }
#pragma unroll
    for (int i = 0; i < 8; i++) {
      const int k = i * 8 + (tid >> 5);
      *reinterpret_cast<uint32_t*>(sg + OFF_WPHI + k * 128 + ((g ^ (k & 7)) << 4) + t * 4) = (i < 7 && lane < 28) ? wv[i % 7] << (k >= 28 ? 16 : 0) : 0u;
    }
    if (tid < 224) reinterpret_cast<uint32_t*>(sg + OFF_B1)[tid] = bv << 16;
    fence_async_smem();
    bar_sync<3, 256>();
    epoch = epoch / NCTA + 1;
  }
  STAMP(0);
  Ring ring{barFull, barEmpty, sb + OFF_RING, 0, 0};
  int apar = 0;
  const uint32_t stsm_off = (w * 16 + ((lane >> 3) & 1) * 8 + (lane & 7)) * 128;
  const uint32_t stsm_hi = lane >> 4;
  const uint64_t dA = mkdesc(abuf, 1024, 128, 0);

  auto gather = [&](unsigned* fl, const unsigned char* img) {
    __syncwarp();
    if (lane == 0) flag_arrive(fl);
    if (w == 0) {
      STAMP(27);
      if (lane == 0) flag_wait(fl, epoch * 32);
      __syncwarp();
      STAMP(28);
      if (lane < 7) { fence_async(); mbar_expect(barAc + lane * 8, 8192); bulk_ld(abuf + lane * 8192, img + lane * 8192, 8192, barAc + lane * 8); }
    }
    __syncwarp();
    apar ^= 1;
  };
  auto slice_off = [&](int j, int hh) -> uint32_t {
    return (7 * r + j) * 1024 + (w * 2 + hh) * 128 + lane * 4;
  };
  auto load_stats = [&](const float2* st) {
    mbar_wait(barAc, apar);
#pragma unroll
    for (int hh = 0; hh < 2; hh++) su[hh] = ldcg4(st + (size_t)(row0 + w * 16 + hh * 8 + g) * 8 + 2 * t);
  };
  auto finish_stats = [&]() {
#pragma unroll
    for (int hh = 0; hh < 2; hh++) {
      const float m0 = __uint_as_float(su[hh].x), m1 = __uint_as_float(su[hh].z);
      float m = m0 + m1;
      m += __shfl_xor_sync(~0u, m, 1); m += __shfl_xor_sync(~0u, m, 2);
      m *= 0.125f;
      float q = __uint_as_float(su[hh].y) + __uint_as_float(su[hh].w) + 56.f * ((m0 - m) * (m0 - m) + (m1 - m) * (m1 - m));
      q += __shfl_xor_sync(~0u, q, 1); q += __shfl_xor_sync(~0u, q, 2);
      mean[hh] = m; rstd[hh] = rsqrtf(q * (1.f / DM) + 1e-5f);
    }
  };

#pragma unroll 1
  for (int layer = 0; layer < 2; layer++) {
    unsigned* const fl = gFlag + (layer * 32 + G * 2 + c) * 7 * 32;
    uint32_t phiq[4][7], xs[7][2];
    {
      float acc[92]; reg_def(acc);
      const uint64_t dQ = layer ? dA : mkdesc(abuf, 16, 1024, 1);
      const int kstep = layer ? 128 : 2;
      int prev = 0;
      if (layer) load_stats(gStat + 2048 * 8);
#pragma unroll 1
      for (int st = 0; st < 14; st++) {
        if (!(st & 1)) mbar_wait(barAc + (st >> 1) * 8, apar);
        const uint64_t da = dQ + (st >> 1) * 512 + (st & 1) * 2 * kstep, db = mkdesc(ring.acquire(), 4096, 1024, 1);
        wg_fence();
        mma_ss_184(acc, da, db, st);
        mma_ss_184(acc, da + kstep, db + 128, 1);
        wg_commit();
        if (st > 0) { wg_wait<1>(); ring.release(prev, elect); }
        prev = ring.advance();
      }
      finish_stats();
      if (layer == 0) STAMP(25);
      mbar_wait(barCS, 0);
#pragma unroll
      for (int j = 0; j < 7; j++) {
        const int ci = 7 * r + j;
        const uint32_t a = abuf + (layer ? slice_off(j, 0) : (ci >> 3) * 8192 + (w * 16 + g) * 128 + (((ci & 7) ^ g) << 4) + t * 4);
        xs[j][0] = lds32(a); xs[j][1] = lds32(a + (layer ? 128 : 1024));
      }
      wg_wait<0>(); reg_fence(acc);
      ring.release(prev, elect);
      STAMP(1 + layer * 12);
      uint32_t f[3][14];
      {
        const float2* cs = reinterpret_cast<const float2*>(sg + OFF_CS) + t;
        const float mr0 = -mean[0] * rstd[0], mr1 = -mean[1] * rstd[1];
#pragma unroll
        for (int p = 0; p < 3; p++)
#pragma unroll
          for (int j = 0; j < 7; j++) {
            const float2 s = cs[p * 32 + j * 4];
            const int b = p * 32 + j * 4;
            f[p][2 * j] = pack(fmaf(acc[b], rstd[0], s.x * mr0), fmaf(acc[b + 1], rstd[0], s.y * mr0));
            f[p][2 * j + 1] = pack(fmaf(acc[b + 2], rstd[1], s.x * mr1), fmaf(acc[b + 3], rstd[1], s.y * mr1));
          }
      }
      float pk[28], pq[28]; reg_def(pk); reg_def(pq);
      const uint64_t dW = mkdesc(sb + OFF_WPHI, 4096, 1024, 1);
      wg_fence();
#pragma unroll
      for (int s = 0; s < 4; s++)
        mma_rs_56(pk, f[1][4 * s], f[1][4 * s + 1], s < 3 ? f[1][(4 * s + 2) % 14] : 0u, s < 3 ? f[1][(4 * s + 3) % 14] : 0u, dW + s * 128, s);
      wg_commit();
#pragma unroll
      for (int s = 0; s < 4; s++)
        mma_rs_56(pq, f[0][4 * s], f[0][4 * s + 1], s < 3 ? f[0][(4 * s + 2) % 14] : 0u, s < 3 ? f[0][(4 * s + 3) % 14] : 0u, dW + s * 128, s);
      wg_commit();
      bar_wg(c);
      const uint32_t srow = abuf + stsm_off, ones = t == 0 ? 0x3F803F80u : 0u;
#pragma unroll
      for (int jp = 0; jp < 4; jp++)
        stsm4(srow + 16384 + (((2 * jp + stsm_hi) ^ (lane & 7)) << 4), f[2][4 * jp], f[2][4 * jp + 1],
              jp < 3 ? f[2][(4 * jp + 2) % 14] : ones, jp < 3 ? f[2][(4 * jp + 3) % 14] : ones);
      wg_wait<0>(); reg_fence(pk); reg_fence(pq);
#pragma unroll 1
      for (int pass = 0; pass < 2; pass++) {
        dual_softmax(pk, phiq);
        if (pass) break;
#pragma unroll
        for (int e = 0; e < 2; e++)
#pragma unroll
          for (int jp = 0; jp < 4; jp++)
            stsm4(srow + e * 8192 + (((2 * jp + stsm_hi) ^ (lane & 7)) << 4), phiq[e][2 * jp], phiq[2 + e][2 * jp],
                  jp < 3 ? phiq[e][(2 * jp + 1) % 7] : 0u, jp < 3 ? phiq[2 + e][(2 * jp + 1) % 7] : 0u);
        fence_async_smem();
        bar_sync<3, 256>();
        float kv[32]; reg_def(kv);
        const uint64_t dP = mkdesc(sb + c * 8192, 4096, 1024, 1), dV = mkdesc(sb + 16384, 4096, 1024, 1);
        wg_fence();
#pragma unroll
        for (int s = 0; s < 8; s++) mma_ss_64t(kv, dP + (s >> 2) * (ABYTES / 16) + (s & 3) * 128, dV + (s >> 2) * (ABYTES / 16) + (s & 3) * 128, s);
        wg_commit();
        wg_wait<0>(); reg_fence(kv);
        float4* kvg = gKV + ((layer * 8 + r) * 2 + c) * 640 + (tid & 127);
#pragma unroll
        for (int i = 0; i < 5; i++) {
          float v0, v1, v2, v3;
          if (i == 4) { v0 = kv[28]; v1 = kv[29]; v2 = kv[30]; v3 = kv[31]; }
          else { v0 = c ? kv[12 + 4 * i] : kv[4 * i]; v1 = c ? kv[13 + 4 * i] : kv[1 + 4 * i]; v2 = c ? kv[14 + 4 * i] : kv[2 + 4 * i]; v3 = c ? kv[15 + 4 * i] : kv[3 + 4 * i]; }
          const bool use = i == 4 ? t == 0 : (i == 0 ? (c == 0 || t >= 2) : (i == 3 ? (c == 1 || t < 2) : true));
          if (use) asm volatile("red.relaxed.gpu.global.add.v4.f32 [%0], {%1,%2,%3,%4};" ::"l"(kvg + i * 128), "f"(v0), "f"(v1), "f"(v2), "f"(v3) : "memory");
        }
        __syncwarp();
        if (lane == 0) flag_arrive(gFlag + (FL_KV + layer * 8 + r) * 32);
        __syncwarp();
        STAMP(2 + layer * 12);
#pragma unroll
        for (int i = 0; i < 28; i++) pk[i] = pq[i];
      }
    }
    {
      if (elect) flag_wait(gFlag + (FL_KV + layer * 8 + r) * 32, epoch * 128);
      bar_wg(c);
      STAMP(3 + layer * 12);
      const float4* kvg = gKV + (layer * 8 + r) * 1280 + (tid & 127);
      uint4 kk[2][5];
#pragma unroll
      for (int e = 0; e < 2; e++)
#pragma unroll
        for (int i = 0; i < 5; i++) kk[e][i] = ldcg4(kvg + e * 640 + i * 128);
      const uint32_t srow = abuf + 24576 + stsm_off;
#pragma unroll
      for (int e = 0; e < 2; e++) {
        uint32_t f[8][2];
#pragma unroll
        for (int j = 0; j < 8; j++) { f[j][0] = 0u; f[j][1] = 0u; }
#pragma unroll
        for (int i = 0; i < 4; i++) {
          f[i + 3 * e][0] = pack(__uint_as_float(kk[e][i].x), __uint_as_float(kk[e][i].y));
          f[i + 3 * e][1] = pack(__uint_as_float(kk[e][i].z), __uint_as_float(kk[e][i].w));
        }
        f[7][0] = e ? pack(0.f, __uint_as_float(kk[e][4].y)) : pack(__uint_as_float(kk[e][4].x), 0.f);
        f[7][1] = e ? pack(0.f, __uint_as_float(kk[e][4].w)) : pack(__uint_as_float(kk[e][4].z), 0.f);
#pragma unroll
        for (int jp = 0; jp < 4; jp++)
          stsm4(srow + e * 8192 + (((2 * jp + stsm_hi) ^ (lane & 7)) << 4), f[2 * jp][0], f[2 * jp][1], f[2 * jp + 1][0], f[2 * jp + 1][1]);
      }
      fence_async_smem();
      bar_wg(c);
      float num[32]; reg_def(num);
      const uint64_t dK = mkdesc(abuf + 24576, 4096, 1024, 1);
      wg_fence();
#pragma unroll
      for (int e = 0; e < 2; e++)
#pragma unroll
        for (int s = 0; s < 4; s++)
          mma_rs_64(num, phiq[e][2 * s], phiq[2 + e][2 * s], s < 3 ? phiq[e][(2 * s + 1) % 7] : 0u, s < 3 ? phiq[2 + e][(2 * s + 1) % 7] : 0u,
                    dK + e * 512 + s * 128, e + s);
      wg_commit();
      wg_wait<0>(); reg_fence(num);
      float rd[4];
#pragma unroll
      for (int i = 0; i < 4; i++) rd[i] = __fdividef(1.f, __shfl_sync(~0u, num[28 + i], lane & ~3) + 1e-6f);
      unsigned char* img = gImg + (size_t)(G * 2 + c) * ABYTES;
#pragma unroll
      for (int j = 0; j < 7; j++) {
        const bool hb = j > 3 || (j == 3 && t >= 2);
        const float r0 = hb ? rd[1] : rd[0], r1 = hb ? rd[3] : rd[2];
        *reinterpret_cast<uint32_t*>(img + slice_off(j, 0)) = pack(num[4 * j] * r0, num[4 * j + 1] * r0);
        *reinterpret_cast<uint32_t*>(img + slice_off(j, 1)) = pack(num[4 * j + 2] * r1, num[4 * j + 3] * r1);
      }
      STAMP(4 + layer * 12);
      gather(fl, img);
      STAMP(5 + layer * 12);
    }
    {
      float acc[28]; reg_def(acc);
      int prev = 0;
#pragma unroll 1
      for (int st = 0; st < 4; st++) {
        mbar_wait(barAc + (st * 7 + 3) / 4 * 8, apar);
        mbar_wait(barAc + (st * 7 + 6) / 4 * 8, apar);
        const uint64_t db = mkdesc(ring.acquire(), 4096, 1024, 1);
        wg_fence();
#pragma unroll
        for (int s = 0; s < 7; s++) { const int ks = st * 7 + s; mma_ss_56(acc, dA + ks * 128, db + s * 128, ks); }
        wg_commit();
        if (st > 0) { wg_wait<1>(); ring.release(prev, elect); }
        prev = ring.advance();
      }
      wg_wait<0>(); reg_fence(acc);
      ring.release(prev, elect);
      unsigned char* img = gImg + (size_t)(32 + G * 2 + c) * ABYTES;
#pragma unroll
      for (int hh = 0; hh < 2; hh++) {
        float s = 0.f, q = 0.f;
#pragma unroll
        for (int j = 0; j < 7; j++) {
          xs[j][hh] = pack(lo(xs[j][hh]) + acc[4 * j + 2 * hh], hi(xs[j][hh]) + acc[4 * j + 2 * hh + 1]);
          *reinterpret_cast<uint32_t*>(img + slice_off(j, hh)) = xs[j][hh];
          s += lo(xs[j][hh]) + hi(xs[j][hh]);
        }
        s += __shfl_xor_sync(~0u, s, 1); s += __shfl_xor_sync(~0u, s, 2);
        s *= 1.f / 56.f;
#pragma unroll
        for (int j = 0; j < 7; j++) { const float a = lo(xs[j][hh]) - s, b = hi(xs[j][hh]) - s; q = fmaf(a, a, q); q = fmaf(b, b, q); }
        q += __shfl_xor_sync(~0u, q, 1); q += __shfl_xor_sync(~0u, q, 2);
        if (t == 0) gStat[(size_t)(row0 + w * 16 + hh * 8 + g) * 8 + r] = make_float2(s, q);
      }
      STAMP(6 + layer * 12);
      gather(fl + 32, img);
      STAMP(7 + layer * 12);
    }
    {
      uint32_t hf[28][2];
      {
        float acc[112]; reg_def(acc);
        int prev = 0;
        load_stats(gStat);
#pragma unroll 1
        for (int st = 0; st < 14; st++) {
          if (!(st & 1)) mbar_wait(barAc + (st >> 1) * 8, apar);
          const uint64_t da = dA + st * 256, db = mkdesc(ring.acquire(), 2048, 512, 2);
          wg_fence();
          mma_ss_224(acc, da, db, st);
          mma_ss_224(acc, da + 128, db + 64, 1);
          wg_commit();
          if (st > 0) { wg_wait<1>(); ring.release(prev, elect); }
          prev = ring.advance();
        }
        finish_stats();
        mbar_wait(barCS + 8, 0);
        wg_wait<0>(); reg_fence(acc);
        ring.release(prev, elect);
        STAMP(8 + layer * 12);
        const float2* bs = reinterpret_cast<const float2*>(sg + OFF_B1) + t;
        const float2* cs = reinterpret_cast<const float2*>(sg + OFF_CS + 768) + t;
        const float mr0 = -mean[0] * rstd[0], mr1 = -mean[1] * rstd[1];
#pragma unroll
        for (int j = 0; j < 28; j++) {
          const float2 b = bs[4 * j], s = cs[4 * j];
          const float h0 = fmaxf(fmaf(acc[4 * j], rstd[0], fmaf(s.x, mr0, b.x)), 0.f), h1 = fmaxf(fmaf(acc[4 * j + 1], rstd[0], fmaf(s.y, mr0, b.y)), 0.f);
          const float h2 = fmaxf(fmaf(acc[4 * j + 2], rstd[1], fmaf(s.x, mr1, b.x)), 0.f), h3 = fmaxf(fmaf(acc[4 * j + 3], rstd[1], fmaf(s.y, mr1, b.y)), 0.f);
          hf[j][0] = pack(h0 * h0, h1 * h1); hf[j][1] = pack(h2 * h2, h3 * h3);
        }
      }
      unsigned char* pdst = gP + (size_t)(((G * 2 + c) * 8 + 2 * w) * 8 + r) * 7168 + lane * 8;
      uint2 pk[8] = {};
#pragma unroll 1
      for (int ch = 0; ch < 7; ch++) {
        float acc[32]; reg_def(acc);
        int sl0 = 0, sl1 = 0;
#pragma unroll
        for (int hk = 0; hk < 2; hk++) {
          const uint64_t db = mkdesc(ring.acquire(), 4096, 1024, 1);
          wg_fence();
#pragma unroll
          for (int s = 0; s < 7; s++) { const int ks = hk * 7 + s; mma_rs_64(acc, hf[2 * ks][0], hf[2 * ks][1], hf[2 * ks + 1][0], hf[2 * ks + 1][1], db + s * 128, ks); }
          wg_commit();
          if (hk) sl1 = ring.advance(); else sl0 = ring.advance();
        }
        if (ch > 0) {
#pragma unroll
          for (int i = 0; i < 8; i++) *reinterpret_cast<uint2*>(pdst + (i & 1) * (8 * 7168) + (i >> 1) * 256) = pk[i];
          pdst += 1024;
        }
        wg_wait<1>(); ring.release(sl0, elect);
        wg_wait<0>(); reg_fence(acc); ring.release(sl1, elect);
#pragma unroll
        for (int i = 0; i < 8; i++) {
          const int b = (i >> 1) * 8 + (i & 1) * 2;
          pk[i] = make_uint2(pack(acc[b], acc[b + 1]), pack(acc[b + 4], acc[b + 5]));
        }
      }
#pragma unroll
      for (int i = 0; i < 8; i++) *reinterpret_cast<uint2*>(pdst + (i & 1) * (8 * 7168) + (i >> 1) * 256) = pk[i];
      STAMP(9 + layer * 12);
    }
    {
      uint32_t bx[14];
#pragma unroll
      for (int j = 0; j < 14; j++) bx[j] = __ldg(reinterpret_cast<const uint32_t*>(b2 + w * 112 + j * 8 + 2 * t));
      __syncwarp();
      if (lane == 0) { flag_arrive(fl + (3 + w) * 32); flag_wait(fl + (3 + (r >> 1)) * 32, epoch * 8); }
      __syncwarp();
      STAMP(10 + layer * 12);
      const unsigned char* psrc = gP + (size_t)(((G * 2 + c) * 8 + r) * 8) * 7168 + w * 1792 + lane * 8;
      unsigned char* img = gImg + (size_t)(64 + G * 2 + c) * ABYTES;
      uint2 pv[8][7];
#pragma unroll
      for (int s = 0; s < 8; s++)
#pragma unroll
        for (int i = 0; i < 7; i++) pv[s][i] = ldcg2(psrc + s * 7168 + i * 256);
      const uint32_t off = w * 14336 + r * 128 + lane * 4;
      unsigned char* dst = layer ? reinterpret_cast<unsigned char*>(out + (size_t)(row0 + r * 8 + g) * DM + w * 112 + 2 * t) : img + off;
      float sm = 0.f, q = 0.f;
#pragma unroll
      for (int j = 0; j < 14; j++) {
        float y0 = lo(bx[j]), y1 = hi(bx[j]);
        const uint32_t xo = lds32(abuf + off + j * 1024);
        y0 += lo(xo); y1 += hi(xo);
#pragma unroll
        for (int s = 0; s < 8; s++) { const uint32_t u = (j & 1) ? pv[s][j >> 1].y : pv[s][j >> 1].x; y0 += lo(u); y1 += hi(u); }
        bx[j] = pack(y0, y1);
        *reinterpret_cast<uint32_t*>(dst + j * (layer ? 16 : 1024)) = bx[j];
        sm += lo(bx[j]) + hi(bx[j]);
      }
      if (layer) break;
      sm += __shfl_xor_sync(~0u, sm, 1); sm += __shfl_xor_sync(~0u, sm, 2);
      sm *= 1.f / 112.f;
#pragma unroll
      for (int j = 0; j < 14; j++) { const float a = lo(bx[j]) - sm, b = hi(bx[j]) - sm; q = fmaf(a, a, q); q = fmaf(b, b, q); }
      q += __shfl_xor_sync(~0u, q, 1); q += __shfl_xor_sync(~0u, q, 2);
      if (t < 2) gStat[(size_t)(2048 + row0 + r * 8 + g) * 8 + 2 * w + t] = make_float2(sm, q * 0.5f);
      STAMP(11);
      gather(fl + 64, img);
      STAMP(12);
    }
  }
  STAMP(30);
  if (tid == 0) asm volatile("red.relaxed.gpu.global.add.u32 [%0], 1;" ::"l"(gFlag + FL_DONE * 32) : "memory");
  }
}

typedef CUresult (*EncFn)(CUtensorMap*, CUtensorMapDataType, cuuint32_t, void*, const cuuint64_t*, const cuuint64_t*,
                          const cuuint32_t*, const cuuint32_t*, CUtensorMapInterleave, CUtensorMapSwizzle,
                          CUtensorMapL2promotion, CUtensorMapFloatOOBfill);

void make_map(EncFn enc, CUtensorMap* m, void* p, int rank, uint64_t d0, uint64_t d1, uint64_t d2, uint64_t s1, uint64_t s2,
              uint32_t b0, uint32_t b1, uint32_t b2, CUtensorMapSwizzle sw) {
  cuuint64_t dims[3] = {d0, d1, d2}, strides[2] = {s1, s2};
  cuuint32_t box[3] = {b0, b1, b2}, es[3] = {1, 1, 1};
  enc(m, CU_TENSOR_MAP_DATA_TYPE_BFLOAT16, rank, p, dims, strides, box, es, CU_TENSOR_MAP_INTERLEAVE_NONE, sw,
      CU_TENSOR_MAP_L2_PROMOTION_L2_128B, CU_TENSOR_MAP_FLOAT_OOB_FILL_NONE);
}

}

extern "C" void kernel_launch(void* const* d_in, const int* in_sizes, int n_in, void* d_out, int out_size) {
  static EncFn enc = nullptr;
  if (!enc) {
    cudaDriverEntryPointQueryResult st;
    void* fn = nullptr;
    cudaGetDriverEntryPoint("cuTensorMapEncodeTiled", &fn, cudaEnableDefault, &st);
    enc = (EncFn)fn;
    cudaFuncSetAttribute(fused_kernel, cudaFuncAttributeMaxDynamicSharedMemorySize, SMEM_BYTES);
  }
  CUtensorMap mQKV, mWO, mW1, mW2, mX;
  make_map(enc, &mQKV, d_in[1], 3, 448, 448, 3, 2688, 896, 64, 32, 3, CU_TENSOR_MAP_SWIZZLE_128B);
  make_map(enc, &mWO, d_in[3], 2, 448, 448, 1, 896, 0, 64, 112, 1, CU_TENSOR_MAP_SWIZZLE_128B);
  make_map(enc, &mW1, d_in[5], 3, 32, 448, 56, 3584, 64, 32, 32, 7, CU_TENSOR_MAP_SWIZZLE_64B);
  make_map(enc, &mW2, d_in[7], 2, 448, 1792, 1, 896, 0, 64, 112, 1, CU_TENSOR_MAP_SWIZZLE_128B);
  make_map(enc, &mX, d_in[0], 2, 448, 2048, 1, 896, 0, 64, 64, 1, CU_TENSOR_MAP_SWIZZLE_128B);
  fused_kernel<<<NCTA, 384, SMEM_BYTES, cudaStreamPerThread>>>(
      mQKV, mWO, mW1, mW2, mX, (const __nv_bfloat16*)d_in[0], (const __nv_bfloat16*)d_in[2], (const __nv_bfloat16*)d_in[6],
      (const __nv_bfloat16*)d_in[8], (const __nv_bfloat16*)d_in[1], (const __nv_bfloat16*)d_in[3], (const __nv_bfloat16*)d_in[5],
      (const __nv_bfloat16*)d_in[7], (__nv_bfloat16*)d_out);
}
```

```cpp
#include <cuda_runtime.h>
#include <cuda_bf16.h>
#include <cuda.h>
#include <stdint.h>

namespace {

constexpr int DM = 448, NCTA = 128;
constexpr int ABYTES = 57344;
constexpr int SLOT = 14336, NSLOT = 7;
constexpr int OFF_RING = 2 * ABYTES;
constexpr int OFF_WPHI = OFF_RING + NSLOT * SLOT;
constexpr int OFF_B1 = OFF_WPHI + 8192;
constexpr int OFF_CS = OFF_B1 + 896;
constexpr int OFF_ONE = OFF_CS + 1664;
constexpr int OFF_BAR = OFF_ONE + 512;
constexpr int SMEM_BYTES = OFF_BAR + 256 + 1024;
constexpr int TILES_PER_LAYER = 46;

__device__ __align__(1024) unsigned char gP[16 * 2 * 8 * 8 * 7168];
__device__ __align__(1024) unsigned char gImg[3 * 32 * ABYTES];
__device__ __align__(1024) float2 gStat[2 * 2048 * 8];
__device__ __align__(1024) float4 gKV[2 * 8 * 2 * 5 * 128];
__device__ __align__(1024) float4 gCS[8 * 16 * 104];
__device__ __align__(128) unsigned gFlag[(2 * 32 * 7 + 32 + 1 + 16) * 32];
#define STAMP(i)

__device__ __forceinline__ uint32_t smem_u32(const void* p) { return (uint32_t)__cvta_generic_to_shared(p); }
__device__ __forceinline__ void mbar_init(uint32_t b, int c) { asm volatile("mbarrier.init.shared::cta.b64 [%0], %1;" ::"r"(b), "r"(c)); }
__device__ __forceinline__ void mbar_expect(uint32_t b, int bytes) { asm volatile("mbarrier.arrive.expect_tx.shared::cta.b64 _, [%0], %1;" ::"r"(b), "r"(bytes) : "memory"); }
__device__ __forceinline__ void mbar_arrive(uint32_t b) { asm volatile("mbarrier.arrive.shared::cta.b64 _, [%0];" ::"r"(b) : "memory"); }
__device__ __forceinline__ void mbar_wait(uint32_t b, int par) {
  uint32_t ok; int n = 0;
  while (true) {
    asm volatile("{.reg .pred p; mbarrier.try_wait.parity.shared::cta.b64 p, [%1], %2; selp.u32 %0,1,0,p;}" : "=r"(ok) : "r"(b), "r"(par) : "memory");
    if (ok) break;
    if (++n > (1 << 22)) break;
  }
}
__device__ __forceinline__ void flag_wait(const unsigned* f, unsigned target) {
  unsigned v; int n = 0;
  while (true) {
    asm volatile("ld.acquire.gpu.global.u32 %0, [%1];" : "=r"(v) : "l"(f) : "memory");
    if ((int)(v - target) >= 0) break;
    if (++n > (1 << 21)) break;
  }
}
__device__ __forceinline__ void flag_arrive(unsigned* f) { asm volatile("red.release.gpu.global.add.u32 [%0], 1;" ::"l"(f) : "memory"); }
__device__ __forceinline__ void fence_async() { asm volatile("fence.proxy.async.global;" ::: "memory"); }
__device__ __forceinline__ void fence_async_smem() { asm volatile("fence.proxy.async.shared::cta;" ::: "memory"); }
template <int ID, int N> __device__ __forceinline__ void bar_sync() { asm volatile("bar.sync %0, %1;" ::"n"(ID), "n"(N) : "memory"); }
__device__ __forceinline__ void bar_wg(int c) { if (c) bar_sync<2, 128>(); else bar_sync<1, 128>(); }
__device__ __forceinline__ void wg_fence() { asm volatile("wgmma.fence.sync.aligned;" ::: "memory"); }
__device__ __forceinline__ void wg_commit() { asm volatile("wgmma.commit_group.sync.aligned;" ::: "memory"); }
template <int N> __device__ __forceinline__ void wg_wait() { asm volatile("wgmma.wait_group.sync.aligned %0;" ::"n"(N) : "memory"); }
template <int N> __device__ __forceinline__ void reg_fence(float (&d)[N]) {
#pragma unroll
  for (int i = 0; i < N; i++) asm volatile("" : "+f"(d[i])::"memory");
}
template <int N> __device__ __forceinline__ void reg_def(float (&d)[N]) {
#pragma unroll
  for (int i = 0; i < N; i++) d[i] = 0.f;
}
__device__ __forceinline__ uint64_t mkdesc(uint32_t addr, uint32_t lbo, uint32_t sbo, uint64_t swz) {
  return (uint64_t)((addr & 0x3FFFF) >> 4) | ((uint64_t)(lbo >> 4) << 16) | ((uint64_t)(sbo >> 4) << 32) | (swz << 62);
}
__device__ __forceinline__ uint32_t pack(float a, float b) {
  uint32_t r; asm("cvt.rn.bf16x2.f32 %0, %1, %2;" : "=r"(r) : "f"(b), "f"(a)); return r;
}
__device__ __forceinline__ float lo(uint32_t u) { return __uint_as_float(u << 16); }
__device__ __forceinline__ float hi(uint32_t u) { return __uint_as_float(u & 0xFFFF0000u); }
__device__ __forceinline__ float ex2(float x) { float y; asm("ex2.approx.ftz.f32 %0, %1;" : "=f"(y) : "f"(x)); return y; }
__device__ __forceinline__ void stsm4(uint32_t a, uint32_t r0, uint32_t r1, uint32_t r2, uint32_t r3) {
  asm volatile("stmatrix.sync.aligned.m8n8.x4.shared.b16 [%0], {%1,%2,%3,%4};" ::"r"(a), "r"(r0), "r"(r1), "r"(r2), "r"(r3) : "memory");
}
__device__ __forceinline__ void tma3(uint32_t dst, const CUtensorMap* m, int c0, int c1, int c2, uint32_t bar) {
  asm volatile("cp.async.bulk.tensor.3d.shared::cluster.global.mbarrier::complete_tx::bytes [%0], [%1, {%3,%4,%5}], [%2];"
               ::"r"(dst), "l"(m), "r"(bar), "r"(c0), "r"(c1), "r"(c2) : "memory");
}
__device__ __forceinline__ void tma2(uint32_t dst, const CUtensorMap* m, int c0, int c1, uint32_t bar) {
  asm volatile("cp.async.bulk.tensor.2d.shared::cluster.global.mbarrier::complete_tx::bytes [%0], [%1, {%3,%4}], [%2];"
               ::"r"(dst), "l"(m), "r"(bar), "r"(c0), "r"(c1) : "memory");
}
__device__ __forceinline__ uint32_t lds32(uint32_t a) { uint32_t v; asm volatile("ld.shared.u32 %0, [%1];" : "=r"(v) : "r"(a) : "memory"); return v; }
__device__ __forceinline__ void bulk_ld(uint32_t dst, const void* src, int bytes, uint32_t bar) {
  asm volatile("cp.async.bulk.shared::cluster.global.mbarrier::complete_tx::bytes [%0], [%1], %2, [%3];" ::"r"(dst), "l"(src), "r"(bytes), "r"(bar) : "memory");
}
__device__ __forceinline__ uint4 ldcg4(const void* p) {
  uint4 v; asm volatile("ld.global.cg.v4.u32 {%0,%1,%2,%3}, [%4];" : "=r"(v.x), "=r"(v.y), "=r"(v.z), "=r"(v.w) : "l"(p) : "memory"); return v;
}

__device__ __forceinline__ uint2 ldcg2(const void* p) {
  uint2 v; asm volatile("ld.global.cg.v2.u32 {%0,%1}, [%2];" : "=r"(v.x), "=r"(v.y) : "l"(p) : "memory"); return v;
}

__device__ __forceinline__ void mma_ss_184(float (&d)[92], uint64_t da, uint64_t db, int acc) {
  asm volatile("{.reg .pred p; setp.ne.b32 p, %94, 0;\n"
    "wgmma.mma_async.sync.aligned.m64n184k16.f32.bf16.bf16 {%0,%1,%2,%3,%4,%5,%6,%7,%8,%9,%10,%11,%12,%13,%14,%15,%16,%17,%18,%19,%20,%21,%22,%23,%24,%25,%26,%27,%28,%29,%30,%31,%32,%33,%34,%35,%36,%37,%38,%39,%40,%41,%42,%43,%44,%45,%46,%47,%48,%49,%50,%51,%52,%53,%54,%55,%56,%57,%58,%59,%60,%61,%62,%63,%64,%65,%66,%67,%68,%69,%70,%71,%72,%73,%74,%75,%76,%77,%78,%79,%80,%81,%82,%83,%84,%85,%86,%87,%88,%89,%90,%91}, %92, %93, p, 1, 1, 0, 1;}\n"
    : "+f"(d[0]),"+f"(d[1]),"+f"(d[2]),"+f"(d[3]),"+f"(d[4]),"+f"(d[5]),"+f"(d[6]),"+f"(d[7]),"+f"(d[8]),"+f"(d[9]),"+f"(d[10]),"+f"(d[11]),"+f"(d[12]),"+f"(d[13]),"+f"(d[14]),"+f"(d[15]),"+f"(d[16]),"+f"(d[17]),"+f"(d[18]),"+f"(d[19]),"+f"(d[20]),"+f"(d[21]),"+f"(d[22]),"+f"(d[23]),"+f"(d[24]),"+f"(d[25]),"+f"(d[26]),"+f"(d[27]),"+f"(d[28]),"+f"(d[29]),"+f"(d[30]),"+f"(d[31]),"+f"(d[32]),"+f"(d[33]),"+f"(d[34]),"+f"(d[35]),"+f"(d[36]),"+f"(d[37]),"+f"(d[38]),"+f"(d[39]),"+f"(d[40]),"+f"(d[41]),"+f"(d[42]),"+f"(d[43]),"+f"(d[44]),"+f"(d[45]),"+f"(d[46]),"+f"(d[47]),"+f"(d[48]),"+f"(d[49]),"+f"(d[50]),"+f"(d[51]),"+f"(d[52]),"+f"(d[53]),"+f"(d[54]),"+f"(d[55]),"+f"(d[56]),"+f"(d[57]),"+f"(d[58]),"+f"(d[59]),"+f"(d[60]),"+f"(d[61]),"+f"(d[62]),"+f"(d[63]),"+f"(d[64]),"+f"(d[65]),"+f"(d[66]),"+f"(d[67]),"+f"(d[68]),"+f"(d[69]),"+f"(d[70]),"+f"(d[71]),"+f"(d[72]),"+f"(d[73]),"+f"(d[74]),"+f"(d[75]),"+f"(d[76]),"+f"(d[77]),"+f"(d[78]),"+f"(d[79]),"+f"(d[80]),"+f"(d[81]),"+f"(d[82]),"+f"(d[83]),"+f"(d[84]),"+f"(d[85]),"+f"(d[86]),"+f"(d[87]),"+f"(d[88]),"+f"(d[89]),"+f"(d[90]),"+f"(d[91])
    : "l"(da), "l"(db), "r"(acc));
}
__device__ __forceinline__ void mma_ss_224(float (&d)[112], uint64_t da, uint64_t db, int acc) {
  asm volatile("{.reg .pred p; setp.ne.b32 p, %114, 0;\n"
    "wgmma.mma_async.sync.aligned.m64n224k16.f32.bf16.bf16 {%0,%1,%2,%3,%4,%5,%6,%7,%8,%9,%10,%11,%12,%13,%14,%15,%16,%17,%18,%19,%20,%21,%22,%23,%24,%25,%26,%27,%28,%29,%30,%31,%32,%33,%34,%35,%36,%37,%38,%39,%40,%41,%42,%43,%44,%45,%46,%47,%48,%49,%50,%51,%52,%53,%54,%55,%56,%57,%58,%59,%60,%61,%62,%63,%64,%65,%66,%67,%68,%69,%70,%71,%72,%73,%74,%75,%76,%77,%78,%79,%80,%81,%82,%83,%84,%85,%86,%87,%88,%89,%90,%91,%92,%93,%94,%95,%96,%97,%98,%99,%100,%101,%102,%103,%104,%105,%106,%107,%108,%109,%110,%111}, %112, %113, p, 1, 1, 0, 1;}\n"
    : "+f"(d[0]),"+f"(d[1]),"+f"(d[2]),"+f"(d[3]),"+f"(d[4]),"+f"(d[5]),"+f"(d[6]),"+f"(d[7]),"+f"(d[8]),"+f"(d[9]),"+f"(d[10]),"+f"(d[11]),"+f"(d[12]),"+f"(d[13]),"+f"(d[14]),"+f"(d[15]),"+f"(d[16]),"+f"(d[17]),"+f"(d[18]),"+f"(d[19]),"+f"(d[20]),"+f"(d[21]),"+f"(d[22]),"+f"(d[23]),"+f"(d[24]),"+f"(d[25]),"+f"(d[26]),"+f"(d[27]),"+f"(d[28]),"+f"(d[29]),"+f"(d[30]),"+f"(d[31]),"+f"(d[32]),"+f"(d[33]),"+f"(d[34]),"+f"(d[35]),"+f"(d[36]),"+f"(d[37]),"+f"(d[38]),"+f"(d[39]),"+f"(d[40]),"+f"(d[41]),"+f"(d[42]),"+f"(d[43]),"+f"(d[44]),"+f"(d[45]),"+f"(d[46]),"+f"(d[47]),"+f"(d[48]),"+f"(d[49]),"+f"(d[50]),"+f"(d[51]),"+f"(d[52]),"+f"(d[53]),"+f"(d[54]),"+f"(d[55]),"+f"(d[56]),"+f"(d[57]),"+f"(d[58]),"+f"(d[59]),"+f"(d[60]),"+f"(d[61]),"+f"(d[62]),"+f"(d[63]),"+f"(d[64]),"+f"(d[65]),"+f"(d[66]),"+f"(d[67]),"+f"(d[68]),"+f"(d[69]),"+f"(d[70]),"+f"(d[71]),"+f"(d[72]),"+f"(d[73]),"+f"(d[74]),"+f"(d[75]),"+f"(d[76]),"+f"(d[77]),"+f"(d[78]),"+f"(d[79]),"+f"(d[80]),"+f"(d[81]),"+f"(d[82]),"+f"(d[83]),"+f"(d[84]),"+f"(d[85]),"+f"(d[86]),"+f"(d[87]),"+f"(d[88]),"+f"(d[89]),"+f"(d[90]),"+f"(d[91]),"+f"(d[92]),"+f"(d[93]),"+f"(d[94]),"+f"(d[95]),"+f"(d[96]),"+f"(d[97]),"+f"(d[98]),"+f"(d[99]),"+f"(d[100]),"+f"(d[101]),"+f"(d[102]),"+f"(d[103]),"+f"(d[104]),"+f"(d[105]),"+f"(d[106]),"+f"(d[107]),"+f"(d[108]),"+f"(d[109]),"+f"(d[110]),"+f"(d[111])
    : "l"(da), "l"(db), "r"(acc));
}
__device__ __forceinline__ void mma_ss_56(float (&d)[28], uint64_t da, uint64_t db, int acc) {
  asm volatile("{.reg .pred p; setp.ne.b32 p, %30, 0;\n"
    "wgmma.mma_async.sync.aligned.m64n56k16.f32.bf16.bf16 {%0,%1,%2,%3,%4,%5,%6,%7,%8,%9,%10,%11,%12,%13,%14,%15,%16,%17,%18,%19,%20,%21,%22,%23,%24,%25,%26,%27}, %28, %29, p, 1, 1, 0, 1;}\n"
    : "+f"(d[0]),"+f"(d[1]),"+f"(d[2]),"+f"(d[3]),"+f"(d[4]),"+f"(d[5]),"+f"(d[6]),"+f"(d[7]),"+f"(d[8]),"+f"(d[9]),"+f"(d[10]),"+f"(d[11]),"+f"(d[12]),"+f"(d[13]),"+f"(d[14]),"+f"(d[15]),"+f"(d[16]),"+f"(d[17]),"+f"(d[18]),"+f"(d[19]),"+f"(d[20]),"+f"(d[21]),"+f"(d[22]),"+f"(d[23]),"+f"(d[24]),"+f"(d[25]),"+f"(d[26]),"+f"(d[27])
    : "l"(da), "l"(db), "r"(acc));
}
__device__ __forceinline__ void mma_rs_56(float (&d)[28], uint32_t a0, uint32_t a1, uint32_t a2, uint32_t a3, uint64_t db, int acc) {
  asm volatile("{.reg .pred p; setp.ne.b32 p, %33, 0;\n"
    "wgmma.mma_async.sync.aligned.m64n56k16.f32.bf16.bf16 {%0,%1,%2,%3,%4,%5,%6,%7,%8,%9,%10,%11,%12,%13,%14,%15,%16,%17,%18,%19,%20,%21,%22,%23,%24,%25,%26,%27}, {%28,%29,%30,%31}, %32, p, 1, 1, 1;}\n"
    : "+f"(d[0]),"+f"(d[1]),"+f"(d[2]),"+f"(d[3]),"+f"(d[4]),"+f"(d[5]),"+f"(d[6]),"+f"(d[7]),"+f"(d[8]),"+f"(d[9]),"+f"(d[10]),"+f"(d[11]),"+f"(d[12]),"+f"(d[13]),"+f"(d[14]),"+f"(d[15]),"+f"(d[16]),"+f"(d[17]),"+f"(d[18]),"+f"(d[19]),"+f"(d[20]),"+f"(d[21]),"+f"(d[22]),"+f"(d[23]),"+f"(d[24]),"+f"(d[25]),"+f"(d[26]),"+f"(d[27])
    : "r"(a0), "r"(a1), "r"(a2), "r"(a3), "l"(db), "r"(acc));
}
__device__ __forceinline__ void mma_ss_64t(float (&d)[32], uint64_t da, uint64_t db, int acc) {
  asm volatile("{.reg .pred p; setp.ne.b32 p, %34, 0;\n"
    "wgmma.mma_async.sync.aligned.m64n64k16.f32.bf16.bf16 {%0,%1,%2,%3,%4,%5,%6,%7,%8,%9,%10,%11,%12,%13,%14,%15,%16,%17,%18,%19,%20,%21,%22,%23,%24,%25,%26,%27,%28,%29,%30,%31}, %32, %33, p, 1, 1, 1, 1;}\n"
    : "+f"(d[0]),"+f"(d[1]),"+f"(d[2]),"+f"(d[3]),"+f"(d[4]),"+f"(d[5]),"+f"(d[6]),"+f"(d[7]),"+f"(d[8]),"+f"(d[9]),"+f"(d[10]),"+f"(d[11]),"+f"(d[12]),"+f"(d[13]),"+f"(d[14]),"+f"(d[15]),"+f"(d[16]),"+f"(d[17]),"+f"(d[18]),"+f"(d[19]),"+f"(d[20]),"+f"(d[21]),"+f"(d[22]),"+f"(d[23]),"+f"(d[24]),"+f"(d[25]),"+f"(d[26]),"+f"(d[27]),"+f"(d[28]),"+f"(d[29]),"+f"(d[30]),"+f"(d[31])
    : "l"(da), "l"(db), "r"(acc));
}
__device__ __forceinline__ void mma_rs_64(float (&d)[32], uint32_t a0, uint32_t a1, uint32_t a2, uint32_t a3, uint64_t db, int acc) {
  asm volatile("{.reg .pred p; setp.ne.b32 p, %37, 0;\n"
    "wgmma.mma_async.sync.aligned.m64n64k16.f32.bf16.bf16 {%0,%1,%2,%3,%4,%5,%6,%7,%8,%9,%10,%11,%12,%13,%14,%15,%16,%17,%18,%19,%20,%21,%22,%23,%24,%25,%26,%27,%28,%29,%30,%31}, {%32,%33,%34,%35}, %36, p, 1, 1, 1;}\n"
    : "+f"(d[0]),"+f"(d[1]),"+f"(d[2]),"+f"(d[3]),"+f"(d[4]),"+f"(d[5]),"+f"(d[6]),"+f"(d[7]),"+f"(d[8]),"+f"(d[9]),"+f"(d[10]),"+f"(d[11]),"+f"(d[12]),"+f"(d[13]),"+f"(d[14]),"+f"(d[15]),"+f"(d[16]),"+f"(d[17]),"+f"(d[18]),"+f"(d[19]),"+f"(d[20]),"+f"(d[21]),"+f"(d[22]),"+f"(d[23]),"+f"(d[24]),"+f"(d[25]),"+f"(d[26]),"+f"(d[27]),"+f"(d[28]),"+f"(d[29]),"+f"(d[30]),"+f"(d[31])
    : "r"(a0), "r"(a1), "r"(a2), "r"(a3), "l"(db), "r"(acc));
}
__device__ __forceinline__ void mma_ss_8t(float (&d)[4], uint64_t da, uint64_t db, int acc) {
  asm volatile("{.reg .pred p; setp.ne.b32 p, %6, 0;\n"
    "wgmma.mma_async.sync.aligned.m64n8k16.f32.bf16.bf16 {%0,%1,%2,%3}, %4, %5, p, 1, 1, 1, 0;}\n"
    : "+f"(d[0]),"+f"(d[1]),"+f"(d[2]),"+f"(d[3])
    : "l"(da), "l"(db), "r"(acc));
}

__device__ __forceinline__ void dual_softmax(const float (&p)[28], uint32_t (&phi)[4][7]) {
  constexpr float L2E = 1.4426950408889634f;
#pragma unroll
  for (int i = 0; i < 4; i++) {
    float mx = p[i], mn = p[i];
#pragma unroll
    for (int j = 1; j < 7; j++) { mx = fmaxf(mx, p[4 * j + i]); mn = fminf(mn, p[4 * j + i]); }
    mx = fmaxf(mx, __shfl_xor_sync(~0u, mx, 1)); mn = fminf(mn, __shfl_xor_sync(~0u, mn, 1));
    mx = fmaxf(mx, __shfl_xor_sync(~0u, mx, 2)); mn = fminf(mn, __shfl_xor_sync(~0u, mn, 2));
    float a[7], b[7], sa = 0.f, sb = 0.f;
    const float mxl = mx * L2E, mnl = mn * L2E;
#pragma unroll
    for (int j = 0; j < 7; j++) {
      a[j] = ex2(fmaf(p[4 * j + i], L2E, -mxl)); b[j] = ex2(fmaf(p[4 * j + i], -L2E, mnl));
      sa += a[j]; sb += b[j];
    }
    sa += __shfl_xor_sync(~0u, sa, 1); sb += __shfl_xor_sync(~0u, sb, 1);
    sa += __shfl_xor_sync(~0u, sa, 2); sb += __shfl_xor_sync(~0u, sb, 2);
    const float ra = __fdividef(1.f, sa), rb = __fdividef(1.f, sb);
#pragma unroll
    for (int j = 0; j < 7; j++) phi[i][j] = pack(a[j] * ra, b[j] * rb);
  }
}

struct Ring {
  uint32_t full, empty, base; int slot, par;
  __device__ __forceinline__ uint32_t acquire() { mbar_wait(full + slot * 8, par); return base + slot * SLOT; }
  __device__ __forceinline__ int advance() { int s = slot; if (++slot == NSLOT) { slot = 0; par ^= 1; } return s; }
  __device__ __forceinline__ void release(int s, bool elect) { if (elect) mbar_arrive(empty + s * 8); }
};
constexpr int FL_KV = 448, FL_CS = FL_KV + 16, FL_DONE = FL_KV + 32;

__global__ void __launch_bounds__(384, 1)
fused_kernel(const __grid_constant__ CUtensorMap mQKV, const __grid_constant__ CUtensorMap mWO,
             const __grid_constant__ CUtensorMap mW1, const __grid_constant__ CUtensorMap mW2,
             const __grid_constant__ CUtensorMap mX,
             const __nv_bfloat16* __restrict__ x, const __nv_bfloat16* __restrict__ wphi,
             const __nv_bfloat16* __restrict__ b1, const __nv_bfloat16* __restrict__ b2,
             const __nv_bfloat16* __restrict__ wqkv, const __nv_bfloat16* __restrict__ wo, const __nv_bfloat16* __restrict__ w1,
             const __nv_bfloat16* __restrict__ w2, __nv_bfloat16* __restrict__ out) {
  extern __shared__ unsigned char smem_raw[];
  const uint32_t sb = (smem_u32(smem_raw) + 1023) & ~1023u;
  unsigned char* sg = smem_raw + (sb - smem_u32(smem_raw));
  const int tid = threadIdx.x, lane = tid & 31;
  const int G = blockIdx.x >> 3, r = blockIdx.x & 7;
  const uint32_t barFull = sb + OFF_BAR, barEmpty = barFull + 56, barA = barEmpty + 56, barCS = barA + 112;
  if (tid >= 256 && tid < 288) {
    if (lane < 30) mbar_init(barFull + lane * 8, lane >= 28 ? 96 : (lane >= 7 && lane < 14 ? 2 : 1));
    asm volatile("fence.mbarrier_init.release.cluster;" ::: "memory");
  }
  __syncthreads();
  const int wgid = __shfl_sync(~0u, tid >> 7, 0);
  if (wgid == 2) {
    if (tid < 288) {
    if (lane < 14) {
        const int k = lane >> 1, cc = lane & 1;
        mbar_expect(barA + (cc * 7 + k) * 8, 8192);
        tma2(sb + (cc * 7 + k) * 8192, &mX, 64 * k, G * 128 + 64 * cc, barA + (cc * 7 + k) * 8);
      } else if (lane < 21) {
        const int i = lane - 14;
        mbar_expect(barFull + i * 8, 12288);
        tma3(sb + OFF_RING + i * SLOT, &mQKV, 56 * r, 32 * i, 0, barFull + i * 8);
      }
    }
    __syncwarp();
    asm volatile("setmaxnreg.dec.sync.aligned.u32 56;");
    if (tid == 256) {
      int slot = 0, par = 0;
      for (int it = NSLOT; it < 2 * TILES_PER_LAYER; it++) {
        const int i = it >= TILES_PER_LAYER ? it - TILES_PER_LAYER : it;
        mbar_wait(barEmpty + slot * 8, par);
        const uint32_t dst = sb + OFF_RING + slot * SLOT, fb = barFull + slot * 8;
        mbar_expect(fb, i < 14 ? 12288 : SLOT);
        if (i < 14) tma3(dst, &mQKV, 56 * r, 32 * i, 0, fb);
        else if (i < 18) tma2(dst, &mWO, 56 * r, 112 * (i - 14), fb);
        else if (i < 32) tma3(dst, &mW1, 0, 32 * (i - 18), 7 * r, fb);
        else tma2(dst, &mW2, 64 * ((i - 32) >> 1), 224 * r + 112 * (i & 1), fb);
        if (++slot == NSLOT) { slot = 0; par ^= 1; }
      }
    } else if (tid >= 288) {
      unsigned ep;
      asm volatile("ld.relaxed.gpu.global.u32 %0, [%1];" : "=r"(ep) : "l"(gFlag + FL_DONE * 32) : "memory");
      const int idx = tid - 288;
      ep = (ep / NCTA + 1) * 3;
      if (G == 0) {
#pragma unroll 1
        for (int i = idx; i < 2 * 1280; i += 96) gKV[((i >= 1280) * 7 + r) * 1280 + i] = make_float4(0.f, 0.f, 0.f, 0.f);
        __syncwarp();
        if (lane == 0) flag_arrive(gFlag + (FL_CS + r) * 32);
      }
      mbar_wait(barFull + 48, 0);
      if (idx < 2) {
        const char* pf = idx ? (const char*)w2 + blockIdx.x * 12544 : (const char*)wo + blockIdx.x * 3136;
        asm volatile("cp.async.bulk.prefetch.L2.global [%0], %1;" ::"l"(pf), "r"(idx ? 12544 : 3136) : "memory");
      }
      if (lane == 0) flag_wait(gFlag + (FL_CS + r) * 32, ep);
      __syncwarp();
      mbar_arrive(barCS);
#pragma unroll 1
      for (int ps = 0; ps < 2; ps++) {
        const int ch = ps * 14 + min(idx >> 2, 13);
        const uint4* src = reinterpret_cast<const uint4*>(w1 + (size_t)(G * 28 + (idx & 3) * 7) * 1792 + 224 * r) + ch;
        uint4 cu[7];
#pragma unroll
        for (int i = 0; i < 7; i++) cu[i] = __ldg(src + i * 224);
        float s[8] = {};
#pragma unroll
        for (int i = 0; i < 7; i++) { s[0] += lo(cu[i].x); s[1] += hi(cu[i].x); s[2] += lo(cu[i].y); s[3] += hi(cu[i].y); s[4] += lo(cu[i].z); s[5] += hi(cu[i].z); s[6] += lo(cu[i].w); s[7] += hi(cu[i].w); }
#pragma unroll
        for (int i = 0; i < 8; i++) { s[i] += __shfl_xor_sync(~0u, s[i], 1); s[i] += __shfl_xor_sync(~0u, s[i], 2); }
        if ((idx & 3) < 2 && idx < 56) gCS[(r * 16 + G) * 56 + ch * 2 + (idx & 1)] = (idx & 1) ? make_float4(s[4], s[5], s[6], s[7]) : make_float4(s[0], s[1], s[2], s[3]);
      }
      __syncwarp();
      if (lane == 0) { flag_arrive(gFlag + (FL_CS + 8 + r) * 32); flag_wait(gFlag + (FL_CS + 8 + r) * 32, ep * 16); }
      __syncwarp();
#pragma unroll 1
      for (int j = idx; j < 112; j += 96) {
        float2 v[16], a = make_float2(0.f, 0.f);
#pragma unroll
        for (int i = 0; i < 16; i++) v[i] = __ldcg(reinterpret_cast<const float2*>(gCS + (r * 16 + i) * 56) + j);
#pragma unroll
        for (int i = 0; i < 16; i++) { a.x += v[i].x; a.y += v[i].y; }
        reinterpret_cast<float2*>(sg + OFF_CS + 768)[j] = a;
      }
      mbar_arrive(barCS + 8);
    }
  } else {
  const int c = wgid, w = (tid >> 5) & 3, g = lane >> 2, t = lane & 3;
  const bool elect = (tid & 127) == 0;
  const uint32_t abuf = sb + c * ABYTES, barAc = barA + c * 56;
  const int row0 = G * 128 + c * 64;
  unsigned epoch;
  asm volatile("ld.relaxed.gpu.global.u32 %0, [%1];" : "=r"(epoch) : "l"(gFlag + FL_DONE * 32) : "memory");
  STAMP(24);
  float mean[2], rstd[2];
  uint32_t wv[7];
#pragma unroll
  for (int i = 0; i < 7; i++)
    wv[i] = __ldg(reinterpret_cast<const unsigned short*>(wphi) + (56 * r + i * 8 + (tid >> 5)) * 28 + min(lane, 27));
  const uint32_t bv = __ldg(reinterpret_cast<const unsigned short*>(b1) + 224 * r + min(tid, 223));
  uint4 su[2];
  {
    float sh[2] = {0.f, 0.f}, s1[2] = {0.f, 0.f}, s2[2] = {0.f, 0.f};
#pragma unroll 1
    for (int k = 0; k < 7; k++) {
      mbar_wait(barAc + k * 8, 0);
#pragma unroll
      for (int i = 0; i < 4; i++) {
        const int hh = i >> 1;
        const uint4 u = *reinterpret_cast<const uint4*>(sg + c * ABYTES + k * 8192 + (w * 16 + hh * 8 + g) * 128 + ((((i ^ g) & 1) * 4 + t) << 4));
        if (k == 0 && !(i & 1)) sh[hh] = lo(u.x);
        const uint32_t e[4] = {u.x, u.y, u.z, u.w};
#pragma unroll
        for (int z = 0; z < 4; z++) { const float a = lo(e[z]) - sh[hh], b = hi(e[z]) - sh[hh]; s1[hh] += a + b; s2[hh] = fmaf(a, a, fmaf(b, b, s2[hh])); }
      }
    }
#pragma unroll
    for (int hh = 0; hh < 2; hh++) {
      const float d = s1[hh] * (1.f / 112.f), m = sh[hh] + d, q = 0.5f * fmaxf(s2[hh] - d * s1[hh], 0.f);
      su[hh] = make_uint4(__float_as_uint(m), __float_as_uint(q), __float_as_uint(m), __float_as_uint(q));
    }
#pragma unroll
    for (int i = 0; i < 8; i++) {
      const int k = i * 8 + (tid >> 5);
      *reinterpret_cast<uint32_t*>(sg + OFF_WPHI + k * 128 + ((g ^ (k & 7)) << 4) + t * 4) = (i < 7 && lane < 28) ? wv[i % 7] << (k >= 28 ? 16 : 0) : 0u;
    }
    if (tid < 224) reinterpret_cast<uint32_t*>(sg + OFF_B1)[tid] = bv << 16;
    if (tid < 192) reinterpret_cast<float*>(sg + OFF_CS)[tid] = 0.f;
    if (tid < 128) reinterpret_cast<uint32_t*>(sg + OFF_ONE)[tid] = 0x3F803F80u;
    fence_async_smem();
    bar_sync<3, 256>();
    epoch = epoch / NCTA + 1;
  }
  asm volatile("setmaxnreg.inc.sync.aligned.u32 224;");
  STAMP(0);
  Ring ring{barFull, barEmpty, sb + OFF_RING, 0, 0};
  int apar = 0;
  const uint32_t stsm_off = (w * 16 + ((lane >> 3) & 1) * 8 + (lane & 7)) * 128;
  const uint32_t stsm_hi = lane >> 4;
  const uint64_t dA = mkdesc(abuf, 1024, 128, 0);

  auto gather = [&](unsigned* fl, const unsigned char* img) {
    __syncwarp();
    if (lane == 0) flag_arrive(fl);
    if (w == 0) {
      STAMP(27);
      if (lane == 0) flag_wait(fl, epoch * 32);
      __syncwarp();
      STAMP(28);
      if (lane < 7) { fence_async(); mbar_expect(barAc + lane * 8, 8192); bulk_ld(abuf + lane * 8192, img + lane * 8192, 8192, barAc + lane * 8); }
    }
    __syncwarp();
    apar ^= 1;
  };
  auto slice_off = [&](int j, int hh) -> uint32_t {
    return (7 * r + j) * 1024 + (w * 2 + hh) * 128 + lane * 4;
  };
  auto load_stats = [&](const float2* st) {
    mbar_wait(barAc, apar);
#pragma unroll
    for (int hh = 0; hh < 2; hh++) su[hh] = ldcg4(st + (size_t)(row0 + w * 16 + hh * 8 + g) * 8 + 2 * t);
  };
  auto finish_stats = [&]() {
#pragma unroll
    for (int hh = 0; hh < 2; hh++) {
      const float m0 = __uint_as_float(su[hh].x), m1 = __uint_as_float(su[hh].z);
      float m = m0 + m1;
      m += __shfl_xor_sync(~0u, m, 1); m += __shfl_xor_sync(~0u, m, 2);
      m *= 0.125f;
      float q = __uint_as_float(su[hh].y) + __uint_as_float(su[hh].w) + 56.f * ((m0 - m) * (m0 - m) + (m1 - m) * (m1 - m));
      q += __shfl_xor_sync(~0u, q, 1); q += __shfl_xor_sync(~0u, q, 2);
      mean[hh] = m; rstd[hh] = rsqrtf(q * (1.f / DM) + 1e-5f);
    }
  };

#pragma unroll 1
  for (int layer = 0; layer < 2; layer++) {
    unsigned* const fl = gFlag + (layer * 32 + G * 2 + c) * 7 * 32;
    uint32_t phiq[4][7], xs[7][2];
    {
      float acc[92]; reg_def(acc);
      const uint64_t dQ = layer ? dA : mkdesc(abuf, 16, 1024, 1);
      const int kstep = layer ? 128 : 2;
      int prev = 0;
      if (layer) load_stats(gStat + 2048 * 8);
      float cq[4], ck[4], cv[4]; reg_def(cq); reg_def(ck); reg_def(cv);
      const uint64_t dOne = mkdesc(sb + OFF_ONE, 128, 128, 0);
#pragma unroll 1
      for (int st = 0; st < 14; st++) {
        if (!(st & 1)) mbar_wait(barAc + (st >> 1) * 8, apar);
        const uint64_t da = dQ + (st >> 1) * 512 + (st & 1) * 2 * kstep, db = mkdesc(ring.acquire(), 4096, 1024, 1);
        wg_fence();
        mma_ss_184(acc, da, db, st);
        mma_ss_184(acc, da + kstep, db + 128, 1);
        if (layer == 0) {
          mma_ss_8t(cq, db + c * 128, dOne, 1); mma_ss_8t(ck, db + 256 + c * 128, dOne, 1); mma_ss_8t(cv, db + 512 + c * 128, dOne, 1);
        }
        wg_commit();
        if (st > 0) { wg_wait<1>(); ring.release(prev, elect); }
        prev = ring.advance();
      }
      finish_stats();
      if (layer == 0) STAMP(25);
#pragma unroll
      for (int j = 0; j < 7; j++) {
        const int ci = 7 * r + j;
        const uint32_t a = abuf + (layer ? slice_off(j, 0) : (ci >> 3) * 8192 + (w * 16 + g) * 128 + (((ci & 7) ^ g) << 4) + t * 4);
        xs[j][0] = lds32(a); xs[j][1] = lds32(a + (layer ? 128 : 1024));
      }
      wg_wait<0>(); reg_fence(acc);
      ring.release(prev, elect);
      reg_fence(cq); reg_fence(ck); reg_fence(cv);
      if (layer == 0) {
        float* cs = reinterpret_cast<float*>(sg + OFF_CS) + w * 16 + g + (t & 1) * 8;
        if (t < 2) { atomicAdd(cs, t ? cq[2] : cq[0]); atomicAdd(cs + 64, t ? ck[2] : ck[0]); atomicAdd(cs + 128, t ? cv[2] : cv[0]); }
        bar_sync<3, 256>();
      }
      STAMP(1 + layer * 12);
      uint32_t f[3][14];
      {
        const float2* cs = reinterpret_cast<const float2*>(sg + OFF_CS) + t;
        const float mr0 = -mean[0] * rstd[0], mr1 = -mean[1] * rstd[1];
#pragma unroll
        for (int p = 0; p < 3; p++)
#pragma unroll
          for (int j = 0; j < 7; j++) {
            const float2 s = cs[p * 32 + j * 4];
            const int b = p * 32 + j * 4;
            f[p][2 * j] = pack(fmaf(acc[b], rstd[0], s.x * mr0), fmaf(acc[b + 1], rstd[0], s.y * mr0));
            f[p][2 * j + 1] = pack(fmaf(acc[b + 2], rstd[1], s.x * mr1), fmaf(acc[b + 3], rstd[1], s.y * mr1));
          }
      }
      float pk[28], pq[28]; reg_def(pk); reg_def(pq);
      const uint64_t dW = mkdesc(sb + OFF_WPHI, 4096, 1024, 1);
      wg_fence();
#pragma unroll
      for (int s = 0; s < 4; s++)
        mma_rs_56(pk, f[1][4 * s], f[1][4 * s + 1], s < 3 ? f[1][(4 * s + 2) % 14] : 0u, s < 3 ? f[1][(4 * s + 3) % 14] : 0u, dW + s * 128, s);
      wg_commit();
#pragma unroll
      for (int s = 0; s < 4; s++)
        mma_rs_56(pq, f[0][4 * s], f[0][4 * s + 1], s < 3 ? f[0][(4 * s + 2) % 14] : 0u, s < 3 ? f[0][(4 * s + 3) % 14] : 0u, dW + s * 128, s);
      wg_commit();
      bar_wg(c);
      const uint32_t srow = abuf + stsm_off, ones = t == 0 ? 0x3F803F80u : 0u;
#pragma unroll
      for (int jp = 0; jp < 4; jp++)
        stsm4(srow + 16384 + (((2 * jp + stsm_hi) ^ (lane & 7)) << 4), f[2][4 * jp], f[2][4 * jp + 1],
              jp < 3 ? f[2][(4 * jp + 2) % 14] : ones, jp < 3 ? f[2][(4 * jp + 3) % 14] : ones);
      wg_wait<0>(); reg_fence(pk); reg_fence(pq);
#pragma unroll 1
      for (int pass = 0; pass < 2; pass++) {
        dual_softmax(pk, phiq);
        if (pass) break;
#pragma unroll
        for (int e = 0; e < 2; e++)
#pragma unroll
          for (int jp = 0; jp < 4; jp++)
            stsm4(srow + e * 8192 + (((2 * jp + stsm_hi) ^ (lane & 7)) << 4), phiq[e][2 * jp], phiq[2 + e][2 * jp],
                  jp < 3 ? phiq[e][(2 * jp + 1) % 7] : 0u, jp < 3 ? phiq[2 + e][(2 * jp + 1) % 7] : 0u);
        fence_async_smem();
        bar_sync<3, 256>();
        float kv[32]; reg_def(kv);
        const uint64_t dP = mkdesc(sb + c * 8192, 4096, 1024, 1), dV = mkdesc(sb + 16384, 4096, 1024, 1);
        wg_fence();
#pragma unroll
        for (int s = 0; s < 8; s++) mma_ss_64t(kv, dP + (s >> 2) * (ABYTES / 16) + (s & 3) * 128, dV + (s >> 2) * (ABYTES / 16) + (s & 3) * 128, s);
        wg_commit();
        mbar_wait(barCS, 0);
        wg_wait<0>(); reg_fence(kv);
        float4* kvg = gKV + ((layer * 8 + r) * 2 + c) * 640 + (tid & 127);
#pragma unroll
        for (int i = 0; i < 5; i++) {
          float v0, v1, v2, v3;
          if (i == 4) { v0 = kv[28]; v1 = kv[29]; v2 = kv[30]; v3 = kv[31]; }
          else { v0 = c ? kv[12 + 4 * i] : kv[4 * i]; v1 = c ? kv[13 + 4 * i] : kv[1 + 4 * i]; v2 = c ? kv[14 + 4 * i] : kv[2 + 4 * i]; v3 = c ? kv[15 + 4 * i] : kv[3 + 4 * i]; }
          const bool use = i == 4 ? t == 0 : (i == 0 ? (c == 0 || t >= 2) : (i == 3 ? (c == 1 || t < 2) : true));
          if (use) asm volatile("red.relaxed.gpu.global.add.v4.f32 [%0], {%1,%2,%3,%4};" ::"l"(kvg + i * 128), "f"(v0), "f"(v1), "f"(v2), "f"(v3) : "memory");
        }
        __syncwarp();
        if (lane == 0) flag_arrive(gFlag + (FL_KV + layer * 8 + r) * 32);
        __syncwarp();
        STAMP(2 + layer * 12);
#pragma unroll
        for (int i = 0; i < 28; i++) pk[i] = pq[i];
      }
    }
    {
      if (elect) flag_wait(gFlag + (FL_KV + layer * 8 + r) * 32, epoch * 128);
      bar_wg(c);
      STAMP(3 + layer * 12);
      const float4* kvg = gKV + (layer * 8 + r) * 1280 + (tid & 127);
      uint4 kk[2][5];
#pragma unroll
      for (int e = 0; e < 2; e++)
#pragma unroll
        for (int i = 0; i < 5; i++) kk[e][i] = ldcg4(kvg + e * 640 + i * 128);
      const uint32_t srow = abuf + 24576 + stsm_off;
#pragma unroll
      for (int e = 0; e < 2; e++) {
        uint32_t f[8][2];
#pragma unroll
        for (int j = 0; j < 8; j++) { f[j][0] = 0u; f[j][1] = 0u; }
#pragma unroll
        for (int i = 0; i < 4; i++) {
          f[i + 3 * e][0] = pack(__uint_as_float(kk[e][i].x), __uint_as_float(kk[e][i].y));
          f[i + 3 * e][1] = pack(__uint_as_float(kk[e][i].z), __uint_as_float(kk[e][i].w));
        }
        f[7][0] = e ? pack(0.f, __uint_as_float(kk[e][4].y)) : pack(__uint_as_float(kk[e][4].x), 0.f);
        f[7][1] = e ? pack(0.f, __uint_as_float(kk[e][4].w)) : pack(__uint_as_float(kk[e][4].z), 0.f);
#pragma unroll
        for (int jp = 0; jp < 4; jp++)
          stsm4(srow + e * 8192 + (((2 * jp + stsm_hi) ^ (lane & 7)) << 4), f[2 * jp][0], f[2 * jp][1], f[2 * jp + 1][0], f[2 * jp + 1][1]);
      }
      fence_async_smem();
      bar_wg(c);
      float num[32]; reg_def(num);
      const uint64_t dK = mkdesc(abuf + 24576, 4096, 1024, 1);
      wg_fence();
#pragma unroll
      for (int e = 0; e < 2; e++)
#pragma unroll
        for (int s = 0; s < 4; s++)
          mma_rs_64(num, phiq[e][2 * s], phiq[2 + e][2 * s], s < 3 ? phiq[e][(2 * s + 1) % 7] : 0u, s < 3 ? phiq[2 + e][(2 * s + 1) % 7] : 0u,
                    dK + e * 512 + s * 128, e + s);
      wg_commit();
      wg_wait<0>(); reg_fence(num);
      float rd[4];
#pragma unroll
      for (int i = 0; i < 4; i++) rd[i] = __fdividef(1.f, __shfl_sync(~0u, num[28 + i], lane & ~3) + 1e-6f);
      unsigned char* img = gImg + (size_t)(G * 2 + c) * ABYTES;
#pragma unroll
      for (int j = 0; j < 7; j++) {
        const bool hb = j > 3 || (j == 3 && t >= 2);
        const float r0 = hb ? rd[1] : rd[0], r1 = hb ? rd[3] : rd[2];
        *reinterpret_cast<uint32_t*>(img + slice_off(j, 0)) = pack(num[4 * j] * r0, num[4 * j + 1] * r0);
        *reinterpret_cast<uint32_t*>(img + slice_off(j, 1)) = pack(num[4 * j + 2] * r1, num[4 * j + 3] * r1);
      }
      STAMP(4 + layer * 12);
      gather(fl, img);
      STAMP(5 + layer * 12);
    }
    {
      float acc[28]; reg_def(acc);
      int prev = 0;
#pragma unroll 1
      for (int st = 0; st < 4; st++) {
        mbar_wait(barAc + (st * 7 + 3) / 4 * 8, apar);
        mbar_wait(barAc + (st * 7 + 6) / 4 * 8, apar);
        const uint64_t db = mkdesc(ring.acquire(), 4096, 1024, 1);
        wg_fence();
#pragma unroll
        for (int s = 0; s < 7; s++) { const int ks = st * 7 + s; mma_ss_56(acc, dA + ks * 128, db + s * 128, ks); }
        wg_commit();
        if (st > 0) { wg_wait<1>(); ring.release(prev, elect); }
        prev = ring.advance();
      }
      wg_wait<0>(); reg_fence(acc);
      ring.release(prev, elect);
      unsigned char* img = gImg + (size_t)(32 + G * 2 + c) * ABYTES;
#pragma unroll
      for (int hh = 0; hh < 2; hh++) {
        float s = 0.f, q = 0.f;
#pragma unroll
        for (int j = 0; j < 7; j++) {
          xs[j][hh] = pack(lo(xs[j][hh]) + acc[4 * j + 2 * hh], hi(xs[j][hh]) + acc[4 * j + 2 * hh + 1]);
          *reinterpret_cast<uint32_t*>(img + slice_off(j, hh)) = xs[j][hh];
          s += lo(xs[j][hh]) + hi(xs[j][hh]);
        }
        s += __shfl_xor_sync(~0u, s, 1); s += __shfl_xor_sync(~0u, s, 2);
        s *= 1.f / 56.f;
#pragma unroll
        for (int j = 0; j < 7; j++) { const float a = lo(xs[j][hh]) - s, b = hi(xs[j][hh]) - s; q = fmaf(a, a, q); q = fmaf(b, b, q); }
        q += __shfl_xor_sync(~0u, q, 1); q += __shfl_xor_sync(~0u, q, 2);
        if (t == 0) gStat[(size_t)(row0 + w * 16 + hh * 8 + g) * 8 + r] = make_float2(s, q);
      }
      STAMP(6 + layer * 12);
      gather(fl + 32, img);
      STAMP(7 + layer * 12);
    }
    {
      uint32_t hf[28][2];
      {
        float acc[112]; reg_def(acc);
        int prev = 0;
        load_stats(gStat);
#pragma unroll 1
        for (int st = 0; st < 14; st++) {
          if (!(st & 1)) mbar_wait(barAc + (st >> 1) * 8, apar);
          const uint64_t da = dA + st * 256, db = mkdesc(ring.acquire(), 2048, 512, 2);
          wg_fence();
          mma_ss_224(acc, da, db, st);
          mma_ss_224(acc, da + 128, db + 64, 1);
          wg_commit();
          if (st > 0) { wg_wait<1>(); ring.release(prev, elect); }
          prev = ring.advance();
        }
        finish_stats();
        mbar_wait(barCS + 8, 0);
        wg_wait<0>(); reg_fence(acc);
        ring.release(prev, elect);
        STAMP(8 + layer * 12);
        const float2* bs = reinterpret_cast<const float2*>(sg + OFF_B1) + t;
        const float2* cs = reinterpret_cast<const float2*>(sg + OFF_CS + 768) + t;
        const float mr0 = -mean[0] * rstd[0], mr1 = -mean[1] * rstd[1];
#pragma unroll
        for (int j = 0; j < 28; j++) {
          const float2 b = bs[4 * j], s = cs[4 * j];
          const float h0 = fmaxf(fmaf(acc[4 * j], rstd[0], fmaf(s.x, mr0, b.x)), 0.f), h1 = fmaxf(fmaf(acc[4 * j + 1], rstd[0], fmaf(s.y, mr0, b.y)), 0.f);
          const float h2 = fmaxf(fmaf(acc[4 * j + 2], rstd[1], fmaf(s.x, mr1, b.x)), 0.f), h3 = fmaxf(fmaf(acc[4 * j + 3], rstd[1], fmaf(s.y, mr1, b.y)), 0.f);
          hf[j][0] = pack(h0 * h0, h1 * h1); hf[j][1] = pack(h2 * h2, h3 * h3);
        }
      }
      unsigned char* pdst = gP + (size_t)(((G * 2 + c) * 8 + 2 * w) * 8 + r) * 7168 + lane * 8;
      uint2 pk[8] = {};
#pragma unroll 1
      for (int ch = 0; ch < 7; ch++) {
        float acc[32]; reg_def(acc);
        int sl0 = 0, sl1 = 0;
#pragma unroll
        for (int hk = 0; hk < 2; hk++) {
          const uint64_t db = mkdesc(ring.acquire(), 4096, 1024, 1);
          wg_fence();
#pragma unroll
          for (int s = 0; s < 7; s++) { const int ks = hk * 7 + s; mma_rs_64(acc, hf[2 * ks][0], hf[2 * ks][1], hf[2 * ks + 1][0], hf[2 * ks + 1][1], db + s * 128, ks); }
          wg_commit();
          if (hk) sl1 = ring.advance(); else sl0 = ring.advance();
        }
        if (ch > 0) {
#pragma unroll
          for (int i = 0; i < 8; i++) *reinterpret_cast<uint2*>(pdst + (i & 1) * (8 * 7168) + (i >> 1) * 256) = pk[i];
          pdst += 1024;
        }
        wg_wait<1>(); ring.release(sl0, elect);
        wg_wait<0>(); reg_fence(acc); ring.release(sl1, elect);
#pragma unroll
        for (int i = 0; i < 8; i++) {
          const int b = (i >> 1) * 8 + (i & 1) * 2;
          pk[i] = make_uint2(pack(acc[b], acc[b + 1]), pack(acc[b + 4], acc[b + 5]));
        }
      }
#pragma unroll
      for (int i = 0; i < 8; i++) *reinterpret_cast<uint2*>(pdst + (i & 1) * (8 * 7168) + (i >> 1) * 256) = pk[i];
      STAMP(9 + layer * 12);
    }
    {
      uint32_t bx[14];
#pragma unroll
      for (int j = 0; j < 14; j++) bx[j] = __ldg(reinterpret_cast<const uint32_t*>(b2 + w * 112 + j * 8 + 2 * t));
      __syncwarp();
      if (lane == 0) { flag_arrive(fl + (3 + w) * 32); flag_wait(fl + (3 + (r >> 1)) * 32, epoch * 8); }
      __syncwarp();
      STAMP(10 + layer * 12);
      const unsigned char* psrc = gP + (size_t)(((G * 2 + c) * 8 + r) * 8) * 7168 + w * 1792 + lane * 8;
      unsigned char* img = gImg + (size_t)(64 + G * 2 + c) * ABYTES;
      uint2 pv[8][7];
#pragma unroll
      for (int s = 0; s < 8; s++)
#pragma unroll
        for (int i = 0; i < 7; i++) pv[s][i] = ldcg2(psrc + s * 7168 + i * 256);
      const uint32_t off = w * 14336 + r * 128 + lane * 4;
      unsigned char* dst = layer ? reinterpret_cast<unsigned char*>(out + (size_t)(row0 + r * 8 + g) * DM + w * 112 + 2 * t) : img + off;
      float sm = 0.f, q = 0.f;
#pragma unroll
      for (int j = 0; j < 14; j++) {
        float y0 = lo(bx[j]), y1 = hi(bx[j]);
        const uint32_t xo = lds32(abuf + off + j * 1024);
        y0 += lo(xo); y1 += hi(xo);
#pragma unroll
        for (int s = 0; s < 8; s++) { const uint32_t u = (j & 1) ? pv[s][j >> 1].y : pv[s][j >> 1].x; y0 += lo(u); y1 += hi(u); }
        bx[j] = pack(y0, y1);
        *reinterpret_cast<uint32_t*>(dst + j * (layer ? 16 : 1024)) = bx[j];
        sm += lo(bx[j]) + hi(bx[j]);
      }
      if (layer) break;
      sm += __shfl_xor_sync(~0u, sm, 1); sm += __shfl_xor_sync(~0u, sm, 2);
      sm *= 1.f / 112.f;
#pragma unroll
      for (int j = 0; j < 14; j++) { const float a = lo(bx[j]) - sm, b = hi(bx[j]) - sm; q = fmaf(a, a, q); q = fmaf(b, b, q); }
      q += __shfl_xor_sync(~0u, q, 1); q += __shfl_xor_sync(~0u, q, 2);
      if (t < 2) gStat[(size_t)(2048 + row0 + r * 8 + g) * 8 + 2 * w + t] = make_float2(sm, q * 0.5f);
      STAMP(11);
      gather(fl + 64, img);
      STAMP(12);
    }
  }
  STAMP(30);
  if (tid == 0) asm volatile("red.relaxed.gpu.global.add.u32 [%0], 1;" ::"l"(gFlag + FL_DONE * 32) : "memory");
  }
}

typedef CUresult (*EncFn)(CUtensorMap*, CUtensorMapDataType, cuuint32_t, void*, const cuuint64_t*, const cuuint64_t*,
                          const cuuint32_t*, const cuuint32_t*, CUtensorMapInterleave, CUtensorMapSwizzle,
                          CUtensorMapL2promotion, CUtensorMapFloatOOBfill);

void make_map(EncFn enc, CUtensorMap* m, void* p, int rank, uint64_t d0, uint64_t d1, uint64_t d2, uint64_t s1, uint64_t s2,
              uint32_t b0, uint32_t b1, uint32_t b2, CUtensorMapSwizzle sw) {
  cuuint64_t dims[3] = {d0, d1, d2}, strides[2] = {s1, s2};
  cuuint32_t box[3] = {b0, b1, b2}, es[3] = {1, 1, 1};
  enc(m, CU_TENSOR_MAP_DATA_TYPE_BFLOAT16, rank, p, dims, strides, box, es, CU_TENSOR_MAP_INTERLEAVE_NONE, sw,
      CU_TENSOR_MAP_L2_PROMOTION_L2_128B, CU_TENSOR_MAP_FLOAT_OOB_FILL_NONE);
}

}

extern "C" void kernel_launch(void* const* d_in, const int* in_sizes, int n_in, void* d_out, int out_size) {
  static EncFn enc = nullptr;
  if (!enc) {
    cudaDriverEntryPointQueryResult st;
    void* fn = nullptr;
    cudaGetDriverEntryPoint("cuTensorMapEncodeTiled", &fn, cudaEnableDefault, &st);
    enc = (EncFn)fn;
    cudaFuncSetAttribute(fused_kernel, cudaFuncAttributeMaxDynamicSharedMemorySize, SMEM_BYTES);
  }
  CUtensorMap mQKV, mWO, mW1, mW2, mX;
  make_map(enc, &mQKV, d_in[1], 3, 448, 448, 3, 2688, 896, 64, 32, 3, CU_TENSOR_MAP_SWIZZLE_128B);
  make_map(enc, &mWO, d_in[3], 2, 448, 448, 1, 896, 0, 64, 112, 1, CU_TENSOR_MAP_SWIZZLE_128B);
  make_map(enc, &mW1, d_in[5], 3, 32, 448, 56, 3584, 64, 32, 32, 7, CU_TENSOR_MAP_SWIZZLE_64B);
  make_map(enc, &mW2, d_in[7], 2, 448, 1792, 1, 896, 0, 64, 112, 1, CU_TENSOR_MAP_SWIZZLE_128B);
  make_map(enc, &mX, d_in[0], 2, 448, 2048, 1, 896, 0, 64, 64, 1, CU_TENSOR_MAP_SWIZZLE_128B);
  fused_kernel<<<NCTA, 384, SMEM_BYTES, cudaStreamPerThread>>>(
      mQKV, mWO, mW1, mW2, mX, (const __nv_bfloat16*)d_in[0], (const __nv_bfloat16*)d_in[2], (const __nv_bfloat16*)d_in[6],
      (const __nv_bfloat16*)d_in[8], (const __nv_bfloat16*)d_in[1], (const __nv_bfloat16*)d_in[3], (const __nv_bfloat16*)d_in[5],
      (const __nv_bfloat16*)d_in[7], (__nv_bfloat16*)d_out);
}
```

```cpp
#include <cuda_runtime.h>
#include <cuda_bf16.h>
#include <cuda.h>
#include <stdint.h>

namespace {

constexpr int DM = 448, NCTA = 128;
constexpr int ABYTES = 57344;
constexpr int SLOT = 14336, NSLOT = 7;
constexpr int OFF_RING = 2 * ABYTES;
constexpr int OFF_WPHI = OFF_RING + NSLOT * SLOT;
constexpr int OFF_B1 = OFF_WPHI + 8192;
constexpr int OFF_CS = OFF_B1 + 896;
constexpr int OFF_ONE = OFF_CS + 1664;
constexpr int OFF_BAR = OFF_ONE + 512;
constexpr int SMEM_BYTES = OFF_BAR + 256 + 1024;
constexpr int TILES_PER_LAYER = 46;

__device__ __align__(1024) unsigned char gP[16 * 2 * 8 * 8 * 7168];
__device__ __align__(1024) unsigned char gImg[3 * 32 * ABYTES];
__device__ __align__(1024) float2 gStat[2 * 2048 * 8];
__device__ __align__(1024) float4 gKV[2 * 8 * 2 * 5 * 128];
__device__ __align__(1024) float4 gCS[8 * 16 * 104];
__device__ __align__(128) unsigned gFlag[(2 * 32 * 7 + 32 + 1 + 16) * 32];
#define STAMP(i)

__device__ __forceinline__ uint32_t smem_u32(const void* p) { return (uint32_t)__cvta_generic_to_shared(p); }
__device__ __forceinline__ void mbar_init(uint32_t b, int c) { asm volatile("mbarrier.init.shared::cta.b64 [%0], %1;" ::"r"(b), "r"(c)); }
__device__ __forceinline__ void mbar_expect(uint32_t b, int bytes) { asm volatile("mbarrier.arrive.expect_tx.shared::cta.b64 _, [%0], %1;" ::"r"(b), "r"(bytes) : "memory"); }
__device__ __forceinline__ void mbar_arrive(uint32_t b) { asm volatile("mbarrier.arrive.shared::cta.b64 _, [%0];" ::"r"(b) : "memory"); }
__device__ __forceinline__ void mbar_wait(uint32_t b, int par) {
  uint32_t ok; int n = 0;
  while (true) {
    asm volatile("{.reg .pred p; mbarrier.try_wait.parity.shared::cta.b64 p, [%1], %2; selp.u32 %0,1,0,p;}" : "=r"(ok) : "r"(b), "r"(par) : "memory");
    if (ok) break;
    if (++n > (1 << 22)) break;
  }
}
__device__ __forceinline__ void flag_wait(const unsigned* f, unsigned target) {
  unsigned v; int n = 0;
  while (true) {
    asm volatile("ld.acquire.gpu.global.u32 %0, [%1];" : "=r"(v) : "l"(f) : "memory");
    if ((int)(v - target) >= 0) break;
    if (++n > (1 << 21)) break;
  }
}
__device__ __forceinline__ void flag_arrive(unsigned* f) { asm volatile("red.release.gpu.global.add.u32 [%0], 1;" ::"l"(f) : "memory"); }
__device__ __forceinline__ void fence_async() { asm volatile("fence.proxy.async.global;" ::: "memory"); }
__device__ __forceinline__ void fence_async_smem() { asm volatile("fence.proxy.async.shared::cta;" ::: "memory"); }
template <int ID, int N> __device__ __forceinline__ void bar_sync() { asm volatile("bar.sync %0, %1;" ::"n"(ID), "n"(N) : "memory"); }
__device__ __forceinline__ void bar_wg(int c) { if (c) bar_sync<2, 128>(); else bar_sync<1, 128>(); }
__device__ __forceinline__ void wg_fence() { asm volatile("wgmma.fence.sync.aligned;" ::: "memory"); }
__device__ __forceinline__ void wg_commit() { asm volatile("wgmma.commit_group.sync.aligned;" ::: "memory"); }
template <int N> __device__ __forceinline__ void wg_wait() { asm volatile("wgmma.wait_group.sync.aligned %0;" ::"n"(N) : "memory"); }
template <int N> __device__ __forceinline__ void reg_fence(float (&d)[N]) {
#pragma unroll
  for (int i = 0; i < N; i++) asm volatile("" : "+f"(d[i])::"memory");
}
template <int N> __device__ __forceinline__ void reg_def(float (&d)[N]) {
#pragma unroll
  for (int i = 0; i < N; i++) d[i] = 0.f;
}
__device__ __forceinline__ uint64_t mkdesc(uint32_t addr, uint32_t lbo, uint32_t sbo, uint64_t swz) {
  return (uint64_t)((addr & 0x3FFFF) >> 4) | ((uint64_t)(lbo >> 4) << 16) | ((uint64_t)(sbo >> 4) << 32) | (swz << 62);
}
__device__ __forceinline__ uint32_t pack(float a, float b) {
  uint32_t r; asm("cvt.rn.bf16x2.f32 %0, %1, %2;" : "=r"(r) : "f"(b), "f"(a)); return r;
}
__device__ __forceinline__ float lo(uint32_t u) { return __uint_as_float(u << 16); }
__device__ __forceinline__ float hi(uint32_t u) { return __uint_as_float(u & 0xFFFF0000u); }
__device__ __forceinline__ float ex2(float x) { float y; asm("ex2.approx.ftz.f32 %0, %1;" : "=f"(y) : "f"(x)); return y; }
__device__ __forceinline__ void stsm4(uint32_t a, uint32_t r0, uint32_t r1, uint32_t r2, uint32_t r3) {
  asm volatile("stmatrix.sync.aligned.m8n8.x4.shared.b16 [%0], {%1,%2,%3,%4};" ::"r"(a), "r"(r0), "r"(r1), "r"(r2), "r"(r3) : "memory");
}
__device__ __forceinline__ void tma3(uint32_t dst, const CUtensorMap* m, int c0, int c1, int c2, uint32_t bar) {
  asm volatile("cp.async.bulk.tensor.3d.shared::cluster.global.mbarrier::complete_tx::bytes [%0], [%1, {%3,%4,%5}], [%2];"
               ::"r"(dst), "l"(m), "r"(bar), "r"(c0), "r"(c1), "r"(c2) : "memory");
}
__device__ __forceinline__ void tma2(uint32_t dst, const CUtensorMap* m, int c0, int c1, uint32_t bar) {
  asm volatile("cp.async.bulk.tensor.2d.shared::cluster.global.mbarrier::complete_tx::bytes [%0], [%1, {%3,%4}], [%2];"
               ::"r"(dst), "l"(m), "r"(bar), "r"(c0), "r"(c1) : "memory");
}
__device__ __forceinline__ uint32_t lds32(uint32_t a) { uint32_t v; asm volatile("ld.shared.u32 %0, [%1];" : "=r"(v) : "r"(a) : "memory"); return v; }
__device__ __forceinline__ void bulk_ld(uint32_t dst, const void* src, int bytes, uint32_t bar) {
  asm volatile("cp.async.bulk.shared::cluster.global.mbarrier::complete_tx::bytes [%0], [%1], %2, [%3];" ::"r"(dst), "l"(src), "r"(bytes), "r"(bar) : "memory");
}
__device__ __forceinline__ uint4 ldcg4(const void* p) {
  uint4 v; asm volatile("ld.global.cg.v4.u32 {%0,%1,%2,%3}, [%4];" : "=r"(v.x), "=r"(v.y), "=r"(v.z), "=r"(v.w) : "l"(p) : "memory"); return v;
}

__device__ __forceinline__ uint2 ldcg2(const void* p) {
  uint2 v; asm volatile("ld.global.cg.v2.u32 {%0,%1}, [%2];" : "=r"(v.x), "=r"(v.y) : "l"(p) : "memory"); return v;
}

__device__ __forceinline__ void mma_ss_184(float (&d)[92], uint64_t da, uint64_t db, int acc) {
  asm volatile("{.reg .pred p; setp.ne.b32 p, %94, 0;\n"
    "wgmma.mma_async.sync.aligned.m64n184k16.f32.bf16.bf16 {%0,%1,%2,%3,%4,%5,%6,%7,%8,%9,%10,%11,%12,%13,%14,%15,%16,%17,%18,%19,%20,%21,%22,%23,%24,%25,%26,%27,%28,%29,%30,%31,%32,%33,%34,%35,%36,%37,%38,%39,%40,%41,%42,%43,%44,%45,%46,%47,%48,%49,%50,%51,%52,%53,%54,%55,%56,%57,%58,%59,%60,%61,%62,%63,%64,%65,%66,%67,%68,%69,%70,%71,%72,%73,%74,%75,%76,%77,%78,%79,%80,%81,%82,%83,%84,%85,%86,%87,%88,%89,%90,%91}, %92, %93, p, 1, 1, 0, 1;}\n"
    : "+f"(d[0]),"+f"(d[1]),"+f"(d[2]),"+f"(d[3]),"+f"(d[4]),"+f"(d[5]),"+f"(d[6]),"+f"(d[7]),"+f"(d[8]),"+f"(d[9]),"+f"(d[10]),"+f"(d[11]),"+f"(d[12]),"+f"(d[13]),"+f"(d[14]),"+f"(d[15]),"+f"(d[16]),"+f"(d[17]),"+f"(d[18]),"+f"(d[19]),"+f"(d[20]),"+f"(d[21]),"+f"(d[22]),"+f"(d[23]),"+f"(d[24]),"+f"(d[25]),"+f"(d[26]),"+f"(d[27]),"+f"(d[28]),"+f"(d[29]),"+f"(d[30]),"+f"(d[31]),"+f"(d[32]),"+f"(d[33]),"+f"(d[34]),"+f"(d[35]),"+f"(d[36]),"+f"(d[37]),"+f"(d[38]),"+f"(d[39]),"+f"(d[40]),"+f"(d[41]),"+f"(d[42]),"+f"(d[43]),"+f"(d[44]),"+f"(d[45]),"+f"(d[46]),"+f"(d[47]),"+f"(d[48]),"+f"(d[49]),"+f"(d[50]),"+f"(d[51]),"+f"(d[52]),"+f"(d[53]),"+f"(d[54]),"+f"(d[55]),"+f"(d[56]),"+f"(d[57]),"+f"(d[58]),"+f"(d[59]),"+f"(d[60]),"+f"(d[61]),"+f"(d[62]),"+f"(d[63]),"+f"(d[64]),"+f"(d[65]),"+f"(d[66]),"+f"(d[67]),"+f"(d[68]),"+f"(d[69]),"+f"(d[70]),"+f"(d[71]),"+f"(d[72]),"+f"(d[73]),"+f"(d[74]),"+f"(d[75]),"+f"(d[76]),"+f"(d[77]),"+f"(d[78]),"+f"(d[79]),"+f"(d[80]),"+f"(d[81]),"+f"(d[82]),"+f"(d[83]),"+f"(d[84]),"+f"(d[85]),"+f"(d[86]),"+f"(d[87]),"+f"(d[88]),"+f"(d[89]),"+f"(d[90]),"+f"(d[91])
    : "l"(da), "l"(db), "r"(acc));
}
__device__ __forceinline__ void mma_ss_224(float (&d)[112], uint64_t da, uint64_t db, int acc) {
  asm volatile("{.reg .pred p; setp.ne.b32 p, %114, 0;\n"
    "wgmma.mma_async.sync.aligned.m64n224k16.f32.bf16.bf16 {%0,%1,%2,%3,%4,%5,%6,%7,%8,%9,%10,%11,%12,%13,%14,%15,%16,%17,%18,%19,%20,%21,%22,%23,%24,%25,%26,%27,%28,%29,%30,%31,%32,%33,%34,%35,%36,%37,%38,%39,%40,%41,%42,%43,%44,%45,%46,%47,%48,%49,%50,%51,%52,%53,%54,%55,%56,%57,%58,%59,%60,%61,%62,%63,%64,%65,%66,%67,%68,%69,%70,%71,%72,%73,%74,%75,%76,%77,%78,%79,%80,%81,%82,%83,%84,%85,%86,%87,%88,%89,%90,%91,%92,%93,%94,%95,%96,%97,%98,%99,%100,%101,%102,%103,%104,%105,%106,%107,%108,%109,%110,%111}, %112, %113, p, 1, 1, 0, 1;}\n"
    : "+f"(d[0]),"+f"(d[1]),"+f"(d[2]),"+f"(d[3]),"+f"(d[4]),"+f"(d[5]),"+f"(d[6]),"+f"(d[7]),"+f"(d[8]),"+f"(d[9]),"+f"(d[10]),"+f"(d[11]),"+f"(d[12]),"+f"(d[13]),"+f"(d[14]),"+f"(d[15]),"+f"(d[16]),"+f"(d[17]),"+f"(d[18]),"+f"(d[19]),"+f"(d[20]),"+f"(d[21]),"+f"(d[22]),"+f"(d[23]),"+f"(d[24]),"+f"(d[25]),"+f"(d[26]),"+f"(d[27]),"+f"(d[28]),"+f"(d[29]),"+f"(d[30]),"+f"(d[31]),"+f"(d[32]),"+f"(d[33]),"+f"(d[34]),"+f"(d[35]),"+f"(d[36]),"+f"(d[37]),"+f"(d[38]),"+f"(d[39]),"+f"(d[40]),"+f"(d[41]),"+f"(d[42]),"+f"(d[43]),"+f"(d[44]),"+f"(d[45]),"+f"(d[46]),"+f"(d[47]),"+f"(d[48]),"+f"(d[49]),"+f"(d[50]),"+f"(d[51]),"+f"(d[52]),"+f"(d[53]),"+f"(d[54]),"+f"(d[55]),"+f"(d[56]),"+f"(d[57]),"+f"(d[58]),"+f"(d[59]),"+f"(d[60]),"+f"(d[61]),"+f"(d[62]),"+f"(d[63]),"+f"(d[64]),"+f"(d[65]),"+f"(d[66]),"+f"(d[67]),"+f"(d[68]),"+f"(d[69]),"+f"(d[70]),"+f"(d[71]),"+f"(d[72]),"+f"(d[73]),"+f"(d[74]),"+f"(d[75]),"+f"(d[76]),"+f"(d[77]),"+f"(d[78]),"+f"(d[79]),"+f"(d[80]),"+f"(d[81]),"+f"(d[82]),"+f"(d[83]),"+f"(d[84]),"+f"(d[85]),"+f"(d[86]),"+f"(d[87]),"+f"(d[88]),"+f"(d[89]),"+f"(d[90]),"+f"(d[91]),"+f"(d[92]),"+f"(d[93]),"+f"(d[94]),"+f"(d[95]),"+f"(d[96]),"+f"(d[97]),"+f"(d[98]),"+f"(d[99]),"+f"(d[100]),"+f"(d[101]),"+f"(d[102]),"+f"(d[103]),"+f"(d[104]),"+f"(d[105]),"+f"(d[106]),"+f"(d[107]),"+f"(d[108]),"+f"(d[109]),"+f"(d[110]),"+f"(d[111])
    : "l"(da), "l"(db), "r"(acc));
}
__device__ __forceinline__ void mma_ss_56(float (&d)[28], uint64_t da, uint64_t db, int acc) {
  asm volatile("{.reg .pred p; setp.ne.b32 p, %30, 0;\n"
    "wgmma.mma_async.sync.aligned.m64n56k16.f32.bf16.bf16 {%0,%1,%2,%3,%4,%5,%6,%7,%8,%9,%10,%11,%12,%13,%14,%15,%16,%17,%18,%19,%20,%21,%22,%23,%24,%25,%26,%27}, %28, %29, p, 1, 1, 0, 1;}\n"
    : "+f"(d[0]),"+f"(d[1]),"+f"(d[2]),"+f"(d[3]),"+f"(d[4]),"+f"(d[5]),"+f"(d[6]),"+f"(d[7]),"+f"(d[8]),"+f"(d[9]),"+f"(d[10]),"+f"(d[11]),"+f"(d[12]),"+f"(d[13]),"+f"(d[14]),"+f"(d[15]),"+f"(d[16]),"+f"(d[17]),"+f"(d[18]),"+f"(d[19]),"+f"(d[20]),"+f"(d[21]),"+f"(d[22]),"+f"(d[23]),"+f"(d[24]),"+f"(d[25]),"+f"(d[26]),"+f"(d[27])
    : "l"(da), "l"(db), "r"(acc));
}
__device__ __forceinline__ void mma_rs_56(float (&d)[28], uint32_t a0, uint32_t a1, uint32_t a2, uint32_t a3, uint64_t db, int acc) {
  asm volatile("{.reg .pred p; setp.ne.b32 p, %33, 0;\n"
    "wgmma.mma_async.sync.aligned.m64n56k16.f32.bf16.bf16 {%0,%1,%2,%3,%4,%5,%6,%7,%8,%9,%10,%11,%12,%13,%14,%15,%16,%17,%18,%19,%20,%21,%22,%23,%24,%25,%26,%27}, {%28,%29,%30,%31}, %32, p, 1, 1, 1;}\n"
    : "+f"(d[0]),"+f"(d[1]),"+f"(d[2]),"+f"(d[3]),"+f"(d[4]),"+f"(d[5]),"+f"(d[6]),"+f"(d[7]),"+f"(d[8]),"+f"(d[9]),"+f"(d[10]),"+f"(d[11]),"+f"(d[12]),"+f"(d[13]),"+f"(d[14]),"+f"(d[15]),"+f"(d[16]),"+f"(d[17]),"+f"(d[18]),"+f"(d[19]),"+f"(d[20]),"+f"(d[21]),"+f"(d[22]),"+f"(d[23]),"+f"(d[24]),"+f"(d[25]),"+f"(d[26]),"+f"(d[27])
    : "r"(a0), "r"(a1), "r"(a2), "r"(a3), "l"(db), "r"(acc));
}
__device__ __forceinline__ void mma_ss_64t(float (&d)[32], uint64_t da, uint64_t db, int acc) {
  asm volatile("{.reg .pred p; setp.ne.b32 p, %34, 0;\n"
    "wgmma.mma_async.sync.aligned.m64n64k16.f32.bf16.bf16 {%0,%1,%2,%3,%4,%5,%6,%7,%8,%9,%10,%11,%12,%13,%14,%15,%16,%17,%18,%19,%20,%21,%22,%23,%24,%25,%26,%27,%28,%29,%30,%31}, %32, %33, p, 1, 1, 1, 1;}\n"
    : "+f"(d[0]),"+f"(d[1]),"+f"(d[2]),"+f"(d[3]),"+f"(d[4]),"+f"(d[5]),"+f"(d[6]),"+f"(d[7]),"+f"(d[8]),"+f"(d[9]),"+f"(d[10]),"+f"(d[11]),"+f"(d[12]),"+f"(d[13]),"+f"(d[14]),"+f"(d[15]),"+f"(d[16]),"+f"(d[17]),"+f"(d[18]),"+f"(d[19]),"+f"(d[20]),"+f"(d[21]),"+f"(d[22]),"+f"(d[23]),"+f"(d[24]),"+f"(d[25]),"+f"(d[26]),"+f"(d[27]),"+f"(d[28]),"+f"(d[29]),"+f"(d[30]),"+f"(d[31])
    : "l"(da), "l"(db), "r"(acc));
}
__device__ __forceinline__ void mma_rs_64(float (&d)[32], uint32_t a0, uint32_t a1, uint32_t a2, uint32_t a3, uint64_t db, int acc) {
  asm volatile("{.reg .pred p; setp.ne.b32 p, %37, 0;\n"
    "wgmma.mma_async.sync.aligned.m64n64k16.f32.bf16.bf16 {%0,%1,%2,%3,%4,%5,%6,%7,%8,%9,%10,%11,%12,%13,%14,%15,%16,%17,%18,%19,%20,%21,%22,%23,%24,%25,%26,%27,%28,%29,%30,%31}, {%32,%33,%34,%35}, %36, p, 1, 1, 1;}\n"
    : "+f"(d[0]),"+f"(d[1]),"+f"(d[2]),"+f"(d[3]),"+f"(d[4]),"+f"(d[5]),"+f"(d[6]),"+f"(d[7]),"+f"(d[8]),"+f"(d[9]),"+f"(d[10]),"+f"(d[11]),"+f"(d[12]),"+f"(d[13]),"+f"(d[14]),"+f"(d[15]),"+f"(d[16]),"+f"(d[17]),"+f"(d[18]),"+f"(d[19]),"+f"(d[20]),"+f"(d[21]),"+f"(d[22]),"+f"(d[23]),"+f"(d[24]),"+f"(d[25]),"+f"(d[26]),"+f"(d[27]),"+f"(d[28]),"+f"(d[29]),"+f"(d[30]),"+f"(d[31])
    : "r"(a0), "r"(a1), "r"(a2), "r"(a3), "l"(db), "r"(acc));
}
__device__ __forceinline__ void mma_ss_8t(float (&d)[4], uint64_t da, uint64_t db, int acc) {
  asm volatile("{.reg .pred p; setp.ne.b32 p, %6, 0;\n"
    "wgmma.mma_async.sync.aligned.m64n8k16.f32.bf16.bf16 {%0,%1,%2,%3}, %4, %5, p, 1, 1, 1, 0;}\n"
    : "+f"(d[0]),"+f"(d[1]),"+f"(d[2]),"+f"(d[3])
    : "l"(da), "l"(db), "r"(acc));
}

__device__ __forceinline__ void dual_softmax(const float (&p)[28], uint32_t (&phi)[4][7]) {
  constexpr float L2E = 1.4426950408889634f;
#pragma unroll
  for (int i = 0; i < 4; i++) {
    float mx = p[i], mn = p[i];
#pragma unroll
    for (int j = 1; j < 7; j++) { mx = fmaxf(mx, p[4 * j + i]); mn = fminf(mn, p[4 * j + i]); }
    mx = fmaxf(mx, __shfl_xor_sync(~0u, mx, 1)); mn = fminf(mn, __shfl_xor_sync(~0u, mn, 1));
    mx = fmaxf(mx, __shfl_xor_sync(~0u, mx, 2)); mn = fminf(mn, __shfl_xor_sync(~0u, mn, 2));
    float a[7], b[7], sa = 0.f, sb = 0.f;
    const float mxl = mx * L2E, mnl = mn * L2E;
#pragma unroll
    for (int j = 0; j < 7; j++) {
      a[j] = ex2(fmaf(p[4 * j + i], L2E, -mxl)); b[j] = ex2(fmaf(p[4 * j + i], -L2E, mnl));
      sa += a[j]; sb += b[j];
    }
    sa += __shfl_xor_sync(~0u, sa, 1); sb += __shfl_xor_sync(~0u, sb, 1);
    sa += __shfl_xor_sync(~0u, sa, 2); sb += __shfl_xor_sync(~0u, sb, 2);
    const float ra = __fdividef(1.f, sa), rb = __fdividef(1.f, sb);
#pragma unroll
    for (int j = 0; j < 7; j++) phi[i][j] = pack(a[j] * ra, b[j] * rb);
  }
}

struct Ring {
  uint32_t full, empty, base; int slot, par;
  __device__ __forceinline__ uint32_t acquire() { mbar_wait(full + slot * 8, par); return base + slot * SLOT; }
  __device__ __forceinline__ int advance() { int s = slot; if (++slot == NSLOT) { slot = 0; par ^= 1; } return s; }
  __device__ __forceinline__ void release(int s, bool elect) { if (elect) mbar_arrive(empty + s * 8); }
};
constexpr int FL_KV = 448, FL_CS = FL_KV + 16, FL_DONE = FL_KV + 32;

__global__ void __launch_bounds__(384, 1)
fused_kernel(const __grid_constant__ CUtensorMap mQKV, const __grid_constant__ CUtensorMap mWO,
             const __grid_constant__ CUtensorMap mW1, const __grid_constant__ CUtensorMap mW2,
             const __grid_constant__ CUtensorMap mX,
             const __nv_bfloat16* __restrict__ x, const __nv_bfloat16* __restrict__ wphi,
             const __nv_bfloat16* __restrict__ b1, const __nv_bfloat16* __restrict__ b2,
             const __nv_bfloat16* __restrict__ wqkv, const __nv_bfloat16* __restrict__ wo, const __nv_bfloat16* __restrict__ w1,
             const __nv_bfloat16* __restrict__ w2, __nv_bfloat16* __restrict__ out) {
  extern __shared__ unsigned char smem_raw[];
  const uint32_t sb = (smem_u32(smem_raw) + 1023) & ~1023u;
  unsigned char* sg = smem_raw + (sb - smem_u32(smem_raw));
  const int tid = threadIdx.x, lane = tid & 31;
  const int G = blockIdx.x >> 3, r = blockIdx.x & 7;
  const uint32_t barFull = sb + OFF_BAR, barEmpty = barFull + 56, barA = barEmpty + 56, barCS = barA + 112;
  if (tid >= 256 && tid < 288) {
    if (lane < 30) mbar_init(barFull + lane * 8, lane >= 28 ? 96 : (lane >= 7 && lane < 14 ? 2 : 1));
    asm volatile("fence.mbarrier_init.release.cluster;" ::: "memory");
  }
  __syncthreads();
  const int wgid = __shfl_sync(~0u, tid >> 7, 0);
  if (wgid == 2) {
    if (tid < 288) {
    if (lane < 14) {
        const int k = lane >> 1, cc = lane & 1;
        mbar_expect(barA + (cc * 7 + k) * 8, 8192);
        tma2(sb + (cc * 7 + k) * 8192, &mX, 64 * k, G * 128 + 64 * cc, barA + (cc * 7 + k) * 8);
      } else if (lane < 21) {
        const int i = lane - 14;
        mbar_expect(barFull + i * 8, 12288);
        tma3(sb + OFF_RING + i * SLOT, &mQKV, 56 * r, 32 * i, 0, barFull + i * 8);
      }
    }
    __syncwarp();
    asm volatile("setmaxnreg.dec.sync.aligned.u32 56;");
    if (tid == 256) {
      int slot = 0, par = 0;
      for (int it = NSLOT; it < 2 * TILES_PER_LAYER; it++) {
        const int i = it >= TILES_PER_LAYER ? it - TILES_PER_LAYER : it;
        mbar_wait(barEmpty + slot * 8, par);
        const uint32_t dst = sb + OFF_RING + slot * SLOT, fb = barFull + slot * 8;
        mbar_expect(fb, i < 14 ? 12288 : SLOT);
        if (i < 14) tma3(dst, &mQKV, 56 * r, 32 * i, 0, fb);
        else if (i < 18) tma2(dst, &mWO, 56 * r, 112 * (i - 14), fb);
        else if (i < 32) tma3(dst, &mW1, 0, 32 * (i - 18), 7 * r, fb);
        else tma2(dst, &mW2, 64 * ((i - 32) >> 1), 224 * r + 112 * (i & 1), fb);
        if (++slot == NSLOT) { slot = 0; par ^= 1; }
      }
    } else if (tid >= 288) {
      unsigned ep;
      asm volatile("ld.relaxed.gpu.global.u32 %0, [%1];" : "=r"(ep) : "l"(gFlag + FL_DONE * 32) : "memory");
      const int idx = tid - 288;
      ep = (ep / NCTA + 1) * 3;
      if (G == 0) {
#pragma unroll 1
        for (int i = idx; i < 2 * 1280; i += 96) gKV[((i >= 1280) * 7 + r) * 1280 + i] = make_float4(0.f, 0.f, 0.f, 0.f);
        __syncwarp();
        if (lane == 0) flag_arrive(gFlag + (FL_CS + r) * 32);
      }
      mbar_wait(barFull + 48, 0);
      if (idx < 2) {
        const char* pf = idx ? (const char*)w2 + blockIdx.x * 12544 : (const char*)wo + blockIdx.x * 3136;
        asm volatile("cp.async.bulk.prefetch.L2.global [%0], %1;" ::"l"(pf), "r"(idx ? 12544 : 3136) : "memory");
      }
      if (lane == 0) flag_wait(gFlag + (FL_CS + r) * 32, ep);
      __syncwarp();
      mbar_arrive(barCS);
#pragma unroll 1
      for (int ps = 0; ps < 2; ps++) {
        const int ch = ps * 14 + min(idx >> 2, 13);
        const uint4* src = reinterpret_cast<const uint4*>(w1 + (size_t)(G * 28 + (idx & 3) * 7) * 1792 + 224 * r) + ch;
        uint4 cu[7];
#pragma unroll
        for (int i = 0; i < 7; i++) cu[i] = __ldg(src + i * 224);
        float s[8] = {};
#pragma unroll
        for (int i = 0; i < 7; i++) { s[0] += lo(cu[i].x); s[1] += hi(cu[i].x); s[2] += lo(cu[i].y); s[3] += hi(cu[i].y); s[4] += lo(cu[i].z); s[5] += hi(cu[i].z); s[6] += lo(cu[i].w); s[7] += hi(cu[i].w); }
#pragma unroll
        for (int i = 0; i < 8; i++) { s[i] += __shfl_xor_sync(~0u, s[i], 1); s[i] += __shfl_xor_sync(~0u, s[i], 2); }
        if ((idx & 3) < 2 && idx < 56) gCS[(r * 16 + G) * 56 + ch * 2 + (idx & 1)] = (idx & 1) ? make_float4(s[4], s[5], s[6], s[7]) : make_float4(s[0], s[1], s[2], s[3]);
      }
      __syncwarp();
      if (lane == 0) { flag_arrive(gFlag + (FL_CS + 8 + r) * 32); flag_wait(gFlag + (FL_CS + 8 + r) * 32, ep * 16); }
      __syncwarp();
#pragma unroll 1
      for (int j = idx; j < 112; j += 96) {
        float2 v[16], a = make_float2(0.f, 0.f);
#pragma unroll
        for (int i = 0; i < 16; i++) v[i] = __ldcg(reinterpret_cast<const float2*>(gCS + (r * 16 + i) * 56) + j);
#pragma unroll
        for (int i = 0; i < 16; i++) { a.x += v[i].x; a.y += v[i].y; }
        reinterpret_cast<float2*>(sg + OFF_CS + 768)[j] = a;
      }
      mbar_arrive(barCS + 8);
    }
  } else {
  const int c = wgid, w = (tid >> 5) & 3, g = lane >> 2, t = lane & 3;
  const bool elect = (tid & 127) == 0;
  const uint32_t abuf = sb + c * ABYTES, barAc = barA + c * 56;
  const int row0 = G * 128 + c * 64;
  unsigned epoch;
  asm volatile("ld.relaxed.gpu.global.u32 %0, [%1];" : "=r"(epoch) : "l"(gFlag + FL_DONE * 32) : "memory");
  STAMP(24);
  float mean[2], rstd[2];
  uint32_t wv[7];
#pragma unroll
  for (int i = 0; i < 7; i++)
    wv[i] = __ldg(reinterpret_cast<const unsigned short*>(wphi) + (56 * r + i * 8 + (tid >> 5)) * 28 + min(lane, 27));
  const uint32_t bv = __ldg(reinterpret_cast<const unsigned short*>(b1) + 224 * r + min(tid, 223));
  uint4 su[2];
  {
    float sh[2] = {0.f, 0.f}, s1[2] = {0.f, 0.f}, s2[2] = {0.f, 0.f};
#pragma unroll 1
    for (int k = 0; k < 7; k++) {
      mbar_wait(barAc + k * 8, 0);
#pragma unroll
      for (int i = 0; i < 4; i++) {
        const int hh = i >> 1;
        const uint4 u = *reinterpret_cast<const uint4*>(sg + c * ABYTES + k * 8192 + (w * 16 + hh * 8 + g) * 128 + ((((i ^ g) & 1) * 4 + t) << 4));
        if (k == 0 && !(i & 1)) sh[hh] = lo(u.x);
        const uint32_t e[4] = {u.x, u.y, u.z, u.w};
#pragma unroll
        for (int z = 0; z < 4; z++) { const float a = lo(e[z]) - sh[hh], b = hi(e[z]) - sh[hh]; s1[hh] += a + b; s2[hh] = fmaf(a, a, fmaf(b, b, s2[hh])); }
      }
    }
#pragma unroll
    for (int hh = 0; hh < 2; hh++) {
      const float d = s1[hh] * (1.f / 112.f), m = sh[hh] + d, q = 0.5f * fmaxf(s2[hh] - d * s1[hh], 0.f);
      su[hh] = make_uint4(__float_as_uint(m), __float_as_uint(q), __float_as_uint(m), __float_as_uint(q));
    }
#pragma unroll
    for (int i = 0; i < 8; i++) {
      const int k = i * 8 + (tid >> 5);
      *reinterpret_cast<uint32_t*>(sg + OFF_WPHI + k * 128 + ((g ^ (k & 7)) << 4) + t * 4) = (i < 7 && lane < 28) ? wv[i % 7] << (k >= 28 ? 16 : 0) : 0u;
    }
    if (tid < 224) reinterpret_cast<uint32_t*>(sg + OFF_B1)[tid] = bv << 16;
    if (tid < 192) reinterpret_cast<float*>(sg + OFF_CS)[tid] = 0.f;
    if (tid < 128) reinterpret_cast<uint32_t*>(sg + OFF_ONE)[tid] = 0x3F803F80u;
    fence_async_smem();
    bar_sync<3, 256>();
    epoch = epoch / NCTA + 1;
  }
  asm volatile("setmaxnreg.inc.sync.aligned.u32 224;");
  STAMP(0);
  Ring ring{barFull, barEmpty, sb + OFF_RING, 0, 0};
  int apar = 0;
  const uint32_t stsm_off = (w * 16 + ((lane >> 3) & 1) * 8 + (lane & 7)) * 128;
  const uint32_t stsm_hi = lane >> 4;
  const uint64_t dA = mkdesc(abuf, 1024, 128, 0);

  auto gather = [&](unsigned* fl, const unsigned char* img) {
    __syncwarp();
    if (lane == 0) flag_arrive(fl);
    if (w == 0) {
      STAMP(27);
      if (lane == 0) flag_wait(fl, epoch * 32);
      __syncwarp();
      STAMP(28);
      if (lane < 7) { fence_async(); mbar_expect(barAc + lane * 8, 8192); bulk_ld(abuf + lane * 8192, img + lane * 8192, 8192, barAc + lane * 8); }
    }
    __syncwarp();
    apar ^= 1;
  };
  auto slice_off = [&](int j, int hh) -> uint32_t {
    return (7 * r + j) * 1024 + (w * 2 + hh) * 128 + lane * 4;
  };
  auto load_stats = [&](const float2* st) {
    mbar_wait(barAc, apar);
#pragma unroll
    for (int hh = 0; hh < 2; hh++) su[hh] = ldcg4(st + (size_t)(row0 + w * 16 + hh * 8 + g) * 8 + 2 * t);
  };
  auto finish_stats = [&]() {
#pragma unroll
    for (int hh = 0; hh < 2; hh++) {
      const float m0 = __uint_as_float(su[hh].x), m1 = __uint_as_float(su[hh].z);
      float m = m0 + m1;
      m += __shfl_xor_sync(~0u, m, 1); m += __shfl_xor_sync(~0u, m, 2);
      m *= 0.125f;
      float q = __uint_as_float(su[hh].y) + __uint_as_float(su[hh].w) + 56.f * ((m0 - m) * (m0 - m) + (m1 - m) * (m1 - m));
      q += __shfl_xor_sync(~0u, q, 1); q += __shfl_xor_sync(~0u, q, 2);
      mean[hh] = m; rstd[hh] = rsqrtf(q * (1.f / DM) + 1e-5f);
    }
  };

#pragma unroll 1
  for (int layer = 0; layer < 2; layer++) {
    unsigned* const fl = gFlag + (layer * 32 + G * 2 + c) * 7 * 32;
    uint32_t phiq[4][7], xs[7][2];
    {
      float acc[92]; reg_def(acc);
      int prev = 0;
      if (layer == 0) {
        const uint64_t dX = mkdesc(abuf, 16, 1024, 1), dOne = mkdesc(sb + OFF_ONE, 128, 128, 0);
        float cq[4], ck[4], cv[4]; reg_def(cq); reg_def(ck); reg_def(cv);
#pragma unroll 1
        for (int st = 0; st < 14; st++) {
          const uint64_t da = dX + (st >> 1) * 512 + (st & 1) * 4, db = mkdesc(ring.acquire(), 4096, 1024, 1);
          wg_fence();
          mma_ss_184(acc, da, db, 1);
          mma_ss_184(acc, da + 2, db + 128, 1);
          mma_ss_8t(cq, db + c * 128, dOne, 1); mma_ss_8t(ck, db + 256 + c * 128, dOne, 1); mma_ss_8t(cv, db + 512 + c * 128, dOne, 1);
          wg_commit();
          if (st > 0) { wg_wait<1>(); ring.release(prev, elect); }
          prev = ring.advance();
        }
        wg_wait<0>(); reg_fence(cq); reg_fence(ck); reg_fence(cv);
        float* cs = reinterpret_cast<float*>(sg + OFF_CS) + w * 16 + g + (t & 1) * 8;
        if (t < 2) { atomicAdd(cs, t ? cq[2] : cq[0]); atomicAdd(cs + 64, t ? ck[2] : ck[0]); atomicAdd(cs + 128, t ? cv[2] : cv[0]); }
        bar_sync<3, 256>();
      } else {
        load_stats(gStat + 2048 * 8);
#pragma unroll 1
        for (int st = 0; st < 14; st++) {
          if (!(st & 1)) mbar_wait(barAc + (st >> 1) * 8, apar);
          const uint64_t da = dA + st * 256, db = mkdesc(ring.acquire(), 4096, 1024, 1);
          wg_fence();
          mma_ss_184(acc, da, db, 1);
          mma_ss_184(acc, da + 128, db + 128, 1);
          wg_commit();
          if (st > 0) { wg_wait<1>(); ring.release(prev, elect); }
          prev = ring.advance();
        }
      }
      finish_stats();
      if (layer == 0) STAMP(25);
#pragma unroll
      for (int j = 0; j < 7; j++) {
        const int ci = 7 * r + j;
        const uint32_t a = abuf + (layer ? slice_off(j, 0) : (ci >> 3) * 8192 + (w * 16 + g) * 128 + (((ci & 7) ^ g) << 4) + t * 4);
        xs[j][0] = lds32(a); xs[j][1] = lds32(a + (layer ? 128 : 1024));
      }
      wg_wait<0>(); reg_fence(acc);
      ring.release(prev, elect);
      STAMP(1 + layer * 12);
      uint32_t f[3][14];
      {
        const float2* cs = reinterpret_cast<const float2*>(sg + OFF_CS) + t;
        const float mr0 = -mean[0] * rstd[0], mr1 = -mean[1] * rstd[1];
#pragma unroll
        for (int p = 0; p < 3; p++)
#pragma unroll
          for (int j = 0; j < 7; j++) {
            const float2 s = cs[p * 32 + j * 4];
            const int b = p * 32 + j * 4;
            f[p][2 * j] = pack(fmaf(acc[b], rstd[0], s.x * mr0), fmaf(acc[b + 1], rstd[0], s.y * mr0));
            f[p][2 * j + 1] = pack(fmaf(acc[b + 2], rstd[1], s.x * mr1), fmaf(acc[b + 3], rstd[1], s.y * mr1));
          }
      }
      float pk[28], pq[28]; reg_def(pk); reg_def(pq);
      const uint64_t dW = mkdesc(sb + OFF_WPHI, 4096, 1024, 1);
      wg_fence();
#pragma unroll
      for (int s = 0; s < 4; s++)
        mma_rs_56(pk, f[1][4 * s], f[1][4 * s + 1], s < 3 ? f[1][(4 * s + 2) % 14] : 0u, s < 3 ? f[1][(4 * s + 3) % 14] : 0u, dW + s * 128, s);
      wg_commit();
#pragma unroll
      for (int s = 0; s < 4; s++)
        mma_rs_56(pq, f[0][4 * s], f[0][4 * s + 1], s < 3 ? f[0][(4 * s + 2) % 14] : 0u, s < 3 ? f[0][(4 * s + 3) % 14] : 0u, dW + s * 128, s);
      wg_commit();
      bar_wg(c);
      const uint32_t srow = abuf + stsm_off, ones = t == 0 ? 0x3F803F80u : 0u;
#pragma unroll
      for (int jp = 0; jp < 4; jp++)
        stsm4(srow + 16384 + (((2 * jp + stsm_hi) ^ (lane & 7)) << 4), f[2][4 * jp], f[2][4 * jp + 1],
              jp < 3 ? f[2][(4 * jp + 2) % 14] : ones, jp < 3 ? f[2][(4 * jp + 3) % 14] : ones);
      wg_wait<0>(); reg_fence(pk); reg_fence(pq);
#pragma unroll 1
      for (int pass = 0; pass < 2; pass++) {
        dual_softmax(pk, phiq);
        if (pass) break;
#pragma unroll
        for (int e = 0; e < 2; e++)
#pragma unroll
          for (int jp = 0; jp < 4; jp++)
            stsm4(srow + e * 8192 + (((2 * jp + stsm_hi) ^ (lane & 7)) << 4), phiq[e][2 * jp], phiq[2 + e][2 * jp],
                  jp < 3 ? phiq[e][(2 * jp + 1) % 7] : 0u, jp < 3 ? phiq[2 + e][(2 * jp + 1) % 7] : 0u);
        fence_async_smem();
        bar_sync<3, 256>();
        float kv[32]; reg_def(kv);
        const uint64_t dP = mkdesc(sb + c * 8192, 4096, 1024, 1), dV = mkdesc(sb + 16384, 4096, 1024, 1);
        wg_fence();
#pragma unroll
        for (int s = 0; s < 8; s++) mma_ss_64t(kv, dP + (s >> 2) * (ABYTES / 16) + (s & 3) * 128, dV + (s >> 2) * (ABYTES / 16) + (s & 3) * 128, s);
        wg_commit();
        mbar_wait(barCS, 0);
        wg_wait<0>(); reg_fence(kv);
        float4* kvg = gKV + ((layer * 8 + r) * 2 + c) * 640 + (tid & 127);
#pragma unroll
        for (int i = 0; i < 5; i++) {
          float v0, v1, v2, v3;
          if (i == 4) { v0 = kv[28]; v1 = kv[29]; v2 = kv[30]; v3 = kv[31]; }
          else { v0 = c ? kv[12 + 4 * i] : kv[4 * i]; v1 = c ? kv[13 + 4 * i] : kv[1 + 4 * i]; v2 = c ? kv[14 + 4 * i] : kv[2 + 4 * i]; v3 = c ? kv[15 + 4 * i] : kv[3 + 4 * i]; }
          const bool use = i == 4 ? t == 0 : (i == 0 ? (c == 0 || t >= 2) : (i == 3 ? (c == 1 || t < 2) : true));
          if (use) asm volatile("red.relaxed.gpu.global.add.v4.f32 [%0], {%1,%2,%3,%4};" ::"l"(kvg + i * 128), "f"(v0), "f"(v1), "f"(v2), "f"(v3) : "memory");
        }
        __syncwarp();
        if (lane == 0) flag_arrive(gFlag + (FL_KV + layer * 8 + r) * 32);
        __syncwarp();
        STAMP(2 + layer * 12);
#pragma unroll
        for (int i = 0; i < 28; i++) pk[i] = pq[i];
      }
    }
    {
      if (elect) flag_wait(gFlag + (FL_KV + layer * 8 + r) * 32, epoch * 128);
      bar_wg(c);
      STAMP(3 + layer * 12);
      const float4* kvg = gKV + (layer * 8 + r) * 1280 + (tid & 127);
      uint4 kk[2][5];
#pragma unroll
      for (int e = 0; e < 2; e++)
#pragma unroll
        for (int i = 0; i < 5; i++) kk[e][i] = ldcg4(kvg + e * 640 + i * 128);
      const uint32_t srow = abuf + 24576 + stsm_off;
#pragma unroll
      for (int e = 0; e < 2; e++) {
        uint32_t f[8][2];
#pragma unroll
        for (int j = 0; j < 8; j++) { f[j][0] = 0u; f[j][1] = 0u; }
#pragma unroll
        for (int i = 0; i < 4; i++) {
          f[i + 3 * e][0] = pack(__uint_as_float(kk[e][i].x), __uint_as_float(kk[e][i].y));
          f[i + 3 * e][1] = pack(__uint_as_float(kk[e][i].z), __uint_as_float(kk[e][i].w));
        }
        f[7][0] = e ? pack(0.f, __uint_as_float(kk[e][4].y)) : pack(__uint_as_float(kk[e][4].x), 0.f);
        f[7][1] = e ? pack(0.f, __uint_as_float(kk[e][4].w)) : pack(__uint_as_float(kk[e][4].z), 0.f);
#pragma unroll
        for (int jp = 0; jp < 4; jp++)
          stsm4(srow + e * 8192 + (((2 * jp + stsm_hi) ^ (lane & 7)) << 4), f[2 * jp][0], f[2 * jp][1], f[2 * jp + 1][0], f[2 * jp + 1][1]);
      }
      fence_async_smem();
      bar_wg(c);
      float num[32]; reg_def(num);
      const uint64_t dK = mkdesc(abuf + 24576, 4096, 1024, 1);
      wg_fence();
#pragma unroll
      for (int e = 0; e < 2; e++)
#pragma unroll
        for (int s = 0; s < 4; s++)
          mma_rs_64(num, phiq[e][2 * s], phiq[2 + e][2 * s], s < 3 ? phiq[e][(2 * s + 1) % 7] : 0u, s < 3 ? phiq[2 + e][(2 * s + 1) % 7] : 0u,
                    dK + e * 512 + s * 128, e + s);
      wg_commit();
      wg_wait<0>(); reg_fence(num);
      float rd[4];
#pragma unroll
      for (int i = 0; i < 4; i++) rd[i] = __fdividef(1.f, __shfl_sync(~0u, num[28 + i], lane & ~3) + 1e-6f);
      unsigned char* img = gImg + (size_t)(G * 2 + c) * ABYTES;
#pragma unroll
      for (int j = 0; j < 7; j++) {
        const bool hb = j > 3 || (j == 3 && t >= 2);
        const float r0 = hb ? rd[1] : rd[0], r1 = hb ? rd[3] : rd[2];
        *reinterpret_cast<uint32_t*>(img + slice_off(j, 0)) = pack(num[4 * j] * r0, num[4 * j + 1] * r0);
        *reinterpret_cast<uint32_t*>(img + slice_off(j, 1)) = pack(num[4 * j + 2] * r1, num[4 * j + 3] * r1);
      }
      STAMP(4 + layer * 12);
      gather(fl, img);
      STAMP(5 + layer * 12);
    }
    {
      float acc[28]; reg_def(acc);
      int prev = 0;
#pragma unroll 1
      for (int st = 0; st < 4; st++) {
        mbar_wait(barAc + (st * 7 + 3) / 4 * 8, apar);
        mbar_wait(barAc + (st * 7 + 6) / 4 * 8, apar);
        const uint64_t db = mkdesc(ring.acquire(), 4096, 1024, 1);
        wg_fence();
#pragma unroll
        for (int s = 0; s < 7; s++) { const int ks = st * 7 + s; mma_ss_56(acc, dA + ks * 128, db + s * 128, ks); }
        wg_commit();
        if (st > 0) { wg_wait<1>(); ring.release(prev, elect); }
        prev = ring.advance();
      }
      wg_wait<0>(); reg_fence(acc);
      ring.release(prev, elect);
      unsigned char* img = gImg + (size_t)(32 + G * 2 + c) * ABYTES;
#pragma unroll
      for (int hh = 0; hh < 2; hh++) {
        float s = 0.f, q = 0.f;
#pragma unroll
        for (int j = 0; j < 7; j++) {
          xs[j][hh] = pack(lo(xs[j][hh]) + acc[4 * j + 2 * hh], hi(xs[j][hh]) + acc[4 * j + 2 * hh + 1]);
          *reinterpret_cast<uint32_t*>(img + slice_off(j, hh)) = xs[j][hh];
          s += lo(xs[j][hh]) + hi(xs[j][hh]);
        }
        s += __shfl_xor_sync(~0u, s, 1); s += __shfl_xor_sync(~0u, s, 2);
        s *= 1.f / 56.f;
#pragma unroll
        for (int j = 0; j < 7; j++) { const float a = lo(xs[j][hh]) - s, b = hi(xs[j][hh]) - s; q = fmaf(a, a, q); q = fmaf(b, b, q); }
        q += __shfl_xor_sync(~0u, q, 1); q += __shfl_xor_sync(~0u, q, 2);
        if (t == 0) gStat[(size_t)(row0 + w * 16 + hh * 8 + g) * 8 + r] = make_float2(s, q);
      }
      STAMP(6 + layer * 12);
      gather(fl + 32, img);
      STAMP(7 + layer * 12);
    }
    {
      uint32_t hf[28][2];
      {
        float acc[112]; reg_def(acc);
        int prev = 0;
        load_stats(gStat);
#pragma unroll 1
        for (int st = 0; st < 14; st++) {
          if (!(st & 1)) mbar_wait(barAc + (st >> 1) * 8, apar);
          const uint64_t da = dA + st * 256, db = mkdesc(ring.acquire(), 2048, 512, 2);
          wg_fence();
          mma_ss_224(acc, da, db, st);
          mma_ss_224(acc, da + 128, db + 64, 1);
          wg_commit();
          if (st > 0) { wg_wait<1>(); ring.release(prev, elect); }
          prev = ring.advance();
        }
        finish_stats();
        mbar_wait(barCS + 8, 0);
        wg_wait<0>(); reg_fence(acc);
        ring.release(prev, elect);
        STAMP(8 + layer * 12);
        const float2* bs = reinterpret_cast<const float2*>(sg + OFF_B1) + t;
        const float2* cs = reinterpret_cast<const float2*>(sg + OFF_CS + 768) + t;
        const float mr0 = -mean[0] * rstd[0], mr1 = -mean[1] * rstd[1];
#pragma unroll
        for (int j = 0; j < 28; j++) {
          const float2 b = bs[4 * j], s = cs[4 * j];
          const float h0 = fmaxf(fmaf(acc[4 * j], rstd[0], fmaf(s.x, mr0, b.x)), 0.f), h1 = fmaxf(fmaf(acc[4 * j + 1], rstd[0], fmaf(s.y, mr0, b.y)), 0.f);
          const float h2 = fmaxf(fmaf(acc[4 * j + 2], rstd[1], fmaf(s.x, mr1, b.x)), 0.f), h3 = fmaxf(fmaf(acc[4 * j + 3], rstd[1], fmaf(s.y, mr1, b.y)), 0.f);
          hf[j][0] = pack(h0 * h0, h1 * h1); hf[j][1] = pack(h2 * h2, h3 * h3);
        }
      }
      unsigned char* pdst = gP + (size_t)(((G * 2 + c) * 8 + 2 * w) * 8 + r) * 7168 + lane * 8;
      uint2 pk[8] = {};
#pragma unroll 1
      for (int ch = 0; ch < 7; ch++) {
        float acc[32]; reg_def(acc);
        int sl0 = 0, sl1 = 0;
#pragma unroll
        for (int hk = 0; hk < 2; hk++) {
          const uint64_t db = mkdesc(ring.acquire(), 4096, 1024, 1);
          wg_fence();
#pragma unroll
          for (int s = 0; s < 7; s++) { const int ks = hk * 7 + s; mma_rs_64(acc, hf[2 * ks][0], hf[2 * ks][1], hf[2 * ks + 1][0], hf[2 * ks + 1][1], db + s * 128, ks); }
          wg_commit();
          if (hk) sl1 = ring.advance(); else sl0 = ring.advance();
        }
        if (ch > 0) {
#pragma unroll
          for (int i = 0; i < 8; i++) *reinterpret_cast<uint2*>(pdst + (i & 1) * (8 * 7168) + (i >> 1) * 256) = pk[i];
          pdst += 1024;
        }
        wg_wait<1>(); ring.release(sl0, elect);
        wg_wait<0>(); reg_fence(acc); ring.release(sl1, elect);
#pragma unroll
        for (int i = 0; i < 8; i++) {
          const int b = (i >> 1) * 8 + (i & 1) * 2;
          pk[i] = make_uint2(pack(acc[b], acc[b + 1]), pack(acc[b + 4], acc[b + 5]));
        }
      }
#pragma unroll
      for (int i = 0; i < 8; i++) *reinterpret_cast<uint2*>(pdst + (i & 1) * (8 * 7168) + (i >> 1) * 256) = pk[i];
      STAMP(9 + layer * 12);
    }
    {
      uint32_t bx[14];
#pragma unroll
      for (int j = 0; j < 14; j++) bx[j] = __ldg(reinterpret_cast<const uint32_t*>(b2 + w * 112 + j * 8 + 2 * t));
      __syncwarp();
      if (lane == 0) { flag_arrive(fl + (3 + w) * 32); flag_wait(fl + (3 + (r >> 1)) * 32, epoch * 8); }
      __syncwarp();
      STAMP(10 + layer * 12);
      const unsigned char* psrc = gP + (size_t)(((G * 2 + c) * 8 + r) * 8) * 7168 + w * 1792 + lane * 8;
      unsigned char* img = gImg + (size_t)(64 + G * 2 + c) * ABYTES;
      uint2 pv[8][7];
#pragma unroll
      for (int s = 0; s < 8; s++)
#pragma unroll
        for (int i = 0; i < 7; i++) pv[s][i] = ldcg2(psrc + s * 7168 + i * 256);
      const uint32_t off = w * 14336 + r * 128 + lane * 4;
      unsigned char* dst = layer ? reinterpret_cast<unsigned char*>(out + (size_t)(row0 + r * 8 + g) * DM + w * 112 + 2 * t) : img + off;
      float sm = 0.f, q = 0.f;
#pragma unroll
      for (int j = 0; j < 14; j++) {
        float y0 = lo(bx[j]), y1 = hi(bx[j]);
        const uint32_t xo = lds32(abuf + off + j * 1024);
        y0 += lo(xo); y1 += hi(xo);
#pragma unroll
        for (int s = 0; s < 8; s++) { const uint32_t u = (j & 1) ? pv[s][j >> 1].y : pv[s][j >> 1].x; y0 += lo(u); y1 += hi(u); }
        bx[j] = pack(y0, y1);
        *reinterpret_cast<uint32_t*>(dst + j * (layer ? 16 : 1024)) = bx[j];
        sm += lo(bx[j]) + hi(bx[j]);
      }
      if (layer) break;
      sm += __shfl_xor_sync(~0u, sm, 1); sm += __shfl_xor_sync(~0u, sm, 2);
      sm *= 1.f / 112.f;
#pragma unroll
      for (int j = 0; j < 14; j++) { const float a = lo(bx[j]) - sm, b = hi(bx[j]) - sm; q = fmaf(a, a, q); q = fmaf(b, b, q); }
      q += __shfl_xor_sync(~0u, q, 1); q += __shfl_xor_sync(~0u, q, 2);
      if (t < 2) gStat[(size_t)(2048 + row0 + r * 8 + g) * 8 + 2 * w + t] = make_float2(sm, q * 0.5f);
      STAMP(11);
      gather(fl + 64, img);
      STAMP(12);
    }
  }
  STAMP(30);
  if (tid == 0) asm volatile("red.relaxed.gpu.global.add.u32 [%0], 1;" ::"l"(gFlag + FL_DONE * 32) : "memory");
  }
}

typedef CUresult (*EncFn)(CUtensorMap*, CUtensorMapDataType, cuuint32_t, void*, const cuuint64_t*, const cuuint64_t*,
                          const cuuint32_t*, const cuuint32_t*, CUtensorMapInterleave, CUtensorMapSwizzle,
                          CUtensorMapL2promotion, CUtensorMapFloatOOBfill);

void make_map(EncFn enc, CUtensorMap* m, void* p, int rank, uint64_t d0, uint64_t d1, uint64_t d2, uint64_t s1, uint64_t s2,
              uint32_t b0, uint32_t b1, uint32_t b2, CUtensorMapSwizzle sw) {
  cuuint64_t dims[3] = {d0, d1, d2}, strides[2] = {s1, s2};
  cuuint32_t box[3] = {b0, b1, b2}, es[3] = {1, 1, 1};
  enc(m, CU_TENSOR_MAP_DATA_TYPE_BFLOAT16, rank, p, dims, strides, box, es, CU_TENSOR_MAP_INTERLEAVE_NONE, sw,
      CU_TENSOR_MAP_L2_PROMOTION_L2_128B, CU_TENSOR_MAP_FLOAT_OOB_FILL_NONE);
}

}

extern "C" void kernel_launch(void* const* d_in, const int* in_sizes, int n_in, void* d_out, int out_size) {
  static EncFn enc = nullptr;
  if (!enc) {
    cudaDriverEntryPointQueryResult st;
    void* fn = nullptr;
    cudaGetDriverEntryPoint("cuTensorMapEncodeTiled", &fn, cudaEnableDefault, &st);
    enc = (EncFn)fn;
    cudaFuncSetAttribute(fused_kernel, cudaFuncAttributeMaxDynamicSharedMemorySize, SMEM_BYTES);
  }
  CUtensorMap mQKV, mWO, mW1, mW2, mX;
  make_map(enc, &mQKV, d_in[1], 3, 448, 448, 3, 2688, 896, 64, 32, 3, CU_TENSOR_MAP_SWIZZLE_128B);
  make_map(enc, &mWO, d_in[3], 2, 448, 448, 1, 896, 0, 64, 112, 1, CU_TENSOR_MAP_SWIZZLE_128B);
  make_map(enc, &mW1, d_in[5], 3, 32, 448, 56, 3584, 64, 32, 32, 7, CU_TENSOR_MAP_SWIZZLE_64B);
  make_map(enc, &mW2, d_in[7], 2, 448, 1792, 1, 896, 0, 64, 112, 1, CU_TENSOR_MAP_SWIZZLE_128B);
  make_map(enc, &mX, d_in[0], 2, 448, 2048, 1, 896, 0, 64, 64, 1, CU_TENSOR_MAP_SWIZZLE_128B);
  fused_kernel<<<NCTA, 384, SMEM_BYTES, cudaStreamPerThread>>>(
      mQKV, mWO, mW1, mW2, mX, (const __nv_bfloat16*)d_in[0], (const __nv_bfloat16*)d_in[2], (const __nv_bfloat16*)d_in[6],
      (const __nv_bfloat16*)d_in[8], (const __nv_bfloat16*)d_in[1], (const __nv_bfloat16*)d_in[3], (const __nv_bfloat16*)d_in[5],
      (const __nv_bfloat16*)d_in[7], (__nv_bfloat16*)d_out);
}
```

```cpp
#include <cuda_runtime.h>
#include <cuda_bf16.h>
#include <cuda.h>
#include <stdint.h>

namespace {

constexpr int DM = 448, NCTA = 128;
constexpr int ABYTES = 57344;
constexpr int SLOT = 14336, NSLOT = 7;
constexpr int OFF_RING = 2 * ABYTES;
constexpr int OFF_WPHI = OFF_RING + NSLOT * SLOT;
constexpr int OFF_B1 = OFF_WPHI + 8192;
constexpr int OFF_CS = OFF_B1 + 896;
constexpr int OFF_ONE = OFF_CS + 1664;
constexpr int OFF_ST = OFF_ONE + 512;
constexpr int OFF_BAR = OFF_ST + 1024;
constexpr int SMEM_BYTES = OFF_BAR + 256 + 1024;
constexpr int TILES_PER_LAYER = 46;

__device__ __align__(1024) unsigned char gP[16 * 2 * 8 * 8 * 7168];
__device__ __align__(1024) unsigned char gImg[3 * 32 * ABYTES];
__device__ __align__(1024) float2 gStat[2 * 2048 * 8];
__device__ __align__(1024) float4 gKV[2 * 8 * 2 * 5 * 128];
__device__ __align__(1024) float4 gCS[8 * 16 * 104];
__device__ __align__(128) unsigned gFlag[(2 * 32 * 7 + 32 + 1 + 16) * 32];
#define STAMP(i)

__device__ __forceinline__ uint32_t smem_u32(const void* p) { return (uint32_t)__cvta_generic_to_shared(p); }
__device__ __forceinline__ void mbar_init(uint32_t b, int c) { asm volatile("mbarrier.init.shared::cta.b64 [%0], %1;" ::"r"(b), "r"(c)); }
__device__ __forceinline__ void mbar_expect(uint32_t b, int bytes) { asm volatile("mbarrier.arrive.expect_tx.shared::cta.b64 _, [%0], %1;" ::"r"(b), "r"(bytes) : "memory"); }
__device__ __forceinline__ void mbar_arrive(uint32_t b) { asm volatile("mbarrier.arrive.shared::cta.b64 _, [%0];" ::"r"(b) : "memory"); }
__device__ __forceinline__ void mbar_wait(uint32_t b, int par) {
  uint32_t ok; int n = 0;
  while (true) {
    asm volatile("{.reg .pred p; mbarrier.try_wait.parity.shared::cta.b64 p, [%1], %2; selp.u32 %0,1,0,p;}" : "=r"(ok) : "r"(b), "r"(par) : "memory");
    if (ok) break;
    if (++n > (1 << 22)) break;
  }
}
__device__ __forceinline__ void flag_wait(const unsigned* f, unsigned target) {
  unsigned v; int n = 0;
  while (true) {
    asm volatile("ld.acquire.gpu.global.u32 %0, [%1];" : "=r"(v) : "l"(f) : "memory");
    if ((int)(v - target) >= 0) break;
    if (++n > (1 << 21)) break;
  }
}
__device__ __forceinline__ void flag_arrive(unsigned* f) { asm volatile("red.release.gpu.global.add.u32 [%0], 1;" ::"l"(f) : "memory"); }
__device__ __forceinline__ void fence_async() { asm volatile("fence.proxy.async.global;" ::: "memory"); }
__device__ __forceinline__ void fence_async_smem() { asm volatile("fence.proxy.async.shared::cta;" ::: "memory"); }
template <int ID, int N> __device__ __forceinline__ void bar_sync() { asm volatile("bar.sync %0, %1;" ::"n"(ID), "n"(N) : "memory"); }
__device__ __forceinline__ void bar_wg(int c) { if (c) bar_sync<2, 128>(); else bar_sync<1, 128>(); }
__device__ __forceinline__ void wg_fence() { asm volatile("wgmma.fence.sync.aligned;" ::: "memory"); }
__device__ __forceinline__ void wg_commit() { asm volatile("wgmma.commit_group.sync.aligned;" ::: "memory"); }
template <int N> __device__ __forceinline__ void wg_wait() { asm volatile("wgmma.wait_group.sync.aligned %0;" ::"n"(N) : "memory"); }
template <int N> __device__ __forceinline__ void reg_fence(float (&d)[N]) {
#pragma unroll
  for (int i = 0; i < N; i++) asm volatile("" : "+f"(d[i])::"memory");
}
template <int N> __device__ __forceinline__ void reg_def(float (&d)[N]) {
#pragma unroll
  for (int i = 0; i < N; i++) d[i] = 0.f;
}
__device__ __forceinline__ uint64_t mkdesc(uint32_t addr, uint32_t lbo, uint32_t sbo, uint64_t swz) {
  return (uint64_t)((addr & 0x3FFFF) >> 4) | ((uint64_t)(lbo >> 4) << 16) | ((uint64_t)(sbo >> 4) << 32) | (swz << 62);
}
__device__ __forceinline__ uint32_t pack(float a, float b) {
  uint32_t r; asm("cvt.rn.bf16x2.f32 %0, %1, %2;" : "=r"(r) : "f"(b), "f"(a)); return r;
}
__device__ __forceinline__ float lo(uint32_t u) { return __uint_as_float(u << 16); }
__device__ __forceinline__ float hi(uint32_t u) { return __uint_as_float(u & 0xFFFF0000u); }
__device__ __forceinline__ float ex2(float x) { float y; asm("ex2.approx.ftz.f32 %0, %1;" : "=f"(y) : "f"(x)); return y; }
__device__ __forceinline__ void stsm4(uint32_t a, uint32_t r0, uint32_t r1, uint32_t r2, uint32_t r3) {
  asm volatile("stmatrix.sync.aligned.m8n8.x4.shared.b16 [%0], {%1,%2,%3,%4};" ::"r"(a), "r"(r0), "r"(r1), "r"(r2), "r"(r3) : "memory");
}
__device__ __forceinline__ void tma3(uint32_t dst, const CUtensorMap* m, int c0, int c1, int c2, uint32_t bar) {
  asm volatile("cp.async.bulk.tensor.3d.shared::cluster.global.mbarrier::complete_tx::bytes [%0], [%1, {%3,%4,%5}], [%2];"
               ::"r"(dst), "l"(m), "r"(bar), "r"(c0), "r"(c1), "r"(c2) : "memory");
}
__device__ __forceinline__ void tma2(uint32_t dst, const CUtensorMap* m, int c0, int c1, uint32_t bar) {
  asm volatile("cp.async.bulk.tensor.2d.shared::cluster.global.mbarrier::complete_tx::bytes [%0], [%1, {%3,%4}], [%2];"
               ::"r"(dst), "l"(m), "r"(bar), "r"(c0), "r"(c1) : "memory");
}
__device__ __forceinline__ uint32_t lds32(uint32_t a) { uint32_t v; asm volatile("ld.shared.u32 %0, [%1];" : "=r"(v) : "r"(a) : "memory"); return v; }
__device__ __forceinline__ void bulk_ld(uint32_t dst, const void* src, int bytes, uint32_t bar) {
  asm volatile("cp.async.bulk.shared::cluster.global.mbarrier::complete_tx::bytes [%0], [%1], %2, [%3];" ::"r"(dst), "l"(src), "r"(bytes), "r"(bar) : "memory");
}
__device__ __forceinline__ uint4 ldcg4(const void* p) {
  uint4 v; asm volatile("ld.global.cg.v4.u32 {%0,%1,%2,%3}, [%4];" : "=r"(v.x), "=r"(v.y), "=r"(v.z), "=r"(v.w) : "l"(p) : "memory"); return v;
}

__device__ __forceinline__ uint2 ldcg2(const void* p) {
  uint2 v; asm volatile("ld.global.cg.v2.u32 {%0,%1}, [%2];" : "=r"(v.x), "=r"(v.y) : "l"(p) : "memory"); return v;
}

__device__ __forceinline__ void mma_ss_184(float (&d)[92], uint64_t da, uint64_t db, int acc) {
  asm volatile("{.reg .pred p; setp.ne.b32 p, %94, 0;\n"
    "wgmma.mma_async.sync.aligned.m64n184k16.f32.bf16.bf16 {%0,%1,%2,%3,%4,%5,%6,%7,%8,%9,%10,%11,%12,%13,%14,%15,%16,%17,%18,%19,%20,%21,%22,%23,%24,%25,%26,%27,%28,%29,%30,%31,%32,%33,%34,%35,%36,%37,%38,%39,%40,%41,%42,%43,%44,%45,%46,%47,%48,%49,%50,%51,%52,%53,%54,%55,%56,%57,%58,%59,%60,%61,%62,%63,%64,%65,%66,%67,%68,%69,%70,%71,%72,%73,%74,%75,%76,%77,%78,%79,%80,%81,%82,%83,%84,%85,%86,%87,%88,%89,%90,%91}, %92, %93, p, 1, 1, 0, 1;}\n"
    : "+f"(d[0]),"+f"(d[1]),"+f"(d[2]),"+f"(d[3]),"+f"(d[4]),"+f"(d[5]),"+f"(d[6]),"+f"(d[7]),"+f"(d[8]),"+f"(d[9]),"+f"(d[10]),"+f"(d[11]),"+f"(d[12]),"+f"(d[13]),"+f"(d[14]),"+f"(d[15]),"+f"(d[16]),"+f"(d[17]),"+f"(d[18]),"+f"(d[19]),"+f"(d[20]),"+f"(d[21]),"+f"(d[22]),"+f"(d[23]),"+f"(d[24]),"+f"(d[25]),"+f"(d[26]),"+f"(d[27]),"+f"(d[28]),"+f"(d[29]),"+f"(d[30]),"+f"(d[31]),"+f"(d[32]),"+f"(d[33]),"+f"(d[34]),"+f"(d[35]),"+f"(d[36]),"+f"(d[37]),"+f"(d[38]),"+f"(d[39]),"+f"(d[40]),"+f"(d[41]),"+f"(d[42]),"+f"(d[43]),"+f"(d[44]),"+f"(d[45]),"+f"(d[46]),"+f"(d[47]),"+f"(d[48]),"+f"(d[49]),"+f"(d[50]),"+f"(d[51]),"+f"(d[52]),"+f"(d[53]),"+f"(d[54]),"+f"(d[55]),"+f"(d[56]),"+f"(d[57]),"+f"(d[58]),"+f"(d[59]),"+f"(d[60]),"+f"(d[61]),"+f"(d[62]),"+f"(d[63]),"+f"(d[64]),"+f"(d[65]),"+f"(d[66]),"+f"(d[67]),"+f"(d[68]),"+f"(d[69]),"+f"(d[70]),"+f"(d[71]),"+f"(d[72]),"+f"(d[73]),"+f"(d[74]),"+f"(d[75]),"+f"(d[76]),"+f"(d[77]),"+f"(d[78]),"+f"(d[79]),"+f"(d[80]),"+f"(d[81]),"+f"(d[82]),"+f"(d[83]),"+f"(d[84]),"+f"(d[85]),"+f"(d[86]),"+f"(d[87]),"+f"(d[88]),"+f"(d[89]),"+f"(d[90]),"+f"(d[91])
    : "l"(da), "l"(db), "r"(acc));
}
__device__ __forceinline__ void mma_ss_224(float (&d)[112], uint64_t da, uint64_t db, int acc) {
  asm volatile("{.reg .pred p; setp.ne.b32 p, %114, 0;\n"
    "wgmma.mma_async.sync.aligned.m64n224k16.f32.bf16.bf16 {%0,%1,%2,%3,%4,%5,%6,%7,%8,%9,%10,%11,%12,%13,%14,%15,%16,%17,%18,%19,%20,%21,%22,%23,%24,%25,%26,%27,%28,%29,%30,%31,%32,%33,%34,%35,%36,%37,%38,%39,%40,%41,%42,%43,%44,%45,%46,%47,%48,%49,%50,%51,%52,%53,%54,%55,%56,%57,%58,%59,%60,%61,%62,%63,%64,%65,%66,%67,%68,%69,%70,%71,%72,%73,%74,%75,%76,%77,%78,%79,%80,%81,%82,%83,%84,%85,%86,%87,%88,%89,%90,%91,%92,%93,%94,%95,%96,%97,%98,%99,%100,%101,%102,%103,%104,%105,%106,%107,%108,%109,%110,%111}, %112, %113, p, 1, 1, 0, 1;}\n"
    : "+f"(d[0]),"+f"(d[1]),"+f"(d[2]),"+f"(d[3]),"+f"(d[4]),"+f"(d[5]),"+f"(d[6]),"+f"(d[7]),"+f"(d[8]),"+f"(d[9]),"+f"(d[10]),"+f"(d[11]),"+f"(d[12]),"+f"(d[13]),"+f"(d[14]),"+f"(d[15]),"+f"(d[16]),"+f"(d[17]),"+f"(d[18]),"+f"(d[19]),"+f"(d[20]),"+f"(d[21]),"+f"(d[22]),"+f"(d[23]),"+f"(d[24]),"+f"(d[25]),"+f"(d[26]),"+f"(d[27]),"+f"(d[28]),"+f"(d[29]),"+f"(d[30]),"+f"(d[31]),"+f"(d[32]),"+f"(d[33]),"+f"(d[34]),"+f"(d[35]),"+f"(d[36]),"+f"(d[37]),"+f"(d[38]),"+f"(d[39]),"+f"(d[40]),"+f"(d[41]),"+f"(d[42]),"+f"(d[43]),"+f"(d[44]),"+f"(d[45]),"+f"(d[46]),"+f"(d[47]),"+f"(d[48]),"+f"(d[49]),"+f"(d[50]),"+f"(d[51]),"+f"(d[52]),"+f"(d[53]),"+f"(d[54]),"+f"(d[55]),"+f"(d[56]),"+f"(d[57]),"+f"(d[58]),"+f"(d[59]),"+f"(d[60]),"+f"(d[61]),"+f"(d[62]),"+f"(d[63]),"+f"(d[64]),"+f"(d[65]),"+f"(d[66]),"+f"(d[67]),"+f"(d[68]),"+f"(d[69]),"+f"(d[70]),"+f"(d[71]),"+f"(d[72]),"+f"(d[73]),"+f"(d[74]),"+f"(d[75]),"+f"(d[76]),"+f"(d[77]),"+f"(d[78]),"+f"(d[79]),"+f"(d[80]),"+f"(d[81]),"+f"(d[82]),"+f"(d[83]),"+f"(d[84]),"+f"(d[85]),"+f"(d[86]),"+f"(d[87]),"+f"(d[88]),"+f"(d[89]),"+f"(d[90]),"+f"(d[91]),"+f"(d[92]),"+f"(d[93]),"+f"(d[94]),"+f"(d[95]),"+f"(d[96]),"+f"(d[97]),"+f"(d[98]),"+f"(d[99]),"+f"(d[100]),"+f"(d[101]),"+f"(d[102]),"+f"(d[103]),"+f"(d[104]),"+f"(d[105]),"+f"(d[106]),"+f"(d[107]),"+f"(d[108]),"+f"(d[109]),"+f"(d[110]),"+f"(d[111])
    : "l"(da), "l"(db), "r"(acc));
}
__device__ __forceinline__ void mma_ss_56(float (&d)[28], uint64_t da, uint64_t db, int acc) {
  asm volatile("{.reg .pred p; setp.ne.b32 p, %30, 0;\n"
    "wgmma.mma_async.sync.aligned.m64n56k16.f32.bf16.bf16 {%0,%1,%2,%3,%4,%5,%6,%7,%8,%9,%10,%11,%12,%13,%14,%15,%16,%17,%18,%19,%20,%21,%22,%23,%24,%25,%26,%27}, %28, %29, p, 1, 1, 0, 1;}\n"
    : "+f"(d[0]),"+f"(d[1]),"+f"(d[2]),"+f"(d[3]),"+f"(d[4]),"+f"(d[5]),"+f"(d[6]),"+f"(d[7]),"+f"(d[8]),"+f"(d[9]),"+f"(d[10]),"+f"(d[11]),"+f"(d[12]),"+f"(d[13]),"+f"(d[14]),"+f"(d[15]),"+f"(d[16]),"+f"(d[17]),"+f"(d[18]),"+f"(d[19]),"+f"(d[20]),"+f"(d[21]),"+f"(d[22]),"+f"(d[23]),"+f"(d[24]),"+f"(d[25]),"+f"(d[26]),"+f"(d[27])
    : "l"(da), "l"(db), "r"(acc));
}
__device__ __forceinline__ void mma_rs_56(float (&d)[28], uint32_t a0, uint32_t a1, uint32_t a2, uint32_t a3, uint64_t db, int acc) {
  asm volatile("{.reg .pred p; setp.ne.b32 p, %33, 0;\n"
    "wgmma.mma_async.sync.aligned.m64n56k16.f32.bf16.bf16 {%0,%1,%2,%3,%4,%5,%6,%7,%8,%9,%10,%11,%12,%13,%14,%15,%16,%17,%18,%19,%20,%21,%22,%23,%24,%25,%26,%27}, {%28,%29,%30,%31}, %32, p, 1, 1, 1;}\n"
    : "+f"(d[0]),"+f"(d[1]),"+f"(d[2]),"+f"(d[3]),"+f"(d[4]),"+f"(d[5]),"+f"(d[6]),"+f"(d[7]),"+f"(d[8]),"+f"(d[9]),"+f"(d[10]),"+f"(d[11]),"+f"(d[12]),"+f"(d[13]),"+f"(d[14]),"+f"(d[15]),"+f"(d[16]),"+f"(d[17]),"+f"(d[18]),"+f"(d[19]),"+f"(d[20]),"+f"(d[21]),"+f"(d[22]),"+f"(d[23]),"+f"(d[24]),"+f"(d[25]),"+f"(d[26]),"+f"(d[27])
    : "r"(a0), "r"(a1), "r"(a2), "r"(a3), "l"(db), "r"(acc));
}
__device__ __forceinline__ void mma_ss_64t(float (&d)[32], uint64_t da, uint64_t db, int acc) {
  asm volatile("{.reg .pred p; setp.ne.b32 p, %34, 0;\n"
    "wgmma.mma_async.sync.aligned.m64n64k16.f32.bf16.bf16 {%0,%1,%2,%3,%4,%5,%6,%7,%8,%9,%10,%11,%12,%13,%14,%15,%16,%17,%18,%19,%20,%21,%22,%23,%24,%25,%26,%27,%28,%29,%30,%31}, %32, %33, p, 1, 1, 1, 1;}\n"
    : "+f"(d[0]),"+f"(d[1]),"+f"(d[2]),"+f"(d[3]),"+f"(d[4]),"+f"(d[5]),"+f"(d[6]),"+f"(d[7]),"+f"(d[8]),"+f"(d[9]),"+f"(d[10]),"+f"(d[11]),"+f"(d[12]),"+f"(d[13]),"+f"(d[14]),"+f"(d[15]),"+f"(d[16]),"+f"(d[17]),"+f"(d[18]),"+f"(d[19]),"+f"(d[20]),"+f"(d[21]),"+f"(d[22]),"+f"(d[23]),"+f"(d[24]),"+f"(d[25]),"+f"(d[26]),"+f"(d[27]),"+f"(d[28]),"+f"(d[29]),"+f"(d[30]),"+f"(d[31])
    : "l"(da), "l"(db), "r"(acc));
}
__device__ __forceinline__ void mma_rs_64(float (&d)[32], uint32_t a0, uint32_t a1, uint32_t a2, uint32_t a3, uint64_t db, int acc) {
  asm volatile("{.reg .pred p; setp.ne.b32 p, %37, 0;\n"
    "wgmma.mma_async.sync.aligned.m64n64k16.f32.bf16.bf16 {%0,%1,%2,%3,%4,%5,%6,%7,%8,%9,%10,%11,%12,%13,%14,%15,%16,%17,%18,%19,%20,%21,%22,%23,%24,%25,%26,%27,%28,%29,%30,%31}, {%32,%33,%34,%35}, %36, p, 1, 1, 1;}\n"
    : "+f"(d[0]),"+f"(d[1]),"+f"(d[2]),"+f"(d[3]),"+f"(d[4]),"+f"(d[5]),"+f"(d[6]),"+f"(d[7]),"+f"(d[8]),"+f"(d[9]),"+f"(d[10]),"+f"(d[11]),"+f"(d[12]),"+f"(d[13]),"+f"(d[14]),"+f"(d[15]),"+f"(d[16]),"+f"(d[17]),"+f"(d[18]),"+f"(d[19]),"+f"(d[20]),"+f"(d[21]),"+f"(d[22]),"+f"(d[23]),"+f"(d[24]),"+f"(d[25]),"+f"(d[26]),"+f"(d[27]),"+f"(d[28]),"+f"(d[29]),"+f"(d[30]),"+f"(d[31])
    : "r"(a0), "r"(a1), "r"(a2), "r"(a3), "l"(db), "r"(acc));
}
__device__ __forceinline__ void mma_ss_8t(float (&d)[4], uint64_t da, uint64_t db, int acc) {
  asm volatile("{.reg .pred p; setp.ne.b32 p, %6, 0;\n"
    "wgmma.mma_async.sync.aligned.m64n8k16.f32.bf16.bf16 {%0,%1,%2,%3}, %4, %5, p, 1, 1, 1, 0;}\n"
    : "+f"(d[0]),"+f"(d[1]),"+f"(d[2]),"+f"(d[3])
    : "l"(da), "l"(db), "r"(acc));
}

__device__ __forceinline__ void dual_softmax(const float (&p)[28], uint32_t (&phi)[4][7]) {
  constexpr float L2E = 1.4426950408889634f;
#pragma unroll
  for (int i = 0; i < 4; i++) {
    float mx = p[i], mn = p[i];
#pragma unroll
    for (int j = 1; j < 7; j++) { mx = fmaxf(mx, p[4 * j + i]); mn = fminf(mn, p[4 * j + i]); }
    mx = fmaxf(mx, __shfl_xor_sync(~0u, mx, 1)); mn = fminf(mn, __shfl_xor_sync(~0u, mn, 1));
    mx = fmaxf(mx, __shfl_xor_sync(~0u, mx, 2)); mn = fminf(mn, __shfl_xor_sync(~0u, mn, 2));
    float a[7], b[7], sa = 0.f, sb = 0.f;
    const float mxl = mx * L2E, mnl = mn * L2E;
#pragma unroll
    for (int j = 0; j < 7; j++) {
      a[j] = ex2(fmaf(p[4 * j + i], L2E, -mxl)); b[j] = ex2(fmaf(p[4 * j + i], -L2E, mnl));
      sa += a[j]; sb += b[j];
    }
    sa += __shfl_xor_sync(~0u, sa, 1); sb += __shfl_xor_sync(~0u, sb, 1);
    sa += __shfl_xor_sync(~0u, sa, 2); sb += __shfl_xor_sync(~0u, sb, 2);
    const float ra = __fdividef(1.f, sa), rb = __fdividef(1.f, sb);
#pragma unroll
    for (int j = 0; j < 7; j++) phi[i][j] = pack(a[j] * ra, b[j] * rb);
  }
}

struct Ring {
  uint32_t full, empty, base; int slot, par;
  __device__ __forceinline__ uint32_t acquire() { mbar_wait(full + slot * 8, par); return base + slot * SLOT; }
  __device__ __forceinline__ int advance() { int s = slot; if (++slot == NSLOT) { slot = 0; par ^= 1; } return s; }
  __device__ __forceinline__ void release(int s, bool elect) { if (elect) mbar_arrive(empty + s * 8); }
};
constexpr int FL_KV = 448, FL_CS = FL_KV + 16, FL_DONE = FL_KV + 32;

__global__ void __launch_bounds__(384, 1)
fused_kernel(const __grid_constant__ CUtensorMap mQKV, const __grid_constant__ CUtensorMap mWO,
             const __grid_constant__ CUtensorMap mW1, const __grid_constant__ CUtensorMap mW2,
             const __grid_constant__ CUtensorMap mX,
             const __nv_bfloat16* __restrict__ x, const __nv_bfloat16* __restrict__ wphi,
             const __nv_bfloat16* __restrict__ b1, const __nv_bfloat16* __restrict__ b2,
             const __nv_bfloat16* __restrict__ wqkv, const __nv_bfloat16* __restrict__ wo, const __nv_bfloat16* __restrict__ w1,
             const __nv_bfloat16* __restrict__ w2, __nv_bfloat16* __restrict__ out) {
  extern __shared__ unsigned char smem_raw[];
  const uint32_t sb = (smem_u32(smem_raw) + 1023) & ~1023u;
  unsigned char* sg = smem_raw + (sb - smem_u32(smem_raw));
  const int tid = threadIdx.x, lane = tid & 31;
  const int G = blockIdx.x >> 3, r = blockIdx.x & 7;
  const uint32_t barFull = sb + OFF_BAR, barEmpty = barFull + 56, barA = barEmpty + 56, barCS = barA + 112;
  const int warp = __shfl_sync(~0u, tid >> 5, 0);
  if (lane == 0) {
    if (warp < 7) { mbar_init(barFull + warp * 8, 1); mbar_init(barEmpty + warp * 8, 2); mbar_init(barA + warp * 8, 1); mbar_init(barA + 56 + warp * 8, 1); }
    else if (warp < 10) mbar_init(barCS + (warp - 7) * 8, 96);
    asm volatile("fence.mbarrier_init.release.cluster;" ::: "memory");
  }
  if (tid < 192) reinterpret_cast<float*>(sg + OFF_CS)[tid] = 0.f;
  if (tid < 128) reinterpret_cast<uint32_t*>(sg + OFF_ONE)[tid] = 0x3F803F80u;
  fence_async_smem();
  __syncthreads();
  if (warp < 7 && lane == 0) {
    mbar_expect(barA + warp * 8, 8192); tma2(sb + warp * 8192, &mX, 64 * warp, G * 128, barA + warp * 8);
    mbar_expect(barA + 56 + warp * 8, 8192); tma2(sb + ABYTES + warp * 8192, &mX, 64 * warp, G * 128 + 64, barA + 56 + warp * 8);
    mbar_expect(barFull + warp * 8, 12288); tma3(sb + OFF_RING + warp * SLOT, &mQKV, 56 * r, 32 * warp, 0, barFull + warp * 8);
  }
  __syncwarp();
  const int wgid = warp >> 2;
  if (wgid == 2) {
    asm volatile("setmaxnreg.dec.sync.aligned.u32 56;");
    if (tid == 256) {
      int slot = 0, par = 0;
      for (int it = NSLOT; it < 2 * TILES_PER_LAYER; it++) {
        const int i = it >= TILES_PER_LAYER ? it - TILES_PER_LAYER : it;
        mbar_wait(barEmpty + slot * 8, par);
        const uint32_t dst = sb + OFF_RING + slot * SLOT, fb = barFull + slot * 8;
        mbar_expect(fb, i < 14 ? 12288 : SLOT);
        if (i < 14) tma3(dst, &mQKV, 56 * r, 32 * i, 0, fb);
        else if (i < 18) tma2(dst, &mWO, 56 * r, 112 * (i - 14), fb);
        else if (i < 32) tma3(dst, &mW1, 0, 32 * (i - 18), 7 * r, fb);
        else tma2(dst, &mW2, 64 * ((i - 32) >> 1), 224 * r + 112 * (i & 1), fb);
        if (++slot == NSLOT) { slot = 0; par ^= 1; }
      }
    } else if (tid >= 288) {
      unsigned ep;
      asm volatile("ld.relaxed.gpu.global.u32 %0, [%1];" : "=r"(ep) : "l"(gFlag + FL_DONE * 32) : "memory");
      const int idx = tid - 288;
      ep = (ep / NCTA + 1) * 3;
      if (G == 0) {
#pragma unroll 1
        for (int i = idx; i < 2 * 1280; i += 96) gKV[((i >= 1280) * 7 + r) * 1280 + i] = make_float4(0.f, 0.f, 0.f, 0.f);
        __syncwarp();
        if (lane == 0) flag_arrive(gFlag + (FL_CS + r) * 32);
      }
      {
        float sh[3], s1[3] = {0.f, 0.f, 0.f}, s2[3] = {0.f, 0.f, 0.f};
#pragma unroll 1
        for (int k = 0; k < 7; k++) {
          mbar_wait(barA + k * 8, 0); mbar_wait(barA + 56 + k * 8, 0);
#pragma unroll
          for (int i = 0; i < 3; i++) {
            const int row = min(i * 48 + (idx >> 1), 127);
            uint4 u[4];
#pragma unroll
            for (int j = 0; j < 4; j++) u[j] = *reinterpret_cast<const uint4*>(sg + (row >> 6) * ABYTES + k * 8192 + (row & 63) * 128 + (((idx & 1) * 4 + (j ^ (row & 3))) << 4));
            if (k == 0) sh[i] = __shfl_sync(~0u, lo(u[0].x), lane & ~1);
#pragma unroll
            for (int j = 0; j < 4; j++) {
              const uint32_t e[4] = {u[j].x, u[j].y, u[j].z, u[j].w};
#pragma unroll
              for (int z = 0; z < 4; z++) { const float a = lo(e[z]) - sh[i], b = hi(e[z]) - sh[i]; s1[i] += a + b; s2[i] = fmaf(a, a, fmaf(b, b, s2[i])); }
            }
          }
        }
#pragma unroll
        for (int i = 0; i < 3; i++) {
          const float a = s1[i] + __shfl_xor_sync(~0u, s1[i], 1), b = s2[i] + __shfl_xor_sync(~0u, s2[i], 1), d = a * (1.f / DM);
          reinterpret_cast<float2*>(sg + OFF_ST)[min(i * 48 + (idx >> 1), 127)] = make_float2(sh[i] + d, rsqrtf(fmaxf(b * (1.f / DM) - d * d, 0.f) + 1e-5f));
        }
        mbar_arrive(barCS + 16);
      }
      if (idx < 2) {
        const char* pf = idx ? (const char*)w2 + blockIdx.x * 12544 : (const char*)wo + blockIdx.x * 3136;
        asm volatile("cp.async.bulk.prefetch.L2.global [%0], %1;" ::"l"(pf), "r"(idx ? 12544 : 3136) : "memory");
      }
      if (lane == 0) flag_wait(gFlag + (FL_CS + r) * 32, ep);
      __syncwarp();
      mbar_arrive(barCS);
#pragma unroll 1
      for (int ps = 0; ps < 2; ps++) {
        const int ch = ps * 14 + min(idx >> 2, 13);
        const uint4* src = reinterpret_cast<const uint4*>(w1 + (size_t)(G * 28 + (idx & 3) * 7) * 1792 + 224 * r) + ch;
        uint4 cu[7];
#pragma unroll
        for (int i = 0; i < 7; i++) cu[i] = __ldg(src + i * 224);
        float s[8] = {};
#pragma unroll
        for (int i = 0; i < 7; i++) { s[0] += lo(cu[i].x); s[1] += hi(cu[i].x); s[2] += lo(cu[i].y); s[3] += hi(cu[i].y); s[4] += lo(cu[i].z); s[5] += hi(cu[i].z); s[6] += lo(cu[i].w); s[7] += hi(cu[i].w); }
#pragma unroll
        for (int i = 0; i < 8; i++) { s[i] += __shfl_xor_sync(~0u, s[i], 1); s[i] += __shfl_xor_sync(~0u, s[i], 2); }
        if ((idx & 3) < 2 && idx < 56) gCS[(r * 16 + G) * 56 + ch * 2 + (idx & 1)] = (idx & 1) ? make_float4(s[4], s[5], s[6], s[7]) : make_float4(s[0], s[1], s[2], s[3]);
      }
      __syncwarp();
      if (lane == 0) { flag_arrive(gFlag + (FL_CS + 8 + r) * 32); flag_wait(gFlag + (FL_CS + 8 + r) * 32, ep * 16); }
      __syncwarp();
#pragma unroll 1
      for (int j = idx; j < 112; j += 96) {
        float2 v[16], a = make_float2(0.f, 0.f);
#pragma unroll
        for (int i = 0; i < 16; i++) v[i] = __ldcg(reinterpret_cast<const float2*>(gCS + (r * 16 + i) * 56) + j);
#pragma unroll
        for (int i = 0; i < 16; i++) { a.x += v[i].x; a.y += v[i].y; }
        reinterpret_cast<float2*>(sg + OFF_CS + 768)[j] = a;
      }
      mbar_arrive(barCS + 8);
    }
  } else {
  const int c = wgid, w = warp & 3, g = lane >> 2, t = lane & 3;
  const bool elect = (tid & 127) == 0;
  const uint32_t abuf = sb + c * ABYTES, barAc = barA + c * 56;
  const int row0 = G * 128 + c * 64;
  unsigned epoch;
  asm volatile("ld.relaxed.gpu.global.u32 %0, [%1];" : "=r"(epoch) : "l"(gFlag + FL_DONE * 32) : "memory");
  STAMP(24);
  float mean[2], rstd[2];
  uint32_t wv[7];
#pragma unroll
  for (int i = 0; i < 7; i++)
    wv[i] = __ldg(reinterpret_cast<const unsigned short*>(wphi) + (56 * r + i * 8 + (tid >> 5)) * 28 + min(lane, 27));
  const uint32_t bv = __ldg(reinterpret_cast<const unsigned short*>(b1) + 224 * r + min(tid, 223));
  uint4 su[2] = {};
  asm volatile("setmaxnreg.inc.sync.aligned.u32 224;");
  STAMP(0);
  Ring ring{barFull, barEmpty, sb + OFF_RING, 0, 0};
  int apar = 0;
  const uint32_t stsm_off = (w * 16 + ((lane >> 3) & 1) * 8 + (lane & 7)) * 128;
  const uint32_t stsm_hi = lane >> 4;
  const uint64_t dA = mkdesc(abuf, 1024, 128, 0);

  auto gather = [&](unsigned* fl, const unsigned char* img) {
    __syncwarp();
    if (lane == 0) {
      flag_arrive(fl);
      STAMP(27);
      flag_wait(fl, epoch * 32);
      STAMP(28);
      fence_async();
      mbar_expect(barAc + w * 8, 8192); bulk_ld(abuf + w * 8192, img + w * 8192, 8192, barAc + w * 8);
      if (w < 3) { mbar_expect(barAc + 32 + w * 8, 8192); bulk_ld(abuf + 32768 + w * 8192, img + 32768 + w * 8192, 8192, barAc + 32 + w * 8); }
    }
    __syncwarp();
    apar ^= 1;
  };
  auto slice_off = [&](int j, int hh) -> uint32_t {
    return (7 * r + j) * 1024 + (w * 2 + hh) * 128 + lane * 4;
  };
  auto load_stats = [&](const float2* st) {
    mbar_wait(barAc, apar);
#pragma unroll
    for (int hh = 0; hh < 2; hh++) su[hh] = ldcg4(st + (size_t)(row0 + w * 16 + hh * 8 + g) * 8 + 2 * t);
  };
  auto finish_stats = [&]() {
#pragma unroll
    for (int hh = 0; hh < 2; hh++) {
      const float m0 = __uint_as_float(su[hh].x), m1 = __uint_as_float(su[hh].z);
      float m = m0 + m1;
      m += __shfl_xor_sync(~0u, m, 1); m += __shfl_xor_sync(~0u, m, 2);
      m *= 0.125f;
      float q = __uint_as_float(su[hh].y) + __uint_as_float(su[hh].w) + 56.f * ((m0 - m) * (m0 - m) + (m1 - m) * (m1 - m));
      q += __shfl_xor_sync(~0u, q, 1); q += __shfl_xor_sync(~0u, q, 2);
      mean[hh] = m; rstd[hh] = rsqrtf(q * (1.f / DM) + 1e-5f);
    }
  };

#pragma unroll 1
  for (int layer = 0; layer < 2; layer++) {
    unsigned* const fl = gFlag + (layer * 32 + G * 2 + c) * 7 * 32;
    uint32_t phiq[4][7], xs[7][2];
    {
      float acc[92]; reg_def(acc);
      int prev = 0;
      if (layer == 0) {
        const uint64_t dX = mkdesc(abuf, 16, 1024, 1), dOne = mkdesc(sb + OFF_ONE, 128, 128, 0);
        float cq[4], ck[4], cv[4]; reg_def(cq); reg_def(ck); reg_def(cv);
#pragma unroll 1
        for (int st = 0; st < 14; st++) {
          if (!(st & 1)) mbar_wait(barAc + (st >> 1) * 8, 0);
          const uint64_t da = dX + (st >> 1) * 512 + (st & 1) * 4, db = mkdesc(ring.acquire(), 4096, 1024, 1);
          wg_fence();
          mma_ss_184(acc, da, db, 1);
          mma_ss_184(acc, da + 2, db + 128, 1);
          mma_ss_8t(cq, db + c * 128, dOne, 1); mma_ss_8t(ck, db + 256 + c * 128, dOne, 1); mma_ss_8t(cv, db + 512 + c * 128, dOne, 1);
          wg_commit();
          if (st > 0) { wg_wait<1>(); ring.release(prev, elect); }
          prev = ring.advance();
        }
#pragma unroll
        for (int i = 0; i < 8; i++) {
          const int k = i * 8 + (tid >> 5);
          *reinterpret_cast<uint32_t*>(sg + OFF_WPHI + k * 128 + ((g ^ (k & 7)) << 4) + t * 4) = (i < 7 && lane < 28) ? wv[i % 7] << (k >= 28 ? 16 : 0) : 0u;
        }
        if (tid < 224) reinterpret_cast<uint32_t*>(sg + OFF_B1)[tid] = bv << 16;
        fence_async_smem();
        epoch = epoch / NCTA + 1;
        wg_wait<0>(); reg_fence(cq); reg_fence(ck); reg_fence(cv);
        float* cs = reinterpret_cast<float*>(sg + OFF_CS) + w * 16 + g + (t & 1) * 8;
        if (t < 2) { atomicAdd(cs, t ? cq[2] : cq[0]); atomicAdd(cs + 64, t ? ck[2] : ck[0]); atomicAdd(cs + 128, t ? cv[2] : cv[0]); }
        bar_sync<3, 256>();
        STAMP(25);
        mbar_wait(barCS + 16, 0);
#pragma unroll
        for (int hh = 0; hh < 2; hh++) { const float2 v = reinterpret_cast<const float2*>(sg + OFF_ST)[c * 64 + w * 16 + hh * 8 + g]; mean[hh] = v.x; rstd[hh] = v.y; }
      } else {
        load_stats(gStat + 2048 * 8);
#pragma unroll 1
        for (int st = 0; st < 14; st++) {
          if (!(st & 1)) mbar_wait(barAc + (st >> 1) * 8, apar);
          const uint64_t da = dA + st * 256, db = mkdesc(ring.acquire(), 4096, 1024, 1);
          wg_fence();
          mma_ss_184(acc, da, db, 1);
          mma_ss_184(acc, da + 128, db + 128, 1);
          wg_commit();
          if (st > 0) { wg_wait<1>(); ring.release(prev, elect); }
          prev = ring.advance();
        }
        finish_stats();
      }
#pragma unroll
      for (int j = 0; j < 7; j++) {
        const int ci = 7 * r + j;
        const uint32_t a = abuf + (layer ? slice_off(j, 0) : (ci >> 3) * 8192 + (w * 16 + g) * 128 + (((ci & 7) ^ g) << 4) + t * 4);
        xs[j][0] = lds32(a); xs[j][1] = lds32(a + (layer ? 128 : 1024));
      }
      wg_wait<0>(); reg_fence(acc);
      ring.release(prev, elect);
      STAMP(1 + layer * 12);
      uint32_t f[3][14];
      {
        const float2* cs = reinterpret_cast<const float2*>(sg + OFF_CS) + t;
        const float mr0 = -mean[0] * rstd[0], mr1 = -mean[1] * rstd[1];
#pragma unroll
        for (int p = 0; p < 3; p++)
#pragma unroll
          for (int j = 0; j < 7; j++) {
            const float2 s = cs[p * 32 + j * 4];
            const int b = p * 32 + j * 4;
            f[p][2 * j] = pack(fmaf(acc[b], rstd[0], s.x * mr0), fmaf(acc[b + 1], rstd[0], s.y * mr0));
            f[p][2 * j + 1] = pack(fmaf(acc[b + 2], rstd[1], s.x * mr1), fmaf(acc[b + 3], rstd[1], s.y * mr1));
          }
      }
      float pk[28], pq[28]; reg_def(pk); reg_def(pq);
      const uint64_t dW = mkdesc(sb + OFF_WPHI, 4096, 1024, 1);
      wg_fence();
#pragma unroll
      for (int s = 0; s < 4; s++)
        mma_rs_56(pk, f[1][4 * s], f[1][4 * s + 1], s < 3 ? f[1][(4 * s + 2) % 14] : 0u, s < 3 ? f[1][(4 * s + 3) % 14] : 0u, dW + s * 128, s);
      wg_commit();
#pragma unroll
      for (int s = 0; s < 4; s++)
        mma_rs_56(pq, f[0][4 * s], f[0][4 * s + 1], s < 3 ? f[0][(4 * s + 2) % 14] : 0u, s < 3 ? f[0][(4 * s + 3) % 14] : 0u, dW + s * 128, s);
      wg_commit();
      bar_wg(c);
      const uint32_t srow = abuf + stsm_off, ones = t == 0 ? 0x3F803F80u : 0u;
#pragma unroll
      for (int jp = 0; jp < 4; jp++)
        stsm4(srow + 16384 + (((2 * jp + stsm_hi) ^ (lane & 7)) << 4), f[2][4 * jp], f[2][4 * jp + 1],
              jp < 3 ? f[2][(4 * jp + 2) % 14] : ones, jp < 3 ? f[2][(4 * jp + 3) % 14] : ones);
      wg_wait<0>(); reg_fence(pk); reg_fence(pq);
#pragma unroll 1
      for (int pass = 0; pass < 2; pass++) {
        dual_softmax(pk, phiq);
        if (pass) break;
#pragma unroll
        for (int e = 0; e < 2; e++)
#pragma unroll
          for (int jp = 0; jp < 4; jp++)
            stsm4(srow + e * 8192 + (((2 * jp + stsm_hi) ^ (lane & 7)) << 4), phiq[e][2 * jp], phiq[2 + e][2 * jp],
                  jp < 3 ? phiq[e][(2 * jp + 1) % 7] : 0u, jp < 3 ? phiq[2 + e][(2 * jp + 1) % 7] : 0u);
        fence_async_smem();
        bar_sync<3, 256>();
        float kv[32]; reg_def(kv);
        const uint64_t dP = mkdesc(sb + c * 8192, 4096, 1024, 1), dV = mkdesc(sb + 16384, 4096, 1024, 1);
        wg_fence();
#pragma unroll
        for (int s = 0; s < 8; s++) mma_ss_64t(kv, dP + (s >> 2) * (ABYTES / 16) + (s & 3) * 128, dV + (s >> 2) * (ABYTES / 16) + (s & 3) * 128, s);
        wg_commit();
        mbar_wait(barCS, 0);
        wg_wait<0>(); reg_fence(kv);
        float4* kvg = gKV + ((layer * 8 + r) * 2 + c) * 640 + (tid & 127);
#pragma unroll
        for (int i = 0; i < 5; i++) {
          float v0, v1, v2, v3;
          if (i == 4) { v0 = kv[28]; v1 = kv[29]; v2 = kv[30]; v3 = kv[31]; }
          else { v0 = c ? kv[12 + 4 * i] : kv[4 * i]; v1 = c ? kv[13 + 4 * i] : kv[1 + 4 * i]; v2 = c ? kv[14 + 4 * i] : kv[2 + 4 * i]; v3 = c ? kv[15 + 4 * i] : kv[3 + 4 * i]; }
          const bool use = i == 4 ? t == 0 : (i == 0 ? (c == 0 || t >= 2) : (i == 3 ? (c == 1 || t < 2) : true));
          if (use) asm volatile("red.relaxed.gpu.global.add.v4.f32 [%0], {%1,%2,%3,%4};" ::"l"(kvg + i * 128), "f"(v0), "f"(v1), "f"(v2), "f"(v3) : "memory");
        }
        __syncwarp();
        if (lane == 0) flag_arrive(gFlag + (FL_KV + layer * 8 + r) * 32);
        __syncwarp();
        STAMP(2 + layer * 12);
#pragma unroll
        for (int i = 0; i < 28; i++) pk[i] = pq[i];
      }
    }
    {
      if (elect) flag_wait(gFlag + (FL_KV + layer * 8 + r) * 32, epoch * 128);
      bar_wg(c);
      STAMP(3 + layer * 12);
      const float4* kvg = gKV + (layer * 8 + r) * 1280 + (tid & 127);
      uint4 kk[2][5];
#pragma unroll
      for (int e = 0; e < 2; e++)
#pragma unroll
        for (int i = 0; i < 5; i++) kk[e][i] = ldcg4(kvg + e * 640 + i * 128);
      const uint32_t srow = abuf + 24576 + stsm_off;
#pragma unroll
      for (int e = 0; e < 2; e++) {
        uint32_t f[8][2];
#pragma unroll
        for (int j = 0; j < 8; j++) { f[j][0] = 0u; f[j][1] = 0u; }
#pragma unroll
        for (int i = 0; i < 4; i++) {
          f[i + 3 * e][0] = pack(__uint_as_float(kk[e][i].x), __uint_as_float(kk[e][i].y));
          f[i + 3 * e][1] = pack(__uint_as_float(kk[e][i].z), __uint_as_float(kk[e][i].w));
        }
        f[7][0] = e ? pack(0.f, __uint_as_float(kk[e][4].y)) : pack(__uint_as_float(kk[e][4].x), 0.f);
        f[7][1] = e ? pack(0.f, __uint_as_float(kk[e][4].w)) : pack(__uint_as_float(kk[e][4].z), 0.f);
#pragma unroll
        for (int jp = 0; jp < 4; jp++)
          stsm4(srow + e * 8192 + (((2 * jp + stsm_hi) ^ (lane & 7)) << 4), f[2 * jp][0], f[2 * jp][1], f[2 * jp + 1][0], f[2 * jp + 1][1]);
      }
      fence_async_smem();
      bar_wg(c);
      float num[32]; reg_def(num);
      const uint64_t dK = mkdesc(abuf + 24576, 4096, 1024, 1);
      wg_fence();
#pragma unroll
      for (int e = 0; e < 2; e++)
#pragma unroll
        for (int s = 0; s < 4; s++)
          mma_rs_64(num, phiq[e][2 * s], phiq[2 + e][2 * s], s < 3 ? phiq[e][(2 * s + 1) % 7] : 0u, s < 3 ? phiq[2 + e][(2 * s + 1) % 7] : 0u,
                    dK + e * 512 + s * 128, e + s);
      wg_commit();
      wg_wait<0>(); reg_fence(num);
      float rd[4];
#pragma unroll
      for (int i = 0; i < 4; i++) rd[i] = __fdividef(1.f, __shfl_sync(~0u, num[28 + i], lane & ~3) + 1e-6f);
      unsigned char* img = gImg + (size_t)(G * 2 + c) * ABYTES;
#pragma unroll
      for (int j = 0; j < 7; j++) {
        const bool hb = j > 3 || (j == 3 && t >= 2);
        const float r0 = hb ? rd[1] : rd[0], r1 = hb ? rd[3] : rd[2];
        *reinterpret_cast<uint32_t*>(img + slice_off(j, 0)) = pack(num[4 * j] * r0, num[4 * j + 1] * r0);
        *reinterpret_cast<uint32_t*>(img + slice_off(j, 1)) = pack(num[4 * j + 2] * r1, num[4 * j + 3] * r1);
      }
      STAMP(4 + layer * 12);
      gather(fl, img);
      STAMP(5 + layer * 12);
    }
    {
      float acc[28]; reg_def(acc);
      int prev = 0;
#pragma unroll 1
      for (int st = 0; st < 4; st++) {
        mbar_wait(barAc + (st * 7 + 3) / 4 * 8, apar);
        mbar_wait(barAc + (st * 7 + 6) / 4 * 8, apar);
        const uint64_t db = mkdesc(ring.acquire(), 4096, 1024, 1);
        wg_fence();
#pragma unroll
        for (int s = 0; s < 7; s++) { const int ks = st * 7 + s; mma_ss_56(acc, dA + ks * 128, db + s * 128, ks); }
        wg_commit();
        if (st > 0) { wg_wait<1>(); ring.release(prev, elect); }
        prev = ring.advance();
      }
      wg_wait<0>(); reg_fence(acc);
      ring.release(prev, elect);
      unsigned char* img = gImg + (size_t)(32 + G * 2 + c) * ABYTES;
#pragma unroll
      for (int hh = 0; hh < 2; hh++) {
        float s = 0.f, q = 0.f;
#pragma unroll
        for (int j = 0; j < 7; j++) {
          xs[j][hh] = pack(lo(xs[j][hh]) + acc[4 * j + 2 * hh], hi(xs[j][hh]) + acc[4 * j + 2 * hh + 1]);
          *reinterpret_cast<uint32_t*>(img + slice_off(j, hh)) = xs[j][hh];
          s += lo(xs[j][hh]) + hi(xs[j][hh]);
        }
        s += __shfl_xor_sync(~0u, s, 1); s += __shfl_xor_sync(~0u, s, 2);
        s *= 1.f / 56.f;
#pragma unroll
        for (int j = 0; j < 7; j++) { const float a = lo(xs[j][hh]) - s, b = hi(xs[j][hh]) - s; q = fmaf(a, a, q); q = fmaf(b, b, q); }
        q += __shfl_xor_sync(~0u, q, 1); q += __shfl_xor_sync(~0u, q, 2);
        if (t == 0) gStat[(size_t)(row0 + w * 16 + hh * 8 + g) * 8 + r] = make_float2(s, q);
      }
      STAMP(6 + layer * 12);
      gather(fl + 32, img);
      STAMP(7 + layer * 12);
    }
    {
      uint32_t hf[28][2];
      {
        float acc[112]; reg_def(acc);
        int prev = 0;
        load_stats(gStat);
#pragma unroll 1
        for (int st = 0; st < 14; st++) {
          if (!(st & 1)) mbar_wait(barAc + (st >> 1) * 8, apar);
          const uint64_t da = dA + st * 256, db = mkdesc(ring.acquire(), 2048, 512, 2);
          wg_fence();
          mma_ss_224(acc, da, db, st);
          mma_ss_224(acc, da + 128, db + 64, 1);
          wg_commit();
          if (st > 0) { wg_wait<1>(); ring.release(prev, elect); }
          prev = ring.advance();
        }
        finish_stats();
        mbar_wait(barCS + 8, 0);
        wg_wait<0>(); reg_fence(acc);
        ring.release(prev, elect);
        STAMP(8 + layer * 12);
        const float2* bs = reinterpret_cast<const float2*>(sg + OFF_B1) + t;
        const float2* cs = reinterpret_cast<const float2*>(sg + OFF_CS + 768) + t;
        const float mr0 = -mean[0] * rstd[0], mr1 = -mean[1] * rstd[1];
#pragma unroll
        for (int j = 0; j < 28; j++) {
          const float2 b = bs[4 * j], s = cs[4 * j];
          const float h0 = fmaxf(fmaf(acc[4 * j], rstd[0], fmaf(s.x, mr0, b.x)), 0.f), h1 = fmaxf(fmaf(acc[4 * j + 1], rstd[0], fmaf(s.y, mr0, b.y)), 0.f);
          const float h2 = fmaxf(fmaf(acc[4 * j + 2], rstd[1], fmaf(s.x, mr1, b.x)), 0.f), h3 = fmaxf(fmaf(acc[4 * j + 3], rstd[1], fmaf(s.y, mr1, b.y)), 0.f);
          hf[j][0] = pack(h0 * h0, h1 * h1); hf[j][1] = pack(h2 * h2, h3 * h3);
        }
      }
      unsigned char* pdst = gP + (size_t)(((G * 2 + c) * 8 + 2 * w) * 8 + r) * 7168 + lane * 8;
      uint2 pk[8] = {};
#pragma unroll 1
      for (int ch = 0; ch < 7; ch++) {
        float acc[32]; reg_def(acc);
        int sl0 = 0, sl1 = 0;
#pragma unroll
        for (int hk = 0; hk < 2; hk++) {
          const uint64_t db = mkdesc(ring.acquire(), 4096, 1024, 1);
          wg_fence();
#pragma unroll
          for (int s = 0; s < 7; s++) { const int ks = hk * 7 + s; mma_rs_64(acc, hf[2 * ks][0], hf[2 * ks][1], hf[2 * ks + 1][0], hf[2 * ks + 1][1], db + s * 128, ks); }
          wg_commit();
          if (hk) sl1 = ring.advance(); else sl0 = ring.advance();
        }
        if (ch > 0) {
#pragma unroll
          for (int i = 0; i < 8; i++) *reinterpret_cast<uint2*>(pdst + (i & 1) * (8 * 7168) + (i >> 1) * 256) = pk[i];
          pdst += 1024;
        }
        wg_wait<1>(); ring.release(sl0, elect);
        wg_wait<0>(); reg_fence(acc); ring.release(sl1, elect);
#pragma unroll
        for (int i = 0; i < 8; i++) {
          const int b = (i >> 1) * 8 + (i & 1) * 2;
          pk[i] = make_uint2(pack(acc[b], acc[b + 1]), pack(acc[b + 4], acc[b + 5]));
        }
      }
#pragma unroll
      for (int i = 0; i < 8; i++) *reinterpret_cast<uint2*>(pdst + (i & 1) * (8 * 7168) + (i >> 1) * 256) = pk[i];
      STAMP(9 + layer * 12);
    }
    {
      uint32_t bx[14];
#pragma unroll
      for (int j = 0; j < 14; j++) bx[j] = __ldg(reinterpret_cast<const uint32_t*>(b2 + w * 112 + j * 8 + 2 * t));
      __syncwarp();
      if (lane == 0) { flag_arrive(fl + (3 + w) * 32); flag_wait(fl + (3 + (r >> 1)) * 32, epoch * 8); }
      __syncwarp();
      STAMP(10 + layer * 12);
      const unsigned char* psrc = gP + (size_t)(((G * 2 + c) * 8 + r) * 8) * 7168 + w * 1792 + lane * 8;
      unsigned char* img = gImg + (size_t)(64 + G * 2 + c) * ABYTES;
      uint2 pv[8][7];
#pragma unroll
      for (int s = 0; s < 8; s++)
#pragma unroll
        for (int i = 0; i < 7; i++) pv[s][i] = ldcg2(psrc + s * 7168 + i * 256);
      const uint32_t off = w * 14336 + r * 128 + lane * 4;
      unsigned char* dst = layer ? reinterpret_cast<unsigned char*>(out + (size_t)(row0 + r * 8 + g) * DM + w * 112 + 2 * t) : img + off;
      float sm = 0.f, q = 0.f;
#pragma unroll
      for (int j = 0; j < 14; j++) {
        float y0 = lo(bx[j]), y1 = hi(bx[j]);
        const uint32_t xo = lds32(abuf + off + j * 1024);
        y0 += lo(xo); y1 += hi(xo);
#pragma unroll
        for (int s = 0; s < 8; s++) { const uint32_t u = (j & 1) ? pv[s][j >> 1].y : pv[s][j >> 1].x; y0 += lo(u); y1 += hi(u); }
        bx[j] = pack(y0, y1);
        *reinterpret_cast<uint32_t*>(dst + j * (layer ? 16 : 1024)) = bx[j];
        sm += lo(bx[j]) + hi(bx[j]);
      }
      if (layer) break;
      sm += __shfl_xor_sync(~0u, sm, 1); sm += __shfl_xor_sync(~0u, sm, 2);
      sm *= 1.f / 112.f;
#pragma unroll
      for (int j = 0; j < 14; j++) { const float a = lo(bx[j]) - sm, b = hi(bx[j]) - sm; q = fmaf(a, a, q); q = fmaf(b, b, q); }
      q += __shfl_xor_sync(~0u, q, 1); q += __shfl_xor_sync(~0u, q, 2);
      if (t < 2) gStat[(size_t)(2048 + row0 + r * 8 + g) * 8 + 2 * w + t] = make_float2(sm, q * 0.5f);
      STAMP(11);
      gather(fl + 64, img);
      STAMP(12);
    }
  }
  STAMP(30);
  if (tid == 0) asm volatile("red.relaxed.gpu.global.add.u32 [%0], 1;" ::"l"(gFlag + FL_DONE * 32) : "memory");
  }
}

typedef CUresult (*EncFn)(CUtensorMap*, CUtensorMapDataType, cuuint32_t, void*, const cuuint64_t*, const cuuint64_t*,
                          const cuuint32_t*, const cuuint32_t*, CUtensorMapInterleave, CUtensorMapSwizzle,
                          CUtensorMapL2promotion, CUtensorMapFloatOOBfill);

void make_map(EncFn enc, CUtensorMap* m, void* p, int rank, uint64_t d0, uint64_t d1, uint64_t d2, uint64_t s1, uint64_t s2,
              uint32_t b0, uint32_t b1, uint32_t b2, CUtensorMapSwizzle sw) {
  cuuint64_t dims[3] = {d0, d1, d2}, strides[2] = {s1, s2};
  cuuint32_t box[3] = {b0, b1, b2}, es[3] = {1, 1, 1};
  enc(m, CU_TENSOR_MAP_DATA_TYPE_BFLOAT16, rank, p, dims, strides, box, es, CU_TENSOR_MAP_INTERLEAVE_NONE, sw,
      CU_TENSOR_MAP_L2_PROMOTION_L2_128B, CU_TENSOR_MAP_FLOAT_OOB_FILL_NONE);
}

}

extern "C" void kernel_launch(void* const* d_in, const int* in_sizes, int n_in, void* d_out, int out_size) {
  static EncFn enc = nullptr;
  if (!enc) {
    cudaDriverEntryPointQueryResult st;
    void* fn = nullptr;
    cudaGetDriverEntryPoint("cuTensorMapEncodeTiled", &fn, cudaEnableDefault, &st);
    enc = (EncFn)fn;
    cudaFuncSetAttribute(fused_kernel, cudaFuncAttributeMaxDynamicSharedMemorySize, SMEM_BYTES);
  }
  CUtensorMap mQKV, mWO, mW1, mW2, mX;
  make_map(enc, &mQKV, d_in[1], 3, 448, 448, 3, 2688, 896, 64, 32, 3, CU_TENSOR_MAP_SWIZZLE_128B);
  make_map(enc, &mWO, d_in[3], 2, 448, 448, 1, 896, 0, 64, 112, 1, CU_TENSOR_MAP_SWIZZLE_128B);
  make_map(enc, &mW1, d_in[5], 3, 32, 448, 56, 3584, 64, 32, 32, 7, CU_TENSOR_MAP_SWIZZLE_64B);
  make_map(enc, &mW2, d_in[7], 2, 448, 1792, 1, 896, 0, 64, 112, 1, CU_TENSOR_MAP_SWIZZLE_128B);
  make_map(enc, &mX, d_in[0], 2, 448, 2048, 1, 896, 0, 64, 64, 1, CU_TENSOR_MAP_SWIZZLE_128B);
  fused_kernel<<<NCTA, 384, SMEM_BYTES, cudaStreamPerThread>>>(
      mQKV, mWO, mW1, mW2, mX, (const __nv_bfloat16*)d_in[0], (const __nv_bfloat16*)d_in[2], (const __nv_bfloat16*)d_in[6],
      (const __nv_bfloat16*)d_in[8], (const __nv_bfloat16*)d_in[1], (const __nv_bfloat16*)d_in[3], (const __nv_bfloat16*)d_in[5],
      (const __nv_bfloat16*)d_in[7], (__nv_bfloat16*)d_out);
}
```

```cpp
#include <cuda_runtime.h>
#include <cuda_bf16.h>
#include <cuda.h>
#include <stdint.h>

namespace {

constexpr int DM = 448, NCTA = 128;
constexpr int ABYTES = 57344;
constexpr int SLOT = 14336, NSLOT = 7;
constexpr int OFF_RING = 2 * ABYTES;
constexpr int OFF_WPHI = OFF_RING + NSLOT * SLOT;
constexpr int OFF_B1 = OFF_WPHI + 8192;
constexpr int OFF_CS = OFF_B1 + 896;
constexpr int OFF_BAR = OFF_CS + 1664;
constexpr int SMEM_BYTES = OFF_BAR + 256 + 1024;
constexpr int TILES_PER_LAYER = 46;

__device__ __align__(1024) unsigned char gP[16 * 2 * 8 * 8 * 7168];
__device__ __align__(1024) unsigned char gImg[3 * 32 * ABYTES];
__device__ __align__(1024) float2 gStat[2 * 2048 * 8];
__device__ __align__(1024) float4 gKV[2 * 8 * 2 * 5 * 128];
__device__ __align__(1024) float4 gCS[8 * 16 * 104];
__device__ __align__(128) unsigned gFlag[(2 * 32 * 7 + 32 + 1 + 16) * 32];
#define STAMP(i)

__device__ __forceinline__ uint32_t smem_u32(const void* p) { return (uint32_t)__cvta_generic_to_shared(p); }
__device__ __forceinline__ void mbar_init(uint32_t b, int c) { asm volatile("mbarrier.init.shared::cta.b64 [%0], %1;" ::"r"(b), "r"(c)); }
__device__ __forceinline__ void mbar_expect(uint32_t b, int bytes) { asm volatile("mbarrier.arrive.expect_tx.shared::cta.b64 _, [%0], %1;" ::"r"(b), "r"(bytes) : "memory"); }
__device__ __forceinline__ void mbar_arrive(uint32_t b) { asm volatile("mbarrier.arrive.shared::cta.b64 _, [%0];" ::"r"(b) : "memory"); }
__device__ __forceinline__ void mbar_wait(uint32_t b, int par) {
  uint32_t ok; int n = 0;
  while (true) {
    asm volatile("{.reg .pred p; mbarrier.try_wait.parity.shared::cta.b64 p, [%1], %2; selp.u32 %0,1,0,p;}" : "=r"(ok) : "r"(b), "r"(par) : "memory");
    if (ok) break;
    if (++n > (1 << 22)) break;
  }
}
__device__ __forceinline__ void flag_wait(const unsigned* f, unsigned target) {
  unsigned v; int n = 0;
  while (true) {
    asm volatile("ld.acquire.gpu.global.u32 %0, [%1];" : "=r"(v) : "l"(f) : "memory");
    if ((int)(v - target) >= 0) break;
    if (++n > (1 << 21)) break;
  }
}
__device__ __forceinline__ void flag_arrive(unsigned* f) { asm volatile("red.release.gpu.global.add.u32 [%0], 1;" ::"l"(f) : "memory"); }
__device__ __forceinline__ void fence_async() { asm volatile("fence.proxy.async.global;" ::: "memory"); }
__device__ __forceinline__ void fence_async_smem() { asm volatile("fence.proxy.async.shared::cta;" ::: "memory"); }
template <int ID, int N> __device__ __forceinline__ void bar_sync() { asm volatile("bar.sync %0, %1;" ::"n"(ID), "n"(N) : "memory"); }
__device__ __forceinline__ void bar_wg(int c) { if (c) bar_sync<2, 128>(); else bar_sync<1, 128>(); }
__device__ __forceinline__ void wg_fence() { asm volatile("wgmma.fence.sync.aligned;" ::: "memory"); }
__device__ __forceinline__ void wg_commit() { asm volatile("wgmma.commit_group.sync.aligned;" ::: "memory"); }
template <int N> __device__ __forceinline__ void wg_wait() { asm volatile("wgmma.wait_group.sync.aligned %0;" ::"n"(N) : "memory"); }
template <int N> __device__ __forceinline__ void reg_fence(float (&d)[N]) {
#pragma unroll
  for (int i = 0; i < N; i++) asm volatile("" : "+f"(d[i])::"memory");
}
template <int N> __device__ __forceinline__ void reg_def(float (&d)[N]) {
#pragma unroll
  for (int i = 0; i < N; i++) d[i] = 0.f;
}
__device__ __forceinline__ uint64_t mkdesc(uint32_t addr, uint32_t lbo, uint32_t sbo, uint64_t swz) {
  return (uint64_t)((addr & 0x3FFFF) >> 4) | ((uint64_t)(lbo >> 4) << 16) | ((uint64_t)(sbo >> 4) << 32) | (swz << 62);
}
__device__ __forceinline__ uint32_t pack(float a, float b) {
  uint32_t r; asm("cvt.rn.bf16x2.f32 %0, %1, %2;" : "=r"(r) : "f"(b), "f"(a)); return r;
}
__device__ __forceinline__ float lo(uint32_t u) { return __uint_as_float(u << 16); }
__device__ __forceinline__ float hi(uint32_t u) { return __uint_as_float(u & 0xFFFF0000u); }
__device__ __forceinline__ float ex2(float x) { float y; asm("ex2.approx.ftz.f32 %0, %1;" : "=f"(y) : "f"(x)); return y; }
__device__ __forceinline__ void stsm4(uint32_t a, uint32_t r0, uint32_t r1, uint32_t r2, uint32_t r3) {
  asm volatile("stmatrix.sync.aligned.m8n8.x4.shared.b16 [%0], {%1,%2,%3,%4};" ::"r"(a), "r"(r0), "r"(r1), "r"(r2), "r"(r3) : "memory");
}
__device__ __forceinline__ void tma3(uint32_t dst, const CUtensorMap* m, int c0, int c1, int c2, uint32_t bar) {
  asm volatile("cp.async.bulk.tensor.3d.shared::cluster.global.mbarrier::complete_tx::bytes [%0], [%1, {%3,%4,%5}], [%2];"
               ::"r"(dst), "l"(m), "r"(bar), "r"(c0), "r"(c1), "r"(c2) : "memory");
}
__device__ __forceinline__ void tma2(uint32_t dst, const CUtensorMap* m, int c0, int c1, uint32_t bar) {
  asm volatile("cp.async.bulk.tensor.2d.shared::cluster.global.mbarrier::complete_tx::bytes [%0], [%1, {%3,%4}], [%2];"
               ::"r"(dst), "l"(m), "r"(bar), "r"(c0), "r"(c1) : "memory");
}
__device__ __forceinline__ uint32_t lds32(uint32_t a) { uint32_t v; asm volatile("ld.shared.u32 %0, [%1];" : "=r"(v) : "r"(a) : "memory"); return v; }
__device__ __forceinline__ void bulk_ld(uint32_t dst, const void* src, int bytes, uint32_t bar) {
  asm volatile("cp.async.bulk.shared::cluster.global.mbarrier::complete_tx::bytes [%0], [%1], %2, [%3];" ::"r"(dst), "l"(src), "r"(bytes), "r"(bar) : "memory");
}
__device__ __forceinline__ uint4 ldcg4(const void* p) {
  uint4 v; asm volatile("ld.global.cg.v4.u32 {%0,%1,%2,%3}, [%4];" : "=r"(v.x), "=r"(v.y), "=r"(v.z), "=r"(v.w) : "l"(p) : "memory"); return v;
}

__device__ __forceinline__ uint2 ldcg2(const void* p) {
  uint2 v; asm volatile("ld.global.cg.v2.u32 {%0,%1}, [%2];" : "=r"(v.x), "=r"(v.y) : "l"(p) : "memory"); return v;
}

__device__ __forceinline__ void mma_ss_184(float (&d)[92], uint64_t da, uint64_t db, int acc) {
  asm volatile("{.reg .pred p; setp.ne.b32 p, %94, 0;\n"
    "wgmma.mma_async.sync.aligned.m64n184k16.f32.bf16.bf16 {%0,%1,%2,%3,%4,%5,%6,%7,%8,%9,%10,%11,%12,%13,%14,%15,%16,%17,%18,%19,%20,%21,%22,%23,%24,%25,%26,%27,%28,%29,%30,%31,%32,%33,%34,%35,%36,%37,%38,%39,%40,%41,%42,%43,%44,%45,%46,%47,%48,%49,%50,%51,%52,%53,%54,%55,%56,%57,%58,%59,%60,%61,%62,%63,%64,%65,%66,%67,%68,%69,%70,%71,%72,%73,%74,%75,%76,%77,%78,%79,%80,%81,%82,%83,%84,%85,%86,%87,%88,%89,%90,%91}, %92, %93, p, 1, 1, 0, 1;}\n"
    : "+f"(d[0]),"+f"(d[1]),"+f"(d[2]),"+f"(d[3]),"+f"(d[4]),"+f"(d[5]),"+f"(d[6]),"+f"(d[7]),"+f"(d[8]),"+f"(d[9]),"+f"(d[10]),"+f"(d[11]),"+f"(d[12]),"+f"(d[13]),"+f"(d[14]),"+f"(d[15]),"+f"(d[16]),"+f"(d[17]),"+f"(d[18]),"+f"(d[19]),"+f"(d[20]),"+f"(d[21]),"+f"(d[22]),"+f"(d[23]),"+f"(d[24]),"+f"(d[25]),"+f"(d[26]),"+f"(d[27]),"+f"(d[28]),"+f"(d[29]),"+f"(d[30]),"+f"(d[31]),"+f"(d[32]),"+f"(d[33]),"+f"(d[34]),"+f"(d[35]),"+f"(d[36]),"+f"(d[37]),"+f"(d[38]),"+f"(d[39]),"+f"(d[40]),"+f"(d[41]),"+f"(d[42]),"+f"(d[43]),"+f"(d[44]),"+f"(d[45]),"+f"(d[46]),"+f"(d[47]),"+f"(d[48]),"+f"(d[49]),"+f"(d[50]),"+f"(d[51]),"+f"(d[52]),"+f"(d[53]),"+f"(d[54]),"+f"(d[55]),"+f"(d[56]),"+f"(d[57]),"+f"(d[58]),"+f"(d[59]),"+f"(d[60]),"+f"(d[61]),"+f"(d[62]),"+f"(d[63]),"+f"(d[64]),"+f"(d[65]),"+f"(d[66]),"+f"(d[67]),"+f"(d[68]),"+f"(d[69]),"+f"(d[70]),"+f"(d[71]),"+f"(d[72]),"+f"(d[73]),"+f"(d[74]),"+f"(d[75]),"+f"(d[76]),"+f"(d[77]),"+f"(d[78]),"+f"(d[79]),"+f"(d[80]),"+f"(d[81]),"+f"(d[82]),"+f"(d[83]),"+f"(d[84]),"+f"(d[85]),"+f"(d[86]),"+f"(d[87]),"+f"(d[88]),"+f"(d[89]),"+f"(d[90]),"+f"(d[91])
    : "l"(da), "l"(db), "r"(acc));
}
__device__ __forceinline__ void mma_ss_224(float (&d)[112], uint64_t da, uint64_t db, int acc) {
  asm volatile("{.reg .pred p; setp.ne.b32 p, %114, 0;\n"
    "wgmma.mma_async.sync.aligned.m64n224k16.f32.bf16.bf16 {%0,%1,%2,%3,%4,%5,%6,%7,%8,%9,%10,%11,%12,%13,%14,%15,%16,%17,%18,%19,%20,%21,%22,%23,%24,%25,%26,%27,%28,%29,%30,%31,%32,%33,%34,%35,%36,%37,%38,%39,%40,%41,%42,%43,%44,%45,%46,%47,%48,%49,%50,%51,%52,%53,%54,%55,%56,%57,%58,%59,%60,%61,%62,%63,%64,%65,%66,%67,%68,%69,%70,%71,%72,%73,%74,%75,%76,%77,%78,%79,%80,%81,%82,%83,%84,%85,%86,%87,%88,%89,%90,%91,%92,%93,%94,%95,%96,%97,%98,%99,%100,%101,%102,%103,%104,%105,%106,%107,%108,%109,%110,%111}, %112, %113, p, 1, 1, 0, 1;}\n"
    : "+f"(d[0]),"+f"(d[1]),"+f"(d[2]),"+f"(d[3]),"+f"(d[4]),"+f"(d[5]),"+f"(d[6]),"+f"(d[7]),"+f"(d[8]),"+f"(d[9]),"+f"(d[10]),"+f"(d[11]),"+f"(d[12]),"+f"(d[13]),"+f"(d[14]),"+f"(d[15]),"+f"(d[16]),"+f"(d[17]),"+f"(d[18]),"+f"(d[19]),"+f"(d[20]),"+f"(d[21]),"+f"(d[22]),"+f"(d[23]),"+f"(d[24]),"+f"(d[25]),"+f"(d[26]),"+f"(d[27]),"+f"(d[28]),"+f"(d[29]),"+f"(d[30]),"+f"(d[31]),"+f"(d[32]),"+f"(d[33]),"+f"(d[34]),"+f"(d[35]),"+f"(d[36]),"+f"(d[37]),"+f"(d[38]),"+f"(d[39]),"+f"(d[40]),"+f"(d[41]),"+f"(d[42]),"+f"(d[43]),"+f"(d[44]),"+f"(d[45]),"+f"(d[46]),"+f"(d[47]),"+f"(d[48]),"+f"(d[49]),"+f"(d[50]),"+f"(d[51]),"+f"(d[52]),"+f"(d[53]),"+f"(d[54]),"+f"(d[55]),"+f"(d[56]),"+f"(d[57]),"+f"(d[58]),"+f"(d[59]),"+f"(d[60]),"+f"(d[61]),"+f"(d[62]),"+f"(d[63]),"+f"(d[64]),"+f"(d[65]),"+f"(d[66]),"+f"(d[67]),"+f"(d[68]),"+f"(d[69]),"+f"(d[70]),"+f"(d[71]),"+f"(d[72]),"+f"(d[73]),"+f"(d[74]),"+f"(d[75]),"+f"(d[76]),"+f"(d[77]),"+f"(d[78]),"+f"(d[79]),"+f"(d[80]),"+f"(d[81]),"+f"(d[82]),"+f"(d[83]),"+f"(d[84]),"+f"(d[85]),"+f"(d[86]),"+f"(d[87]),"+f"(d[88]),"+f"(d[89]),"+f"(d[90]),"+f"(d[91]),"+f"(d[92]),"+f"(d[93]),"+f"(d[94]),"+f"(d[95]),"+f"(d[96]),"+f"(d[97]),"+f"(d[98]),"+f"(d[99]),"+f"(d[100]),"+f"(d[101]),"+f"(d[102]),"+f"(d[103]),"+f"(d[104]),"+f"(d[105]),"+f"(d[106]),"+f"(d[107]),"+f"(d[108]),"+f"(d[109]),"+f"(d[110]),"+f"(d[111])
    : "l"(da), "l"(db), "r"(acc));
}
__device__ __forceinline__ void mma_ss_56(float (&d)[28], uint64_t da, uint64_t db, int acc) {
  asm volatile("{.reg .pred p; setp.ne.b32 p, %30, 0;\n"
    "wgmma.mma_async.sync.aligned.m64n56k16.f32.bf16.bf16 {%0,%1,%2,%3,%4,%5,%6,%7,%8,%9,%10,%11,%12,%13,%14,%15,%16,%17,%18,%19,%20,%21,%22,%23,%24,%25,%26,%27}, %28, %29, p, 1, 1, 0, 1;}\n"
    : "+f"(d[0]),"+f"(d[1]),"+f"(d[2]),"+f"(d[3]),"+f"(d[4]),"+f"(d[5]),"+f"(d[6]),"+f"(d[7]),"+f"(d[8]),"+f"(d[9]),"+f"(d[10]),"+f"(d[11]),"+f"(d[12]),"+f"(d[13]),"+f"(d[14]),"+f"(d[15]),"+f"(d[16]),"+f"(d[17]),"+f"(d[18]),"+f"(d[19]),"+f"(d[20]),"+f"(d[21]),"+f"(d[22]),"+f"(d[23]),"+f"(d[24]),"+f"(d[25]),"+f"(d[26]),"+f"(d[27])
    : "l"(da), "l"(db), "r"(acc));
}
__device__ __forceinline__ void mma_rs_56(float (&d)[28], uint32_t a0, uint32_t a1, uint32_t a2, uint32_t a3, uint64_t db, int acc) {
  asm volatile("{.reg .pred p; setp.ne.b32 p, %33, 0;\n"
    "wgmma.mma_async.sync.aligned.m64n56k16.f32.bf16.bf16 {%0,%1,%2,%3,%4,%5,%6,%7,%8,%9,%10,%11,%12,%13,%14,%15,%16,%17,%18,%19,%20,%21,%22,%23,%24,%25,%26,%27}, {%28,%29,%30,%31}, %32, p, 1, 1, 1;}\n"
    : "+f"(d[0]),"+f"(d[1]),"+f"(d[2]),"+f"(d[3]),"+f"(d[4]),"+f"(d[5]),"+f"(d[6]),"+f"(d[7]),"+f"(d[8]),"+f"(d[9]),"+f"(d[10]),"+f"(d[11]),"+f"(d[12]),"+f"(d[13]),"+f"(d[14]),"+f"(d[15]),"+f"(d[16]),"+f"(d[17]),"+f"(d[18]),"+f"(d[19]),"+f"(d[20]),"+f"(d[21]),"+f"(d[22]),"+f"(d[23]),"+f"(d[24]),"+f"(d[25]),"+f"(d[26]),"+f"(d[27])
    : "r"(a0), "r"(a1), "r"(a2), "r"(a3), "l"(db), "r"(acc));
}
__device__ __forceinline__ void mma_ss_64t(float (&d)[32], uint64_t da, uint64_t db, int acc) {
  asm volatile("{.reg .pred p; setp.ne.b32 p, %34, 0;\n"
    "wgmma.mma_async.sync.aligned.m64n64k16.f32.bf16.bf16 {%0,%1,%2,%3,%4,%5,%6,%7,%8,%9,%10,%11,%12,%13,%14,%15,%16,%17,%18,%19,%20,%21,%22,%23,%24,%25,%26,%27,%28,%29,%30,%31}, %32, %33, p, 1, 1, 1, 1;}\n"
    : "+f"(d[0]),"+f"(d[1]),"+f"(d[2]),"+f"(d[3]),"+f"(d[4]),"+f"(d[5]),"+f"(d[6]),"+f"(d[7]),"+f"(d[8]),"+f"(d[9]),"+f"(d[10]),"+f"(d[11]),"+f"(d[12]),"+f"(d[13]),"+f"(d[14]),"+f"(d[15]),"+f"(d[16]),"+f"(d[17]),"+f"(d[18]),"+f"(d[19]),"+f"(d[20]),"+f"(d[21]),"+f"(d[22]),"+f"(d[23]),"+f"(d[24]),"+f"(d[25]),"+f"(d[26]),"+f"(d[27]),"+f"(d[28]),"+f"(d[29]),"+f"(d[30]),"+f"(d[31])
    : "l"(da), "l"(db), "r"(acc));
}
__device__ __forceinline__ void mma_rs_64(float (&d)[32], uint32_t a0, uint32_t a1, uint32_t a2, uint32_t a3, uint64_t db, int acc) {
  asm volatile("{.reg .pred p; setp.ne.b32 p, %37, 0;\n"
    "wgmma.mma_async.sync.aligned.m64n64k16.f32.bf16.bf16 {%0,%1,%2,%3,%4,%5,%6,%7,%8,%9,%10,%11,%12,%13,%14,%15,%16,%17,%18,%19,%20,%21,%22,%23,%24,%25,%26,%27,%28,%29,%30,%31}, {%32,%33,%34,%35}, %36, p, 1, 1, 1;}\n"
    : "+f"(d[0]),"+f"(d[1]),"+f"(d[2]),"+f"(d[3]),"+f"(d[4]),"+f"(d[5]),"+f"(d[6]),"+f"(d[7]),"+f"(d[8]),"+f"(d[9]),"+f"(d[10]),"+f"(d[11]),"+f"(d[12]),"+f"(d[13]),"+f"(d[14]),"+f"(d[15]),"+f"(d[16]),"+f"(d[17]),"+f"(d[18]),"+f"(d[19]),"+f"(d[20]),"+f"(d[21]),"+f"(d[22]),"+f"(d[23]),"+f"(d[24]),"+f"(d[25]),"+f"(d[26]),"+f"(d[27]),"+f"(d[28]),"+f"(d[29]),"+f"(d[30]),"+f"(d[31])
    : "r"(a0), "r"(a1), "r"(a2), "r"(a3), "l"(db), "r"(acc));
}

__device__ __forceinline__ void dual_softmax(const float (&p)[28], uint32_t (&phi)[4][7]) {
  constexpr float L2E = 1.4426950408889634f;
#pragma unroll
  for (int i = 0; i < 4; i++) {
    float mx = p[i], mn = p[i];
#pragma unroll
    for (int j = 1; j < 7; j++) { mx = fmaxf(mx, p[4 * j + i]); mn = fminf(mn, p[4 * j + i]); }
    mx = fmaxf(mx, __shfl_xor_sync(~0u, mx, 1)); mn = fminf(mn, __shfl_xor_sync(~0u, mn, 1));
    mx = fmaxf(mx, __shfl_xor_sync(~0u, mx, 2)); mn = fminf(mn, __shfl_xor_sync(~0u, mn, 2));
    float a[7], b[7], sa = 0.f, sb = 0.f;
    const float mxl = mx * L2E, mnl = mn * L2E;
#pragma unroll
    for (int j = 0; j < 7; j++) {
      a[j] = ex2(fmaf(p[4 * j + i], L2E, -mxl)); b[j] = ex2(fmaf(p[4 * j + i], -L2E, mnl));
      sa += a[j]; sb += b[j];
    }
    sa += __shfl_xor_sync(~0u, sa, 1); sb += __shfl_xor_sync(~0u, sb, 1);
    sa += __shfl_xor_sync(~0u, sa, 2); sb += __shfl_xor_sync(~0u, sb, 2);
    const float ra = __fdividef(1.f, sa), rb = __fdividef(1.f, sb);
#pragma unroll
    for (int j = 0; j < 7; j++) phi[i][j] = pack(a[j] * ra, b[j] * rb);
  }
}

struct Ring {
  uint32_t full, empty, base; int slot, par;
  __device__ __forceinline__ uint32_t acquire() { mbar_wait(full + slot * 8, par); return base + slot * SLOT; }
  __device__ __forceinline__ int advance() { int s = slot; if (++slot == NSLOT) { slot = 0; par ^= 1; } return s; }
  __device__ __forceinline__ void release(int s, bool elect) { if (elect) mbar_arrive(empty + s * 8); }
};
constexpr int FL_KV = 448, FL_CS = FL_KV + 16, FL_DONE = FL_KV + 32;

__global__ void __launch_bounds__(384, 1)
fused_kernel(const __grid_constant__ CUtensorMap mQKV, const __grid_constant__ CUtensorMap mWO,
             const __grid_constant__ CUtensorMap mW1, const __grid_constant__ CUtensorMap mW2,
             const __nv_bfloat16* __restrict__ x, const __nv_bfloat16* __restrict__ wphi,
             const __nv_bfloat16* __restrict__ b1, const __nv_bfloat16* __restrict__ b2,
             const __nv_bfloat16* __restrict__ wqkv, const __nv_bfloat16* __restrict__ wo, const __nv_bfloat16* __restrict__ w1,
             const __nv_bfloat16* __restrict__ w2, __nv_bfloat16* __restrict__ out) {
  extern __shared__ unsigned char smem_raw[];
  const uint32_t sb = (smem_u32(smem_raw) + 1023) & ~1023u;
  unsigned char* sg = smem_raw + (sb - smem_u32(smem_raw));
  const int tid = threadIdx.x, lane = tid & 31;
  const int G = blockIdx.x >> 3, r = blockIdx.x & 7;
  const uint32_t barFull = sb + OFF_BAR, barEmpty = barFull + 56, barA = barEmpty + 56, barCS = barA + 112;
  const int warp = __shfl_sync(~0u, tid >> 5, 0);
  const uint32_t xoff = (warp >> 2) * ABYTES + (lane >> 3) * 1024 + ((warp & 3) * 16 + (lane & 7)) * 16;
  if (warp < 8) {
    const char* src = reinterpret_cast<const char*>(x + (size_t)(G * 128 + warp * 16 + (lane & 7)) * DM) + (lane >> 3) * 16;
#pragma unroll
    for (int i = 0; i < 28; i++)
      asm volatile("cp.async.cg.shared.global [%0], [%1], 16;" ::"r"(sb + xoff + (i % 14) * 4096 + (i / 14) * 128), "l"(src + (i % 14) * 64 + (i / 14) * 8 * 896) : "memory");
  }
  if (lane == 0) {
    if (warp < 7) { mbar_init(barFull + warp * 8, 1); mbar_init(barEmpty + warp * 8, 2); mbar_init(barA + warp * 8, 1); mbar_init(barA + 56 + warp * 8, 1); }
    else if (warp < 9) mbar_init(barCS + (warp - 7) * 8, 96);
    else if (warp == 11)
      asm volatile("cp.async.bulk.prefetch.L2.global [%0], %1;" ::"l"((const char*)wqkv + 602112 + blockIdx.x * 4704), "r"(4704) : "memory");
    asm volatile("fence.mbarrier_init.release.cluster;" ::: "memory");
  }
  if (tid < 192) reinterpret_cast<float*>(sg + OFF_CS)[tid] = 0.f;
  __syncthreads();
  const int wgid = warp >> 2;
  if (wgid == 2) {
    asm volatile("setmaxnreg.dec.sync.aligned.u32 56;");
    if (tid == 256) {
      int slot = 0, par = 1;
      for (int it = 0; it < 2 * TILES_PER_LAYER; it++) {
        const int i = it >= TILES_PER_LAYER ? it - TILES_PER_LAYER : it;
        mbar_wait(barEmpty + slot * 8, par);
        const uint32_t dst = sb + OFF_RING + slot * SLOT, fb = barFull + slot * 8;
        mbar_expect(fb, i < 14 ? 12288 : SLOT);
        if (i < 14) tma3(dst, &mQKV, 56 * r, 32 * i, 0, fb);
        else if (i < 18) tma2(dst, &mWO, 56 * r, 112 * (i - 14), fb);
        else if (i < 32) tma3(dst, &mW1, 0, 32 * (i - 18), 7 * r, fb);
        else tma2(dst, &mW2, 64 * ((i - 32) >> 1), 224 * r + 112 * (i & 1), fb);
        if (++slot == NSLOT) { slot = 0; par ^= 1; }
      }
    } else if (tid >= 288) {
      unsigned ep;
      asm volatile("ld.relaxed.gpu.global.u32 %0, [%1];" : "=r"(ep) : "l"(gFlag + FL_DONE * 32) : "memory");
      const int idx = tid - 288;
      ep = (ep / NCTA + 1) * 3;
      if (G == 0) {
#pragma unroll 1
        for (int i = idx; i < 2 * 1280; i += 96) gKV[((i >= 1280) * 7 + r) * 1280 + i] = make_float4(0.f, 0.f, 0.f, 0.f);
        __syncwarp();
        if (lane == 0) flag_arrive(gFlag + (FL_CS + r) * 32);
      }
      mbar_wait(barFull + 48, 0);
      if (idx < 2) {
        const char* pf = idx ? (const char*)w2 + blockIdx.x * 12544 : (const char*)wo + blockIdx.x * 3136;
        asm volatile("cp.async.bulk.prefetch.L2.global [%0], %1;" ::"l"(pf), "r"(idx ? 12544 : 3136) : "memory");
      }
      if (lane == 0) flag_wait(gFlag + (FL_CS + r) * 32, ep);
      __syncwarp();
      mbar_arrive(barCS);
#pragma unroll 1
      for (int ps = 0; ps < 3; ps++) {
        const int nch = ps ? 14 : 21, ch = min(idx >> 2, nch - 1), p = ch / 7, k0 = G * 28 + (idx & 3) * 7;
        const uint4* src = ps ? reinterpret_cast<const uint4*>(w1 + (size_t)k0 * 1792 + 224 * r) + (ps - 1) * 14 + ch
                              : reinterpret_cast<const uint4*>(wqkv + (size_t)k0 * 1344 + p * 448 + 56 * r) + (ch - 7 * p);
        uint4 cu[7];
#pragma unroll
        for (int i = 0; i < 7; i++) cu[i] = __ldg(src + i * (ps ? 224 : 168));
        float s[8] = {};
#pragma unroll
        for (int i = 0; i < 7; i++) { s[0] += lo(cu[i].x); s[1] += hi(cu[i].x); s[2] += lo(cu[i].y); s[3] += hi(cu[i].y); s[4] += lo(cu[i].z); s[5] += hi(cu[i].z); s[6] += lo(cu[i].w); s[7] += hi(cu[i].w); }
#pragma unroll
        for (int i = 0; i < 8; i++) { s[i] += __shfl_xor_sync(~0u, s[i], 1); s[i] += __shfl_xor_sync(~0u, s[i], 2); }
        if ((idx & 3) < 2 && idx < nch * 4) gCS[(r * 16 + G) * 104 + (ps ? 10 + ps * 14 + ch : ch + p) * 2 + (idx & 1)] = (idx & 1) ? make_float4(s[4], s[5], s[6], s[7]) : make_float4(s[0], s[1], s[2], s[3]);
      }
      __syncwarp();
      if (lane == 0) { flag_arrive(gFlag + (FL_CS + 8 + r) * 32); flag_wait(gFlag + (FL_CS + 8 + r) * 32, ep * 16); }
      __syncwarp();
#pragma unroll 1
      for (int j = idx; j < 208; j += 96) {
        float2 v[16], a = make_float2(0.f, 0.f);
#pragma unroll
        for (int i = 0; i < 16; i++) v[i] = __ldcg(reinterpret_cast<const float2*>(gCS + (r * 16 + i) * 104) + j);
#pragma unroll
        for (int i = 0; i < 16; i++) { a.x += v[i].x; a.y += v[i].y; }
        reinterpret_cast<float2*>(sg + OFF_CS)[j] = a;
      }
      mbar_arrive(barCS + 8);
    }
  } else {
  asm volatile("setmaxnreg.inc.sync.aligned.u32 224;");
  const int c = wgid, w = warp & 3, g = lane >> 2, t = lane & 3;
  const bool elect = (tid & 127) == 0;
  const uint32_t abuf = sb + c * ABYTES, barAc = barA + c * 56;
  const int row0 = G * 128 + c * 64;
  unsigned epoch;
  asm volatile("ld.relaxed.gpu.global.u32 %0, [%1];" : "=r"(epoch) : "l"(gFlag + FL_DONE * 32) : "memory");
  STAMP(24);
  float mean[2], rstd[2];
  uint32_t wv[7];
#pragma unroll
  for (int i = 0; i < 7; i++)
    wv[i] = __ldg(reinterpret_cast<const unsigned short*>(wphi) + (56 * r + i * 8 + (tid >> 5)) * 28 + min(lane, 27));
  const uint32_t bv = __ldg(reinterpret_cast<const unsigned short*>(b1) + 224 * r + min(tid, 223));
  uint4 su[2] = {};
  uint32_t xs[7][2];
  {
    asm volatile("cp.async.wait_all;" ::: "memory");
    __syncwarp();
#pragma unroll
    for (int j = 0; j < 7; j++) { xs[j][0] = lds32(abuf + (7 * r + j) * 1024 + w * 256 + lane * 4); xs[j][1] = lds32(abuf + (7 * r + j) * 1024 + w * 256 + 128 + lane * 4); }
    __syncwarp();
#pragma unroll 1
    for (int hh = 0; hh < 2; hh++) {
      uint4* p = reinterpret_cast<uint4*>(sg + xoff + hh * 128);
      uint4 v[14];
#pragma unroll
      for (int k = 0; k < 14; k++) v[k] = p[k * 256];
      float sm = 0.f, q = 0.f;
#pragma unroll
      for (int k = 0; k < 14; k++) sm += (lo(v[k].x) + hi(v[k].x)) + (lo(v[k].y) + hi(v[k].y)) + (lo(v[k].z) + hi(v[k].z)) + (lo(v[k].w) + hi(v[k].w));
      sm += __shfl_xor_sync(~0u, sm, 8); sm += __shfl_xor_sync(~0u, sm, 16);
      sm *= 1.f / DM;
      float d[14][8];
#pragma unroll
      for (int k = 0; k < 14; k++) {
        const uint32_t e[4] = {v[k].x, v[k].y, v[k].z, v[k].w};
#pragma unroll
        for (int z = 0; z < 4; z++) { d[k][2 * z] = lo(e[z]) - sm; d[k][2 * z + 1] = hi(e[z]) - sm; q = fmaf(d[k][2 * z], d[k][2 * z], fmaf(d[k][2 * z + 1], d[k][2 * z + 1], q)); }
      }
      q += __shfl_xor_sync(~0u, q, 8); q += __shfl_xor_sync(~0u, q, 16);
      q = rsqrtf(q * (1.f / DM) + 1e-5f);
#pragma unroll
      for (int k = 0; k < 14; k++) p[k * 256] = make_uint4(pack(d[k][0] * q, d[k][1] * q), pack(d[k][2] * q, d[k][3] * q), pack(d[k][4] * q, d[k][5] * q), pack(d[k][6] * q, d[k][7] * q));
    }
#pragma unroll
    for (int i = 0; i < 8; i++) {
      const int k = i * 8 + (tid >> 5);
      *reinterpret_cast<uint32_t*>(sg + OFF_WPHI + k * 128 + ((g ^ (k & 7)) << 4) + t * 4) = (i < 7 && lane < 28) ? wv[i % 7] << (k >= 28 ? 16 : 0) : 0u;
    }
    if (tid < 224) reinterpret_cast<uint32_t*>(sg + OFF_B1)[tid] = bv << 16;
    fence_async_smem();
    bar_sync<3, 256>();
    epoch = epoch / NCTA + 1;
    mean[0] = mean[1] = 0.f; rstd[0] = rstd[1] = 1.f;
  }
  STAMP(0);
  Ring ring{barFull, barEmpty, sb + OFF_RING, 0, 0};
  int apar = 1;
  const uint32_t stsm_off = (w * 16 + ((lane >> 3) & 1) * 8 + (lane & 7)) * 128;
  const uint32_t stsm_hi = lane >> 4;
  const uint64_t dA = mkdesc(abuf, 1024, 128, 0);

  auto gather = [&](unsigned* fl, const unsigned char* img) {
    __syncwarp();
    if (lane == 0) {
      flag_arrive(fl);
      STAMP(27);
      flag_wait(fl, epoch * 32);
      STAMP(28);
      fence_async();
      mbar_expect(barAc + w * 8, 8192); bulk_ld(abuf + w * 8192, img + w * 8192, 8192, barAc + w * 8);
      if (w < 3) { mbar_expect(barAc + 32 + w * 8, 8192); bulk_ld(abuf + 32768 + w * 8192, img + 32768 + w * 8192, 8192, barAc + 32 + w * 8); }
    }
    __syncwarp();
    apar ^= 1;
  };
  auto slice_off = [&](int j, int hh) -> uint32_t {
    return (7 * r + j) * 1024 + (w * 2 + hh) * 128 + lane * 4;
  };
  auto load_stats = [&](const float2* st) {
    mbar_wait(barAc, apar);
#pragma unroll
    for (int hh = 0; hh < 2; hh++) su[hh] = ldcg4(st + (size_t)(row0 + w * 16 + hh * 8 + g) * 8 + 2 * t);
  };
  auto finish_stats = [&]() {
#pragma unroll
    for (int hh = 0; hh < 2; hh++) {
      const float m0 = __uint_as_float(su[hh].x), m1 = __uint_as_float(su[hh].z);
      float m = m0 + m1;
      m += __shfl_xor_sync(~0u, m, 1); m += __shfl_xor_sync(~0u, m, 2);
      m *= 0.125f;
      float q = __uint_as_float(su[hh].y) + __uint_as_float(su[hh].w) + 56.f * ((m0 - m) * (m0 - m) + (m1 - m) * (m1 - m));
      q += __shfl_xor_sync(~0u, q, 1); q += __shfl_xor_sync(~0u, q, 2);
      mean[hh] = m; rstd[hh] = rsqrtf(q * (1.f / DM) + 1e-5f);
    }
  };

#pragma unroll 1
  for (int layer = 0; layer < 2; layer++) {
    unsigned* const fl = gFlag + (layer * 32 + G * 2 + c) * 7 * 32;
    uint32_t phiq[4][7];
    {
      float acc[92]; reg_def(acc);
      int prev = 0;
      if (layer) load_stats(gStat + 2048 * 8);
#pragma unroll 1
      for (int st = 0; st < 14; st++) {
        if (!(st & 1)) mbar_wait(barAc + (st >> 1) * 8, apar);
        const uint64_t da = dA + st * 256, db = mkdesc(ring.acquire(), 4096, 1024, 1);
        wg_fence();
        mma_ss_184(acc, da, db, 1);
        mma_ss_184(acc, da + 128, db + 128, 1);
        wg_commit();
        if (st > 0) { wg_wait<1>(); ring.release(prev, elect); }
        prev = ring.advance();
      }
      if (layer) {
        finish_stats();
#pragma unroll
        for (int j = 0; j < 7; j++) { xs[j][0] = lds32(abuf + slice_off(j, 0)); xs[j][1] = lds32(abuf + slice_off(j, 1)); }
      }
      wg_wait<0>(); reg_fence(acc);
      ring.release(prev, elect);
      STAMP(1 + layer * 12);
      uint32_t f[3][14];
      {
        const float2* cs = reinterpret_cast<const float2*>(sg + OFF_CS) + t;
        const float mr0 = -mean[0] * rstd[0], mr1 = -mean[1] * rstd[1];
#pragma unroll
        for (int p = 0; p < 3; p++)
#pragma unroll
          for (int j = 0; j < 7; j++) {
            const float2 s = cs[p * 32 + j * 4];
            const int b = p * 32 + j * 4;
            f[p][2 * j] = pack(fmaf(acc[b], rstd[0], s.x * mr0), fmaf(acc[b + 1], rstd[0], s.y * mr0));
            f[p][2 * j + 1] = pack(fmaf(acc[b + 2], rstd[1], s.x * mr1), fmaf(acc[b + 3], rstd[1], s.y * mr1));
          }
      }
      float pk[28], pq[28]; reg_def(pk); reg_def(pq);
      const uint64_t dW = mkdesc(sb + OFF_WPHI, 4096, 1024, 1);
      wg_fence();
#pragma unroll
      for (int s = 0; s < 4; s++)
        mma_rs_56(pk, f[1][4 * s], f[1][4 * s + 1], s < 3 ? f[1][(4 * s + 2) % 14] : 0u, s < 3 ? f[1][(4 * s + 3) % 14] : 0u, dW + s * 128, s);
      wg_commit();
#pragma unroll
      for (int s = 0; s < 4; s++)
        mma_rs_56(pq, f[0][4 * s], f[0][4 * s + 1], s < 3 ? f[0][(4 * s + 2) % 14] : 0u, s < 3 ? f[0][(4 * s + 3) % 14] : 0u, dW + s * 128, s);
      wg_commit();
      bar_wg(c);
      const uint32_t srow = abuf + stsm_off, ones = t == 0 ? 0x3F803F80u : 0u;
#pragma unroll
      for (int jp = 0; jp < 4; jp++)
        stsm4(srow + 16384 + (((2 * jp + stsm_hi) ^ (lane & 7)) << 4), f[2][4 * jp], f[2][4 * jp + 1],
              jp < 3 ? f[2][(4 * jp + 2) % 14] : ones, jp < 3 ? f[2][(4 * jp + 3) % 14] : ones);
      wg_wait<0>(); reg_fence(pk); reg_fence(pq);
#pragma unroll 1
      for (int pass = 0; pass < 2; pass++) {
        dual_softmax(pk, phiq);
        if (pass) break;
#pragma unroll
        for (int e = 0; e < 2; e++)
#pragma unroll
          for (int jp = 0; jp < 4; jp++)
            stsm4(srow + e * 8192 + (((2 * jp + stsm_hi) ^ (lane & 7)) << 4), phiq[e][2 * jp], phiq[2 + e][2 * jp],
                  jp < 3 ? phiq[e][(2 * jp + 1) % 7] : 0u, jp < 3 ? phiq[2 + e][(2 * jp + 1) % 7] : 0u);
        fence_async_smem();
        bar_sync<3, 256>();
        float kv[32]; reg_def(kv);
        const uint64_t dP = mkdesc(sb + c * 8192, 4096, 1024, 1), dV = mkdesc(sb + 16384, 4096, 1024, 1);
        wg_fence();
#pragma unroll
        for (int s = 0; s < 8; s++) mma_ss_64t(kv, dP + (s >> 2) * (ABYTES / 16) + (s & 3) * 128, dV + (s >> 2) * (ABYTES / 16) + (s & 3) * 128, s);
        wg_commit();
        mbar_wait(barCS, 0);
        wg_wait<0>(); reg_fence(kv);
        float4* kvg = gKV + ((layer * 8 + r) * 2 + c) * 640 + (tid & 127);
#pragma unroll
        for (int i = 0; i < 5; i++) {
          float v0, v1, v2, v3;
          if (i == 4) { v0 = kv[28]; v1 = kv[29]; v2 = kv[30]; v3 = kv[31]; }
          else { v0 = c ? kv[12 + 4 * i] : kv[4 * i]; v1 = c ? kv[13 + 4 * i] : kv[1 + 4 * i]; v2 = c ? kv[14 + 4 * i] : kv[2 + 4 * i]; v3 = c ? kv[15 + 4 * i] : kv[3 + 4 * i]; }
          const bool use = i == 4 ? t == 0 : (i == 0 ? (c == 0 || t >= 2) : (i == 3 ? (c == 1 || t < 2) : true));
          if (use) asm volatile("red.relaxed.gpu.global.add.v4.f32 [%0], {%1,%2,%3,%4};" ::"l"(kvg + i * 128), "f"(v0), "f"(v1), "f"(v2), "f"(v3) : "memory");
        }
        __syncwarp();
        if (lane == 0) flag_arrive(gFlag + (FL_KV + layer * 8 + r) * 32);
        __syncwarp();
        STAMP(2 + layer * 12);
#pragma unroll
        for (int i = 0; i < 28; i++) pk[i] = pq[i];
      }
    }
    {
      if (elect) flag_wait(gFlag + (FL_KV + layer * 8 + r) * 32, epoch * 128);
      bar_wg(c);
      STAMP(3 + layer * 12);
      const float4* kvg = gKV + (layer * 8 + r) * 1280 + (tid & 127);
      uint4 kk[2][5];
#pragma unroll
      for (int e = 0; e < 2; e++)
#pragma unroll
        for (int i = 0; i < 5; i++) kk[e][i] = ldcg4(kvg + e * 640 + i * 128);
      const uint32_t srow = abuf + 24576 + stsm_off;
#pragma unroll
      for (int e = 0; e < 2; e++) {
        uint32_t f[8][2];
#pragma unroll
        for (int j = 0; j < 8; j++) { f[j][0] = 0u; f[j][1] = 0u; }
#pragma unroll
        for (int i = 0; i < 4; i++) {
          f[i + 3 * e][0] = pack(__uint_as_float(kk[e][i].x), __uint_as_float(kk[e][i].y));
          f[i + 3 * e][1] = pack(__uint_as_float(kk[e][i].z), __uint_as_float(kk[e][i].w));
        }
        f[7][0] = e ? pack(0.f, __uint_as_float(kk[e][4].y)) : pack(__uint_as_float(kk[e][4].x), 0.f);
        f[7][1] = e ? pack(0.f, __uint_as_float(kk[e][4].w)) : pack(__uint_as_float(kk[e][4].z), 0.f);
#pragma unroll
        for (int jp = 0; jp < 4; jp++)
          stsm4(srow + e * 8192 + (((2 * jp + stsm_hi) ^ (lane & 7)) << 4), f[2 * jp][0], f[2 * jp][1], f[2 * jp + 1][0], f[2 * jp + 1][1]);
      }
      fence_async_smem();
      bar_wg(c);
      float num[32]; reg_def(num);
      const uint64_t dK = mkdesc(abuf + 24576, 4096, 1024, 1);
      wg_fence();
#pragma unroll
      for (int e = 0; e < 2; e++)
#pragma unroll
        for (int s = 0; s < 4; s++)
          mma_rs_64(num, phiq[e][2 * s], phiq[2 + e][2 * s], s < 3 ? phiq[e][(2 * s + 1) % 7] : 0u, s < 3 ? phiq[2 + e][(2 * s + 1) % 7] : 0u,
                    dK + e * 512 + s * 128, e + s);
      wg_commit();
      wg_wait<0>(); reg_fence(num);
      float rd[4];
#pragma unroll
      for (int i = 0; i < 4; i++) rd[i] = __fdividef(1.f, __shfl_sync(~0u, num[28 + i], lane & ~3) + 1e-6f);
      unsigned char* img = gImg + (size_t)(G * 2 + c) * ABYTES;
#pragma unroll
      for (int j = 0; j < 7; j++) {
        const bool hb = j > 3 || (j == 3 && t >= 2);
        const float r0 = hb ? rd[1] : rd[0], r1 = hb ? rd[3] : rd[2];
        *reinterpret_cast<uint32_t*>(img + slice_off(j, 0)) = pack(num[4 * j] * r0, num[4 * j + 1] * r0);
        *reinterpret_cast<uint32_t*>(img + slice_off(j, 1)) = pack(num[4 * j + 2] * r1, num[4 * j + 3] * r1);
      }
      STAMP(4 + layer * 12);
      gather(fl, img);
      STAMP(5 + layer * 12);
    }
    {
      float acc[28]; reg_def(acc);
      int prev = 0;
#pragma unroll 1
      for (int st = 0; st < 4; st++) {
        mbar_wait(barAc + (st * 7 + 3) / 4 * 8, apar);
        mbar_wait(barAc + (st * 7 + 6) / 4 * 8, apar);
        const uint64_t db = mkdesc(ring.acquire(), 4096, 1024, 1);
        wg_fence();
#pragma unroll
        for (int s = 0; s < 7; s++) { const int ks = st * 7 + s; mma_ss_56(acc, dA + ks * 128, db + s * 128, ks); }
        wg_commit();
        if (st > 0) { wg_wait<1>(); ring.release(prev, elect); }
        prev = ring.advance();
      }
      wg_wait<0>(); reg_fence(acc);
      ring.release(prev, elect);
      unsigned char* img = gImg + (size_t)(32 + G * 2 + c) * ABYTES;
#pragma unroll
      for (int hh = 0; hh < 2; hh++) {
        float s = 0.f, q = 0.f;
#pragma unroll
        for (int j = 0; j < 7; j++) {
          xs[j][hh] = pack(lo(xs[j][hh]) + acc[4 * j + 2 * hh], hi(xs[j][hh]) + acc[4 * j + 2 * hh + 1]);
          *reinterpret_cast<uint32_t*>(img + slice_off(j, hh)) = xs[j][hh];
          s += lo(xs[j][hh]) + hi(xs[j][hh]);
        }
        s += __shfl_xor_sync(~0u, s, 1); s += __shfl_xor_sync(~0u, s, 2);
        s *= 1.f / 56.f;
#pragma unroll
        for (int j = 0; j < 7; j++) { const float a = lo(xs[j][hh]) - s, b = hi(xs[j][hh]) - s; q = fmaf(a, a, q); q = fmaf(b, b, q); }
        q += __shfl_xor_sync(~0u, q, 1); q += __shfl_xor_sync(~0u, q, 2);
        if (t == 0) gStat[(size_t)(row0 + w * 16 + hh * 8 + g) * 8 + r] = make_float2(s, q);
      }
      STAMP(6 + layer * 12);
      gather(fl + 32, img);
      STAMP(7 + layer * 12);
    }
    {
      uint32_t hf[28][2];
      {
        float acc[112]; reg_def(acc);
        int prev = 0;
        load_stats(gStat);
#pragma unroll 1
        for (int st = 0; st < 14; st++) {
          if (!(st & 1)) mbar_wait(barAc + (st >> 1) * 8, apar);
          const uint64_t da = dA + st * 256, db = mkdesc(ring.acquire(), 2048, 512, 2);
          wg_fence();
          mma_ss_224(acc, da, db, st);
          mma_ss_224(acc, da + 128, db + 64, 1);
          wg_commit();
          if (st > 0) { wg_wait<1>(); ring.release(prev, elect); }
          prev = ring.advance();
        }
        finish_stats();
        mbar_wait(barCS + 8, 0);
        wg_wait<0>(); reg_fence(acc);
        ring.release(prev, elect);
        STAMP(8 + layer * 12);
        const float2* bs = reinterpret_cast<const float2*>(sg + OFF_B1) + t;
        const float2* cs = reinterpret_cast<const float2*>(sg + OFF_CS + 768) + t;
        const float mr0 = -mean[0] * rstd[0], mr1 = -mean[1] * rstd[1];
#pragma unroll
        for (int j = 0; j < 28; j++) {
          const float2 b = bs[4 * j], s = cs[4 * j];
          const float h0 = fmaxf(fmaf(acc[4 * j], rstd[0], fmaf(s.x, mr0, b.x)), 0.f), h1 = fmaxf(fmaf(acc[4 * j + 1], rstd[0], fmaf(s.y, mr0, b.y)), 0.f);
          const float h2 = fmaxf(fmaf(acc[4 * j + 2], rstd[1], fmaf(s.x, mr1, b.x)), 0.f), h3 = fmaxf(fmaf(acc[4 * j + 3], rstd[1], fmaf(s.y, mr1, b.y)), 0.f);
          hf[j][0] = pack(h0 * h0, h1 * h1); hf[j][1] = pack(h2 * h2, h3 * h3);
        }
      }
      unsigned char* pdst = gP + (size_t)(((G * 2 + c) * 8 + 2 * w) * 8 + r) * 7168 + lane * 8;
      uint2 pk[8] = {};
#pragma unroll 1
      for (int ch = 0; ch < 7; ch++) {
        float acc[32]; reg_def(acc);
        int sl0 = 0, sl1 = 0;
#pragma unroll
        for (int hk = 0; hk < 2; hk++) {
          const uint64_t db = mkdesc(ring.acquire(), 4096, 1024, 1);
          wg_fence();
#pragma unroll
          for (int s = 0; s < 7; s++) { const int ks = hk * 7 + s; mma_rs_64(acc, hf[2 * ks][0], hf[2 * ks][1], hf[2 * ks + 1][0], hf[2 * ks + 1][1], db + s * 128, ks); }
          wg_commit();
          if (hk) sl1 = ring.advance(); else sl0 = ring.advance();
        }
        if (ch > 0) {
#pragma unroll
          for (int i = 0; i < 8; i++) *reinterpret_cast<uint2*>(pdst + (i & 1) * (8 * 7168) + (i >> 1) * 256) = pk[i];
          pdst += 1024;
        }
        wg_wait<1>(); ring.release(sl0, elect);
        wg_wait<0>(); reg_fence(acc); ring.release(sl1, elect);
#pragma unroll
        for (int i = 0; i < 8; i++) {
          const int b = (i >> 1) * 8 + (i & 1) * 2;
          pk[i] = make_uint2(pack(acc[b], acc[b + 1]), pack(acc[b + 4], acc[b + 5]));
        }
      }
#pragma unroll
      for (int i = 0; i < 8; i++) *reinterpret_cast<uint2*>(pdst + (i & 1) * (8 * 7168) + (i >> 1) * 256) = pk[i];
      STAMP(9 + layer * 12);
    }
    {
      uint32_t bx[14];
#pragma unroll
      for (int j = 0; j < 14; j++) bx[j] = __ldg(reinterpret_cast<const uint32_t*>(b2 + w * 112 + j * 8 + 2 * t));
      __syncwarp();
      if (lane == 0) { flag_arrive(fl + (3 + w) * 32); flag_wait(fl + (3 + (r >> 1)) * 32, epoch * 8); }
      __syncwarp();
      STAMP(10 + layer * 12);
      const unsigned char* psrc = gP + (size_t)(((G * 2 + c) * 8 + r) * 8) * 7168 + w * 1792 + lane * 8;
      unsigned char* img = gImg + (size_t)(64 + G * 2 + c) * ABYTES;
      uint2 pv[8][7];
#pragma unroll
      for (int s = 0; s < 8; s++)
#pragma unroll
        for (int i = 0; i < 7; i++) pv[s][i] = ldcg2(psrc + s * 7168 + i * 256);
      const uint32_t off = w * 14336 + r * 128 + lane * 4;
      unsigned char* dst = layer ? reinterpret_cast<unsigned char*>(out + (size_t)(row0 + r * 8 + g) * DM + w * 112 + 2 * t) : img + off;
      float sm = 0.f, q = 0.f;
#pragma unroll
      for (int j = 0; j < 14; j++) {
        float y0 = lo(bx[j]), y1 = hi(bx[j]);
        const uint32_t xo = lds32(abuf + off + j * 1024);
        y0 += lo(xo); y1 += hi(xo);
#pragma unroll
        for (int s = 0; s < 8; s++) { const uint32_t u = (j & 1) ? pv[s][j >> 1].y : pv[s][j >> 1].x; y0 += lo(u); y1 += hi(u); }
        bx[j] = pack(y0, y1);
        *reinterpret_cast<uint32_t*>(dst + j * (layer ? 16 : 1024)) = bx[j];
        sm += lo(bx[j]) + hi(bx[j]);
      }
      if (layer) break;
      sm += __shfl_xor_sync(~0u, sm, 1); sm += __shfl_xor_sync(~0u, sm, 2);
      sm *= 1.f / 112.f;
#pragma unroll
      for (int j = 0; j < 14; j++) { const float a = lo(bx[j]) - sm, b = hi(bx[j]) - sm; q = fmaf(a, a, q); q = fmaf(b, b, q); }
      q += __shfl_xor_sync(~0u, q, 1); q += __shfl_xor_sync(~0u, q, 2);
      if (t < 2) gStat[(size_t)(2048 + row0 + r * 8 + g) * 8 + 2 * w + t] = make_float2(sm, q * 0.5f);
      STAMP(11);
      gather(fl + 64, img);
      STAMP(12);
    }
  }
  STAMP(30);
  if (tid == 0) asm volatile("red.relaxed.gpu.global.add.u32 [%0], 1;" ::"l"(gFlag + FL_DONE * 32) : "memory");
  }
}

typedef CUresult (*EncFn)(CUtensorMap*, CUtensorMapDataType, cuuint32_t, void*, const cuuint64_t*, const cuuint64_t*,
                          const cuuint32_t*, const cuuint32_t*, CUtensorMapInterleave, CUtensorMapSwizzle,
                          CUtensorMapL2promotion, CUtensorMapFloatOOBfill);

void make_map(EncFn enc, CUtensorMap* m, void* p, int rank, uint64_t d0, uint64_t d1, uint64_t d2, uint64_t s1, uint64_t s2,
              uint32_t b0, uint32_t b1, uint32_t b2, CUtensorMapSwizzle sw) {
  cuuint64_t dims[3] = {d0, d1, d2}, strides[2] = {s1, s2};
  cuuint32_t box[3] = {b0, b1, b2}, es[3] = {1, 1, 1};
  enc(m, CU_TENSOR_MAP_DATA_TYPE_BFLOAT16, rank, p, dims, strides, box, es, CU_TENSOR_MAP_INTERLEAVE_NONE, sw,
      CU_TENSOR_MAP_L2_PROMOTION_L2_128B, CU_TENSOR_MAP_FLOAT_OOB_FILL_NONE);
}

}

extern "C" void kernel_launch(void* const* d_in, const int* in_sizes, int n_in, void* d_out, int out_size) {
  static EncFn enc = nullptr;
  if (!enc) {
    cudaDriverEntryPointQueryResult st;
    void* fn = nullptr;
    cudaGetDriverEntryPoint("cuTensorMapEncodeTiled", &fn, cudaEnableDefault, &st);
    enc = (EncFn)fn;
    cudaFuncSetAttribute(fused_kernel, cudaFuncAttributeMaxDynamicSharedMemorySize, SMEM_BYTES);
  }
  CUtensorMap mQKV, mWO, mW1, mW2;
  make_map(enc, &mQKV, d_in[1], 3, 448, 448, 3, 2688, 896, 64, 32, 3, CU_TENSOR_MAP_SWIZZLE_128B);
  make_map(enc, &mWO, d_in[3], 2, 448, 448, 1, 896, 0, 64, 112, 1, CU_TENSOR_MAP_SWIZZLE_128B);
  make_map(enc, &mW1, d_in[5], 3, 32, 448, 56, 3584, 64, 32, 32, 7, CU_TENSOR_MAP_SWIZZLE_64B);
  make_map(enc, &mW2, d_in[7], 2, 448, 1792, 1, 896, 0, 64, 112, 1, CU_TENSOR_MAP_SWIZZLE_128B);
  fused_kernel<<<NCTA, 384, SMEM_BYTES, cudaStreamPerThread>>>(
      mQKV, mWO, mW1, mW2, (const __nv_bfloat16*)d_in[0], (const __nv_bfloat16*)d_in[2], (const __nv_bfloat16*)d_in[6],
      (const __nv_bfloat16*)d_in[8], (const __nv_bfloat16*)d_in[1], (const __nv_bfloat16*)d_in[3], (const __nv_bfloat16*)d_in[5],
      (const __nv_bfloat16*)d_in[7], (__nv_bfloat16*)d_out);
}
```

```cpp
#include <cuda_runtime.h>
#include <cuda_bf16.h>
#include <cuda.h>
#include <stdint.h>

namespace {

constexpr int DM = 448, NCTA = 128;
constexpr int ABYTES = 57344;
constexpr int SLOT = 14336, NSLOT = 7;
constexpr int OFF_RING = 2 * ABYTES;
constexpr int OFF_WPHI = OFF_RING + NSLOT * SLOT;
constexpr int OFF_B1 = OFF_WPHI + 8192;
constexpr int OFF_CS = OFF_B1 + 896;
constexpr int OFF_BAR = OFF_CS + 1664;
constexpr int SMEM_BYTES = OFF_BAR + 272 + 1024;
constexpr int TILES_PER_LAYER = 46;

__device__ __align__(1024) unsigned char gP[16 * 2 * 8 * 8 * 7168];
__device__ __align__(1024) unsigned char gImg[3 * 32 * ABYTES];
__device__ __align__(1024) float2 gStat[2 * 2048 * 8];
__device__ __align__(1024) float4 gKV[2 * 8 * 2 * 5 * 128];
__device__ __align__(1024) float4 gCS[8 * 16 * 104];
__device__ __align__(128) unsigned gFlag[(2 * 32 * 7 + 32 + 1 + 16) * 32];
#define STAMP(i)

__device__ __forceinline__ uint32_t smem_u32(const void* p) { return (uint32_t)__cvta_generic_to_shared(p); }
__device__ __forceinline__ void mbar_init(uint32_t b, int c) { asm volatile("mbarrier.init.shared::cta.b64 [%0], %1;" ::"r"(b), "r"(c)); }
__device__ __forceinline__ void mbar_expect(uint32_t b, int bytes) { asm volatile("mbarrier.arrive.expect_tx.shared::cta.b64 _, [%0], %1;" ::"r"(b), "r"(bytes) : "memory"); }
__device__ __forceinline__ void mbar_arrive(uint32_t b) { asm volatile("mbarrier.arrive.shared::cta.b64 _, [%0];" ::"r"(b) : "memory"); }
__device__ __forceinline__ void mbar_wait(uint32_t b, int par) {
  uint32_t ok; int n = 0;
  while (true) {
    asm volatile("{.reg .pred p; mbarrier.try_wait.parity.shared::cta.b64 p, [%1], %2; selp.u32 %0,1,0,p;}" : "=r"(ok) : "r"(b), "r"(par) : "memory");
    if (ok) break;
    if (++n > (1 << 22)) break;
  }
}
__device__ __forceinline__ void flag_wait(const unsigned* f, unsigned target) {
  unsigned v; int n = 0;
  while (true) {
    asm volatile("ld.acquire.gpu.global.u32 %0, [%1];" : "=r"(v) : "l"(f) : "memory");
    if ((int)(v - target) >= 0) break;
    if (++n > (1 << 21)) break;
  }
}
__device__ __forceinline__ void flag_arrive(unsigned* f) { asm volatile("red.release.gpu.global.add.u32 [%0], 1;" ::"l"(f) : "memory"); }
__device__ __forceinline__ void fence_async() { asm volatile("fence.proxy.async.global;" ::: "memory"); }
__device__ __forceinline__ void fence_async_smem() { asm volatile("fence.proxy.async.shared::cta;" ::: "memory"); }
template <int ID, int N> __device__ __forceinline__ void bar_sync() { asm volatile("bar.sync %0, %1;" ::"n"(ID), "n"(N) : "memory"); }
__device__ __forceinline__ void bar_wg(int c) { if (c) bar_sync<2, 128>(); else bar_sync<1, 128>(); }
__device__ __forceinline__ void wg_fence() { asm volatile("wgmma.fence.sync.aligned;" ::: "memory"); }
__device__ __forceinline__ void wg_commit() { asm volatile("wgmma.commit_group.sync.aligned;" ::: "memory"); }
template <int N> __device__ __forceinline__ void wg_wait() { asm volatile("wgmma.wait_group.sync.aligned %0;" ::"n"(N) : "memory"); }
template <int N> __device__ __forceinline__ void reg_fence(float (&d)[N]) {
#pragma unroll
  for (int i = 0; i < N; i++) asm volatile("" : "+f"(d[i])::"memory");
}
template <int N> __device__ __forceinline__ void reg_def(float (&d)[N]) {
#pragma unroll
  for (int i = 0; i < N; i++) d[i] = 0.f;
}
__device__ __forceinline__ uint64_t mkdesc(uint32_t addr, uint32_t lbo, uint32_t sbo, uint64_t swz) {
  return (uint64_t)((addr & 0x3FFFF) >> 4) | ((uint64_t)(lbo >> 4) << 16) | ((uint64_t)(sbo >> 4) << 32) | (swz << 62);
}
__device__ __forceinline__ uint32_t pack(float a, float b) {
  uint32_t r; asm("cvt.rn.bf16x2.f32 %0, %1, %2;" : "=r"(r) : "f"(b), "f"(a)); return r;
}
__device__ __forceinline__ float lo(uint32_t u) { return __uint_as_float(u << 16); }
__device__ __forceinline__ float hi(uint32_t u) { return __uint_as_float(u & 0xFFFF0000u); }
__device__ __forceinline__ float ex2(float x) { float y; asm("ex2.approx.ftz.f32 %0, %1;" : "=f"(y) : "f"(x)); return y; }
__device__ __forceinline__ void stsm4(uint32_t a, uint32_t r0, uint32_t r1, uint32_t r2, uint32_t r3) {
  asm volatile("stmatrix.sync.aligned.m8n8.x4.shared.b16 [%0], {%1,%2,%3,%4};" ::"r"(a), "r"(r0), "r"(r1), "r"(r2), "r"(r3) : "memory");
}
__device__ __forceinline__ void tma3(uint32_t dst, const CUtensorMap* m, int c0, int c1, int c2, uint32_t bar) {
  asm volatile("cp.async.bulk.tensor.3d.shared::cluster.global.mbarrier::complete_tx::bytes [%0], [%1, {%3,%4,%5}], [%2];"
               ::"r"(dst), "l"(m), "r"(bar), "r"(c0), "r"(c1), "r"(c2) : "memory");
}
__device__ __forceinline__ void tma2(uint32_t dst, const CUtensorMap* m, int c0, int c1, uint32_t bar) {
  asm volatile("cp.async.bulk.tensor.2d.shared::cluster.global.mbarrier::complete_tx::bytes [%0], [%1, {%3,%4}], [%2];"
               ::"r"(dst), "l"(m), "r"(bar), "r"(c0), "r"(c1) : "memory");
}
__device__ __forceinline__ uint32_t lds32(uint32_t a) { uint32_t v; asm volatile("ld.shared.u32 %0, [%1];" : "=r"(v) : "r"(a) : "memory"); return v; }
__device__ __forceinline__ void bulk_ld(uint32_t dst, const void* src, int bytes, uint32_t bar) {
  asm volatile("cp.async.bulk.shared::cluster.global.mbarrier::complete_tx::bytes [%0], [%1], %2, [%3];" ::"r"(dst), "l"(src), "r"(bytes), "r"(bar) : "memory");
}
__device__ __forceinline__ uint4 ldcg4(const void* p) {
  uint4 v; asm volatile("ld.global.cg.v4.u32 {%0,%1,%2,%3}, [%4];" : "=r"(v.x), "=r"(v.y), "=r"(v.z), "=r"(v.w) : "l"(p) : "memory"); return v;
}

__device__ __forceinline__ uint2 ldcg2(const void* p) {
  uint2 v; asm volatile("ld.global.cg.v2.u32 {%0,%1}, [%2];" : "=r"(v.x), "=r"(v.y) : "l"(p) : "memory"); return v;
}

__device__ __forceinline__ void mma_ss_184(float (&d)[92], uint64_t da, uint64_t db, int acc) {
  asm volatile("{.reg .pred p; setp.ne.b32 p, %94, 0;\n"
    "wgmma.mma_async.sync.aligned.m64n184k16.f32.bf16.bf16 {%0,%1,%2,%3,%4,%5,%6,%7,%8,%9,%10,%11,%12,%13,%14,%15,%16,%17,%18,%19,%20,%21,%22,%23,%24,%25,%26,%27,%28,%29,%30,%31,%32,%33,%34,%35,%36,%37,%38,%39,%40,%41,%42,%43,%44,%45,%46,%47,%48,%49,%50,%51,%52,%53,%54,%55,%56,%57,%58,%59,%60,%61,%62,%63,%64,%65,%66,%67,%68,%69,%70,%71,%72,%73,%74,%75,%76,%77,%78,%79,%80,%81,%82,%83,%84,%85,%86,%87,%88,%89,%90,%91}, %92, %93, p, 1, 1, 0, 1;}\n"
    : "+f"(d[0]),"+f"(d[1]),"+f"(d[2]),"+f"(d[3]),"+f"(d[4]),"+f"(d[5]),"+f"(d[6]),"+f"(d[7]),"+f"(d[8]),"+f"(d[9]),"+f"(d[10]),"+f"(d[11]),"+f"(d[12]),"+f"(d[13]),"+f"(d[14]),"+f"(d[15]),"+f"(d[16]),"+f"(d[17]),"+f"(d[18]),"+f"(d[19]),"+f"(d[20]),"+f"(d[21]),"+f"(d[22]),"+f"(d[23]),"+f"(d[24]),"+f"(d[25]),"+f"(d[26]),"+f"(d[27]),"+f"(d[28]),"+f"(d[29]),"+f"(d[30]),"+f"(d[31]),"+f"(d[32]),"+f"(d[33]),"+f"(d[34]),"+f"(d[35]),"+f"(d[36]),"+f"(d[37]),"+f"(d[38]),"+f"(d[39]),"+f"(d[40]),"+f"(d[41]),"+f"(d[42]),"+f"(d[43]),"+f"(d[44]),"+f"(d[45]),"+f"(d[46]),"+f"(d[47]),"+f"(d[48]),"+f"(d[49]),"+f"(d[50]),"+f"(d[51]),"+f"(d[52]),"+f"(d[53]),"+f"(d[54]),"+f"(d[55]),"+f"(d[56]),"+f"(d[57]),"+f"(d[58]),"+f"(d[59]),"+f"(d[60]),"+f"(d[61]),"+f"(d[62]),"+f"(d[63]),"+f"(d[64]),"+f"(d[65]),"+f"(d[66]),"+f"(d[67]),"+f"(d[68]),"+f"(d[69]),"+f"(d[70]),"+f"(d[71]),"+f"(d[72]),"+f"(d[73]),"+f"(d[74]),"+f"(d[75]),"+f"(d[76]),"+f"(d[77]),"+f"(d[78]),"+f"(d[79]),"+f"(d[80]),"+f"(d[81]),"+f"(d[82]),"+f"(d[83]),"+f"(d[84]),"+f"(d[85]),"+f"(d[86]),"+f"(d[87]),"+f"(d[88]),"+f"(d[89]),"+f"(d[90]),"+f"(d[91])
    : "l"(da), "l"(db), "r"(acc));
}
__device__ __forceinline__ void mma_ss_224(float (&d)[112], uint64_t da, uint64_t db, int acc) {
  asm volatile("{.reg .pred p; setp.ne.b32 p, %114, 0;\n"
    "wgmma.mma_async.sync.aligned.m64n224k16.f32.bf16.bf16 {%0,%1,%2,%3,%4,%5,%6,%7,%8,%9,%10,%11,%12,%13,%14,%15,%16,%17,%18,%19,%20,%21,%22,%23,%24,%25,%26,%27,%28,%29,%30,%31,%32,%33,%34,%35,%36,%37,%38,%39,%40,%41,%42,%43,%44,%45,%46,%47,%48,%49,%50,%51,%52,%53,%54,%55,%56,%57,%58,%59,%60,%61,%62,%63,%64,%65,%66,%67,%68,%69,%70,%71,%72,%73,%74,%75,%76,%77,%78,%79,%80,%81,%82,%83,%84,%85,%86,%87,%88,%89,%90,%91,%92,%93,%94,%95,%96,%97,%98,%99,%100,%101,%102,%103,%104,%105,%106,%107,%108,%109,%110,%111}, %112, %113, p, 1, 1, 0, 1;}\n"
    : "+f"(d[0]),"+f"(d[1]),"+f"(d[2]),"+f"(d[3]),"+f"(d[4]),"+f"(d[5]),"+f"(d[6]),"+f"(d[7]),"+f"(d[8]),"+f"(d[9]),"+f"(d[10]),"+f"(d[11]),"+f"(d[12]),"+f"(d[13]),"+f"(d[14]),"+f"(d[15]),"+f"(d[16]),"+f"(d[17]),"+f"(d[18]),"+f"(d[19]),"+f"(d[20]),"+f"(d[21]),"+f"(d[22]),"+f"(d[23]),"+f"(d[24]),"+f"(d[25]),"+f"(d[26]),"+f"(d[27]),"+f"(d[28]),"+f"(d[29]),"+f"(d[30]),"+f"(d[31]),"+f"(d[32]),"+f"(d[33]),"+f"(d[34]),"+f"(d[35]),"+f"(d[36]),"+f"(d[37]),"+f"(d[38]),"+f"(d[39]),"+f"(d[40]),"+f"(d[41]),"+f"(d[42]),"+f"(d[43]),"+f"(d[44]),"+f"(d[45]),"+f"(d[46]),"+f"(d[47]),"+f"(d[48]),"+f"(d[49]),"+f"(d[50]),"+f"(d[51]),"+f"(d[52]),"+f"(d[53]),"+f"(d[54]),"+f"(d[55]),"+f"(d[56]),"+f"(d[57]),"+f"(d[58]),"+f"(d[59]),"+f"(d[60]),"+f"(d[61]),"+f"(d[62]),"+f"(d[63]),"+f"(d[64]),"+f"(d[65]),"+f"(d[66]),"+f"(d[67]),"+f"(d[68]),"+f"(d[69]),"+f"(d[70]),"+f"(d[71]),"+f"(d[72]),"+f"(d[73]),"+f"(d[74]),"+f"(d[75]),"+f"(d[76]),"+f"(d[77]),"+f"(d[78]),"+f"(d[79]),"+f"(d[80]),"+f"(d[81]),"+f"(d[82]),"+f"(d[83]),"+f"(d[84]),"+f"(d[85]),"+f"(d[86]),"+f"(d[87]),"+f"(d[88]),"+f"(d[89]),"+f"(d[90]),"+f"(d[91]),"+f"(d[92]),"+f"(d[93]),"+f"(d[94]),"+f"(d[95]),"+f"(d[96]),"+f"(d[97]),"+f"(d[98]),"+f"(d[99]),"+f"(d[100]),"+f"(d[101]),"+f"(d[102]),"+f"(d[103]),"+f"(d[104]),"+f"(d[105]),"+f"(d[106]),"+f"(d[107]),"+f"(d[108]),"+f"(d[109]),"+f"(d[110]),"+f"(d[111])
    : "l"(da), "l"(db), "r"(acc));
}
__device__ __forceinline__ void mma_ss_56(float (&d)[28], uint64_t da, uint64_t db, int acc) {
  asm volatile("{.reg .pred p; setp.ne.b32 p, %30, 0;\n"
    "wgmma.mma_async.sync.aligned.m64n56k16.f32.bf16.bf16 {%0,%1,%2,%3,%4,%5,%6,%7,%8,%9,%10,%11,%12,%13,%14,%15,%16,%17,%18,%19,%20,%21,%22,%23,%24,%25,%26,%27}, %28, %29, p, 1, 1, 0, 1;}\n"
    : "+f"(d[0]),"+f"(d[1]),"+f"(d[2]),"+f"(d[3]),"+f"(d[4]),"+f"(d[5]),"+f"(d[6]),"+f"(d[7]),"+f"(d[8]),"+f"(d[9]),"+f"(d[10]),"+f"(d[11]),"+f"(d[12]),"+f"(d[13]),"+f"(d[14]),"+f"(d[15]),"+f"(d[16]),"+f"(d[17]),"+f"(d[18]),"+f"(d[19]),"+f"(d[20]),"+f"(d[21]),"+f"(d[22]),"+f"(d[23]),"+f"(d[24]),"+f"(d[25]),"+f"(d[26]),"+f"(d[27])
    : "l"(da), "l"(db), "r"(acc));
}
__device__ __forceinline__ void mma_rs_56(float (&d)[28], uint32_t a0, uint32_t a1, uint32_t a2, uint32_t a3, uint64_t db, int acc) {
  asm volatile("{.reg .pred p; setp.ne.b32 p, %33, 0;\n"
    "wgmma.mma_async.sync.aligned.m64n56k16.f32.bf16.bf16 {%0,%1,%2,%3,%4,%5,%6,%7,%8,%9,%10,%11,%12,%13,%14,%15,%16,%17,%18,%19,%20,%21,%22,%23,%24,%25,%26,%27}, {%28,%29,%30,%31}, %32, p, 1, 1, 1;}\n"
    : "+f"(d[0]),"+f"(d[1]),"+f"(d[2]),"+f"(d[3]),"+f"(d[4]),"+f"(d[5]),"+f"(d[6]),"+f"(d[7]),"+f"(d[8]),"+f"(d[9]),"+f"(d[10]),"+f"(d[11]),"+f"(d[12]),"+f"(d[13]),"+f"(d[14]),"+f"(d[15]),"+f"(d[16]),"+f"(d[17]),"+f"(d[18]),"+f"(d[19]),"+f"(d[20]),"+f"(d[21]),"+f"(d[22]),"+f"(d[23]),"+f"(d[24]),"+f"(d[25]),"+f"(d[26]),"+f"(d[27])
    : "r"(a0), "r"(a1), "r"(a2), "r"(a3), "l"(db), "r"(acc));
}
__device__ __forceinline__ void mma_ss_64t(float (&d)[32], uint64_t da, uint64_t db, int acc) {
  asm volatile("{.reg .pred p; setp.ne.b32 p, %34, 0;\n"
    "wgmma.mma_async.sync.aligned.m64n64k16.f32.bf16.bf16 {%0,%1,%2,%3,%4,%5,%6,%7,%8,%9,%10,%11,%12,%13,%14,%15,%16,%17,%18,%19,%20,%21,%22,%23,%24,%25,%26,%27,%28,%29,%30,%31}, %32, %33, p, 1, 1, 1, 1;}\n"
    : "+f"(d[0]),"+f"(d[1]),"+f"(d[2]),"+f"(d[3]),"+f"(d[4]),"+f"(d[5]),"+f"(d[6]),"+f"(d[7]),"+f"(d[8]),"+f"(d[9]),"+f"(d[10]),"+f"(d[11]),"+f"(d[12]),"+f"(d[13]),"+f"(d[14]),"+f"(d[15]),"+f"(d[16]),"+f"(d[17]),"+f"(d[18]),"+f"(d[19]),"+f"(d[20]),"+f"(d[21]),"+f"(d[22]),"+f"(d[23]),"+f"(d[24]),"+f"(d[25]),"+f"(d[26]),"+f"(d[27]),"+f"(d[28]),"+f"(d[29]),"+f"(d[30]),"+f"(d[31])
    : "l"(da), "l"(db), "r"(acc));
}
__device__ __forceinline__ void mma_rs_64(float (&d)[32], uint32_t a0, uint32_t a1, uint32_t a2, uint32_t a3, uint64_t db, int acc) {
  asm volatile("{.reg .pred p; setp.ne.b32 p, %37, 0;\n"
    "wgmma.mma_async.sync.aligned.m64n64k16.f32.bf16.bf16 {%0,%1,%2,%3,%4,%5,%6,%7,%8,%9,%10,%11,%12,%13,%14,%15,%16,%17,%18,%19,%20,%21,%22,%23,%24,%25,%26,%27,%28,%29,%30,%31}, {%32,%33,%34,%35}, %36, p, 1, 1, 1;}\n"
    : "+f"(d[0]),"+f"(d[1]),"+f"(d[2]),"+f"(d[3]),"+f"(d[4]),"+f"(d[5]),"+f"(d[6]),"+f"(d[7]),"+f"(d[8]),"+f"(d[9]),"+f"(d[10]),"+f"(d[11]),"+f"(d[12]),"+f"(d[13]),"+f"(d[14]),"+f"(d[15]),"+f"(d[16]),"+f"(d[17]),"+f"(d[18]),"+f"(d[19]),"+f"(d[20]),"+f"(d[21]),"+f"(d[22]),"+f"(d[23]),"+f"(d[24]),"+f"(d[25]),"+f"(d[26]),"+f"(d[27]),"+f"(d[28]),"+f"(d[29]),"+f"(d[30]),"+f"(d[31])
    : "r"(a0), "r"(a1), "r"(a2), "r"(a3), "l"(db), "r"(acc));
}

__device__ __forceinline__ void dual_softmax(const float (&p)[28], uint32_t (&phi)[4][7]) {
  constexpr float L2E = 1.4426950408889634f;
#pragma unroll
  for (int i = 0; i < 4; i++) {
    float mx = p[i], mn = p[i];
#pragma unroll
    for (int j = 1; j < 7; j++) { mx = fmaxf(mx, p[4 * j + i]); mn = fminf(mn, p[4 * j + i]); }
    mx = fmaxf(mx, __shfl_xor_sync(~0u, mx, 1)); mn = fminf(mn, __shfl_xor_sync(~0u, mn, 1));
    mx = fmaxf(mx, __shfl_xor_sync(~0u, mx, 2)); mn = fminf(mn, __shfl_xor_sync(~0u, mn, 2));
    float a[7], b[7], sa = 0.f, sb = 0.f;
    const float mxl = mx * L2E, mnl = mn * L2E;
#pragma unroll
    for (int j = 0; j < 7; j++) {
      a[j] = ex2(fmaf(p[4 * j + i], L2E, -mxl)); b[j] = ex2(fmaf(p[4 * j + i], -L2E, mnl));
      sa += a[j]; sb += b[j];
    }
    sa += __shfl_xor_sync(~0u, sa, 1); sb += __shfl_xor_sync(~0u, sb, 1);
    sa += __shfl_xor_sync(~0u, sa, 2); sb += __shfl_xor_sync(~0u, sb, 2);
    const float ra = __fdividef(1.f, sa), rb = __fdividef(1.f, sb);
#pragma unroll
    for (int j = 0; j < 7; j++) phi[i][j] = pack(a[j] * ra, b[j] * rb);
  }
}

struct Ring {
  uint32_t full, empty, base; int slot, par;
  __device__ __forceinline__ uint32_t acquire() { mbar_wait(full + slot * 8, par); return base + slot * SLOT; }
  __device__ __forceinline__ int advance() { int s = slot; if (++slot == NSLOT) { slot = 0; par ^= 1; } return s; }
  __device__ __forceinline__ void release(int s, bool elect) { if (elect) mbar_arrive(empty + s * 8); }
};
constexpr int FL_KV = 448, FL_CS = FL_KV + 16, FL_DONE = FL_KV + 32;

__global__ void __launch_bounds__(384, 1)
fused_kernel(const __grid_constant__ CUtensorMap mQKV, const __grid_constant__ CUtensorMap mWO,
             const __grid_constant__ CUtensorMap mW1, const __grid_constant__ CUtensorMap mW2,
             const __grid_constant__ CUtensorMap mX, const __nv_bfloat16* __restrict__ wphi,
             const __nv_bfloat16* __restrict__ b1, const __nv_bfloat16* __restrict__ b2,
             const __nv_bfloat16* __restrict__ wqkv, const __nv_bfloat16* __restrict__ wo, const __nv_bfloat16* __restrict__ w1,
             const __nv_bfloat16* __restrict__ w2, __nv_bfloat16* __restrict__ out) {
  extern __shared__ unsigned char smem_raw[];
  const uint32_t sb = (smem_u32(smem_raw) + 1023) & ~1023u;
  unsigned char* sg = smem_raw + (sb - smem_u32(smem_raw));
  const int tid = threadIdx.x, lane = tid & 31;
  const int G = blockIdx.x >> 3, r = blockIdx.x & 7;
  const uint32_t barFull = sb + OFF_BAR, barEmpty = barFull + 56, barA = barEmpty + 56, barCS = barA + 112, barX = barCS + 16;
  const int warp = __shfl_sync(~0u, tid >> 5, 0);
  if (lane == 0) {
    if (warp >= 10) {
      const int cc = warp - 10;
      mbar_init(barX + cc * 8, 1);
      fence_async_smem();
      mbar_expect(barX + cc * 8, ABYTES);
#pragma unroll 1
      for (int k = 0; k < 7; k++) tma2(sb + cc * ABYTES + k * 8192, &mX, 64 * k, G * 128 + 64 * cc, barX + cc * 8);
    } else if (warp < 7) { mbar_init(barFull + warp * 8, 1); mbar_init(barEmpty + warp * 8, 2); mbar_init(barA + warp * 8, 1); mbar_init(barA + 56 + warp * 8, 1); }
    else if (warp < 9) mbar_init(barCS + (warp - 7) * 8, 96);
    else
      asm volatile("cp.async.bulk.prefetch.L2.global [%0], %1;" ::"l"((const char*)wqkv + blockIdx.x * 9408), "r"(9408) : "memory");
    asm volatile("fence.mbarrier_init.release.cluster;" ::: "memory");
  }
  if (tid < 192) reinterpret_cast<float*>(sg + OFF_CS)[tid] = 0.f;
  __syncthreads();
  const int wgid = warp >> 2;
  if (wgid == 2) {
    asm volatile("setmaxnreg.dec.sync.aligned.u32 56;");
    if (tid == 256) {
      int slot = 0, par = 1;
      for (int it = 0; it < 2 * TILES_PER_LAYER; it++) {
        const int i = it >= TILES_PER_LAYER ? it - TILES_PER_LAYER : it;
        mbar_wait(barEmpty + slot * 8, par);
        const uint32_t dst = sb + OFF_RING + slot * SLOT, fb = barFull + slot * 8;
        mbar_expect(fb, i < 14 ? 12288 : SLOT);
        if (i < 14) tma3(dst, &mQKV, 56 * r, 32 * i, 0, fb);
        else if (i < 18) tma2(dst, &mWO, 56 * r, 112 * (i - 14), fb);
        else if (i < 32) tma3(dst, &mW1, 0, 32 * (i - 18), 7 * r, fb);
        else tma2(dst, &mW2, 64 * ((i - 32) >> 1), 224 * r + 112 * (i & 1), fb);
        if (++slot == NSLOT) { slot = 0; par ^= 1; }
      }
    } else if (tid >= 288) {
      unsigned ep;
      asm volatile("ld.relaxed.gpu.global.u32 %0, [%1];" : "=r"(ep) : "l"(gFlag + FL_DONE * 32) : "memory");
      const int idx = tid - 288;
      ep = (ep / NCTA + 1) * 3;
      if (G == 0) {
#pragma unroll 1
        for (int i = idx; i < 2 * 1280; i += 96) gKV[((i >= 1280) * 7 + r) * 1280 + i] = make_float4(0.f, 0.f, 0.f, 0.f);
        __syncwarp();
        if (lane == 0) flag_arrive(gFlag + (FL_CS + r) * 32);
      }
      mbar_wait(barFull + 48, 0);
      if (idx < 2) {
        const char* pf = idx ? (const char*)w2 + blockIdx.x * 12544 : (const char*)wo + blockIdx.x * 3136;
        asm volatile("cp.async.bulk.prefetch.L2.global [%0], %1;" ::"l"(pf), "r"(idx ? 12544 : 3136) : "memory");
      }
      if (lane == 0) flag_wait(gFlag + (FL_CS + r) * 32, ep);
      __syncwarp();
      mbar_arrive(barCS);
#pragma unroll 1
      for (int ps = 0; ps < 3; ps++) {
        const int nch = ps ? 14 : 21, ch = min(idx >> 2, nch - 1), p = ch / 7, k0 = G * 28 + (idx & 3) * 7;
        const uint4* src = ps ? reinterpret_cast<const uint4*>(w1 + (size_t)k0 * 1792 + 224 * r) + (ps - 1) * 14 + ch
                              : reinterpret_cast<const uint4*>(wqkv + (size_t)k0 * 1344 + p * 448 + 56 * r) + (ch - 7 * p);
        uint4 cu[7];
#pragma unroll
        for (int i = 0; i < 7; i++) cu[i] = __ldg(src + i * (ps ? 224 : 168));
        float s[8] = {};
#pragma unroll
        for (int i = 0; i < 7; i++) { s[0] += lo(cu[i].x); s[1] += hi(cu[i].x); s[2] += lo(cu[i].y); s[3] += hi(cu[i].y); s[4] += lo(cu[i].z); s[5] += hi(cu[i].z); s[6] += lo(cu[i].w); s[7] += hi(cu[i].w); }
#pragma unroll
        for (int i = 0; i < 8; i++) { s[i] += __shfl_xor_sync(~0u, s[i], 1); s[i] += __shfl_xor_sync(~0u, s[i], 2); }
        if ((idx & 3) < 2 && idx < nch * 4) gCS[(r * 16 + G) * 104 + (ps ? 10 + ps * 14 + ch : ch + p) * 2 + (idx & 1)] = (idx & 1) ? make_float4(s[4], s[5], s[6], s[7]) : make_float4(s[0], s[1], s[2], s[3]);
      }
      __syncwarp();
      if (lane == 0) { flag_arrive(gFlag + (FL_CS + 8 + r) * 32); flag_wait(gFlag + (FL_CS + 8 + r) * 32, ep * 16); }
      __syncwarp();
#pragma unroll 1
      for (int j = idx; j < 208; j += 96) {
        float2 v[16], a = make_float2(0.f, 0.f);
#pragma unroll
        for (int i = 0; i < 16; i++) v[i] = __ldcg(reinterpret_cast<const float2*>(gCS + (r * 16 + i) * 104) + j);
#pragma unroll
        for (int i = 0; i < 16; i++) { a.x += v[i].x; a.y += v[i].y; }
        reinterpret_cast<float2*>(sg + OFF_CS)[j] = a;
      }
      mbar_arrive(barCS + 8);
    }
  } else {
  asm volatile("setmaxnreg.inc.sync.aligned.u32 224;");
  const int c = wgid, w = warp & 3, g = lane >> 2, t = lane & 3;
  const bool elect = (tid & 127) == 0;
  const uint32_t abuf = sb + c * ABYTES, barAc = barA + c * 56;
  const int row0 = G * 128 + c * 64;
  unsigned epoch;
  asm volatile("ld.relaxed.gpu.global.u32 %0, [%1];" : "=r"(epoch) : "l"(gFlag + FL_DONE * 32) : "memory");
  STAMP(24);
  float mean[2], rstd[2];
  uint32_t wv[7];
#pragma unroll
  for (int i = 0; i < 7; i++)
    wv[i] = __ldg(reinterpret_cast<const unsigned short*>(wphi) + (56 * r + i * 8 + (tid >> 5)) * 28 + min(lane, 27));
  const uint32_t bv = __ldg(reinterpret_cast<const unsigned short*>(b1) + 224 * r + min(tid, 223));
  uint4 su[2] = {};
  uint32_t xs[7][2];
  {
    mbar_wait(barX + c * 8, 0);
    STAMP(25);
#pragma unroll
    for (int j = 0; j < 7; j++) {
      const int ci = 7 * r + j;
      const uint32_t a = abuf + (ci >> 3) * 8192 + (w * 16 + g) * 128 + (((ci & 7) ^ g) << 4) + t * 4;
      xs[j][0] = lds32(a); xs[j][1] = lds32(a + 1024);
    }
    __syncwarp();
#pragma unroll 1
    for (int hh = 0; hh < 2; hh++) {
      uint4* p = reinterpret_cast<uint4*>(sg + c * ABYTES + (w * 16 + hh * 8 + g) * 128) + t;
      uint4 v[14];
#pragma unroll
      for (int k = 0; k < 14; k++) v[k] = p[(k >> 1) * 512 + ((k ^ g) & 1) * 4];
      float sm = 0.f, q = 0.f;
#pragma unroll
      for (int k = 0; k < 14; k++) sm += (lo(v[k].x) + hi(v[k].x)) + (lo(v[k].y) + hi(v[k].y)) + (lo(v[k].z) + hi(v[k].z)) + (lo(v[k].w) + hi(v[k].w));
      sm += __shfl_xor_sync(~0u, sm, 1); sm += __shfl_xor_sync(~0u, sm, 2);
      sm *= 1.f / DM;
#pragma unroll
      for (int k = 0; k < 14; k++) {
        const uint32_t e[4] = {v[k].x, v[k].y, v[k].z, v[k].w};
#pragma unroll
        for (int z = 0; z < 4; z++) { const float a = lo(e[z]) - sm, b = hi(e[z]) - sm; q = fmaf(a, a, fmaf(b, b, q)); }
      }
      q += __shfl_xor_sync(~0u, q, 1); q += __shfl_xor_sync(~0u, q, 2);
      q = rsqrtf(q * (1.f / DM) + 1e-5f);
      sm *= -q;
#pragma unroll
      for (int k = 0; k < 14; k++)
        p[(k >> 1) * 512 + ((k ^ g) & 1) * 4] = make_uint4(pack(fmaf(lo(v[k].x), q, sm), fmaf(hi(v[k].x), q, sm)), pack(fmaf(lo(v[k].y), q, sm), fmaf(hi(v[k].y), q, sm)),
                                                           pack(fmaf(lo(v[k].z), q, sm), fmaf(hi(v[k].z), q, sm)), pack(fmaf(lo(v[k].w), q, sm), fmaf(hi(v[k].w), q, sm)));
    }
#pragma unroll
    for (int i = 0; i < 8; i++) {
      const int k = i * 8 + (tid >> 5);
      *reinterpret_cast<uint32_t*>(sg + OFF_WPHI + k * 128 + ((g ^ (k & 7)) << 4) + t * 4) = (i < 7 && lane < 28) ? wv[i % 7] << (k >= 28 ? 16 : 0) : 0u;
    }
    if (tid < 224) reinterpret_cast<uint32_t*>(sg + OFF_B1)[tid] = bv << 16;
    fence_async_smem();
    bar_sync<3, 256>();
    epoch = epoch / NCTA + 1;
    mean[0] = mean[1] = 0.f; rstd[0] = rstd[1] = 1.f;
  }
  STAMP(0);
  Ring ring{barFull, barEmpty, sb + OFF_RING, 0, 0};
  int apar = 1;
  const uint32_t stsm_off = (w * 16 + ((lane >> 3) & 1) * 8 + (lane & 7)) * 128;
  const uint32_t stsm_hi = lane >> 4;
  const uint64_t dA = mkdesc(abuf, 1024, 128, 0);

  auto gather = [&](unsigned* fl, const unsigned char* img) {
    __syncwarp();
    if (lane == 0) {
      flag_arrive(fl);
      STAMP(27);
      flag_wait(fl, epoch * 32);
      STAMP(28);
      fence_async();
      mbar_expect(barAc + w * 8, 8192); bulk_ld(abuf + w * 8192, img + w * 8192, 8192, barAc + w * 8);
      if (w < 3) { mbar_expect(barAc + 32 + w * 8, 8192); bulk_ld(abuf + 32768 + w * 8192, img + 32768 + w * 8192, 8192, barAc + 32 + w * 8); }
    }
    __syncwarp();
    apar ^= 1;
  };
  auto slice_off = [&](int j, int hh) -> uint32_t {
    return (7 * r + j) * 1024 + (w * 2 + hh) * 128 + lane * 4;
  };
  auto load_stats = [&](const float2* st) {
    mbar_wait(barAc, apar);
#pragma unroll
    for (int hh = 0; hh < 2; hh++) su[hh] = ldcg4(st + (size_t)(row0 + w * 16 + hh * 8 + g) * 8 + 2 * t);
  };
  auto finish_stats = [&]() {
#pragma unroll
    for (int hh = 0; hh < 2; hh++) {
      const float m0 = __uint_as_float(su[hh].x), m1 = __uint_as_float(su[hh].z);
      float m = m0 + m1;
      m += __shfl_xor_sync(~0u, m, 1); m += __shfl_xor_sync(~0u, m, 2);
      m *= 0.125f;
      float q = __uint_as_float(su[hh].y) + __uint_as_float(su[hh].w) + 56.f * ((m0 - m) * (m0 - m) + (m1 - m) * (m1 - m));
      q += __shfl_xor_sync(~0u, q, 1); q += __shfl_xor_sync(~0u, q, 2);
      mean[hh] = m; rstd[hh] = rsqrtf(q * (1.f / DM) + 1e-5f);
    }
  };

#pragma unroll 1
  for (int layer = 0; layer < 2; layer++) {
    unsigned* const fl = gFlag + (layer * 32 + G * 2 + c) * 7 * 32;
    uint32_t phiq[4][7];
    {
      float acc[92]; reg_def(acc);
      int prev = 0;
      const uint64_t dQ = layer ? dA : mkdesc(abuf, 16, 1024, 1);
      const int kstep = layer ? 128 : 2;
      if (layer) load_stats(gStat + 2048 * 8);
#pragma unroll 1
      for (int st = 0; st < 14; st++) {
        if (!(st & 1)) mbar_wait(barAc + (st >> 1) * 8, apar);
        const uint64_t da = dQ + (st >> 1) * 512 + (st & 1) * 2 * kstep, db = mkdesc(ring.acquire(), 4096, 1024, 1);
        wg_fence();
        mma_ss_184(acc, da, db, 1);
        mma_ss_184(acc, da + kstep, db + 128, 1);
        wg_commit();
        if (st > 0) { wg_wait<1>(); ring.release(prev, elect); }
        prev = ring.advance();
      }
      if (layer) {
        finish_stats();
#pragma unroll
        for (int j = 0; j < 7; j++) { xs[j][0] = lds32(abuf + slice_off(j, 0)); xs[j][1] = lds32(abuf + slice_off(j, 1)); }
      }
      wg_wait<0>(); reg_fence(acc);
      ring.release(prev, elect);
      STAMP(1 + layer * 12);
      uint32_t f[3][14];
      {
        const float2* cs = reinterpret_cast<const float2*>(sg + OFF_CS) + t;
        const float mr0 = -mean[0] * rstd[0], mr1 = -mean[1] * rstd[1];
#pragma unroll
        for (int p = 0; p < 3; p++)
#pragma unroll
          for (int j = 0; j < 7; j++) {
            const float2 s = cs[p * 32 + j * 4];
            const int b = p * 32 + j * 4;
            f[p][2 * j] = pack(fmaf(acc[b], rstd[0], s.x * mr0), fmaf(acc[b + 1], rstd[0], s.y * mr0));
            f[p][2 * j + 1] = pack(fmaf(acc[b + 2], rstd[1], s.x * mr1), fmaf(acc[b + 3], rstd[1], s.y * mr1));
          }
      }
      float pk[28], pq[28]; reg_def(pk); reg_def(pq);
      const uint64_t dW = mkdesc(sb + OFF_WPHI, 4096, 1024, 1);
      wg_fence();
#pragma unroll
      for (int s = 0; s < 4; s++)
        mma_rs_56(pk, f[1][4 * s], f[1][4 * s + 1], s < 3 ? f[1][(4 * s + 2) % 14] : 0u, s < 3 ? f[1][(4 * s + 3) % 14] : 0u, dW + s * 128, s);
      wg_commit();
#pragma unroll
      for (int s = 0; s < 4; s++)
        mma_rs_56(pq, f[0][4 * s], f[0][4 * s + 1], s < 3 ? f[0][(4 * s + 2) % 14] : 0u, s < 3 ? f[0][(4 * s + 3) % 14] : 0u, dW + s * 128, s);
      wg_commit();
      bar_wg(c);
      const uint32_t srow = abuf + stsm_off, ones = t == 0 ? 0x3F803F80u : 0u;
#pragma unroll
      for (int jp = 0; jp < 4; jp++)
        stsm4(srow + 16384 + (((2 * jp + stsm_hi) ^ (lane & 7)) << 4), f[2][4 * jp], f[2][4 * jp + 1],
              jp < 3 ? f[2][(4 * jp + 2) % 14] : ones, jp < 3 ? f[2][(4 * jp + 3) % 14] : ones);
      wg_wait<0>(); reg_fence(pk); reg_fence(pq);
#pragma unroll 1
      for (int pass = 0; pass < 2; pass++) {
        dual_softmax(pk, phiq);
        if (pass) break;
#pragma unroll
        for (int e = 0; e < 2; e++)
#pragma unroll
          for (int jp = 0; jp < 4; jp++)
            stsm4(srow + e * 8192 + (((2 * jp + stsm_hi) ^ (lane & 7)) << 4), phiq[e][2 * jp], phiq[2 + e][2 * jp],
                  jp < 3 ? phiq[e][(2 * jp + 1) % 7] : 0u, jp < 3 ? phiq[2 + e][(2 * jp + 1) % 7] : 0u);
        fence_async_smem();
        bar_sync<3, 256>();
        float kv[32]; reg_def(kv);
        const uint64_t dP = mkdesc(sb + c * 8192, 4096, 1024, 1), dV = mkdesc(sb + 16384, 4096, 1024, 1);
        wg_fence();
#pragma unroll
        for (int s = 0; s < 8; s++) mma_ss_64t(kv, dP + (s >> 2) * (ABYTES / 16) + (s & 3) * 128, dV + (s >> 2) * (ABYTES / 16) + (s & 3) * 128, s);
        wg_commit();
        mbar_wait(barCS, 0);
        wg_wait<0>(); reg_fence(kv);
        float4* kvg = gKV + ((layer * 8 + r) * 2 + c) * 640 + (tid & 127);
#pragma unroll
        for (int i = 0; i < 5; i++) {
          float v0, v1, v2, v3;
          if (i == 4) { v0 = kv[28]; v1 = kv[29]; v2 = kv[30]; v3 = kv[31]; }
          else { v0 = c ? kv[12 + 4 * i] : kv[4 * i]; v1 = c ? kv[13 + 4 * i] : kv[1 + 4 * i]; v2 = c ? kv[14 + 4 * i] : kv[2 + 4 * i]; v3 = c ? kv[15 + 4 * i] : kv[3 + 4 * i]; }
          const bool use = i == 4 ? t == 0 : (i == 0 ? (c == 0 || t >= 2) : (i == 3 ? (c == 1 || t < 2) : true));
          if (use) asm volatile("red.relaxed.gpu.global.add.v4.f32 [%0], {%1,%2,%3,%4};" ::"l"(kvg + i * 128), "f"(v0), "f"(v1), "f"(v2), "f"(v3) : "memory");
        }
        __syncwarp();
        if (lane == 0) flag_arrive(gFlag + (FL_KV + layer * 8 + r) * 32);
        __syncwarp();
        STAMP(2 + layer * 12);
#pragma unroll
        for (int i = 0; i < 28; i++) pk[i] = pq[i];
      }
    }
    {
      if (elect) flag_wait(gFlag + (FL_KV + layer * 8 + r) * 32, epoch * 128);
      bar_wg(c);
      STAMP(3 + layer * 12);
      const float4* kvg = gKV + (layer * 8 + r) * 1280 + (tid & 127);
      uint4 kk[2][5];
#pragma unroll
      for (int e = 0; e < 2; e++)
#pragma unroll
        for (int i = 0; i < 5; i++) kk[e][i] = ldcg4(kvg + e * 640 + i * 128);
      const uint32_t srow = abuf + 24576 + stsm_off;
#pragma unroll
      for (int e = 0; e < 2; e++) {
        uint32_t f[8][2];
#pragma unroll
        for (int j = 0; j < 8; j++) { f[j][0] = 0u; f[j][1] = 0u; }
#pragma unroll
        for (int i = 0; i < 4; i++) {
          f[i + 3 * e][0] = pack(__uint_as_float(kk[e][i].x), __uint_as_float(kk[e][i].y));
          f[i + 3 * e][1] = pack(__uint_as_float(kk[e][i].z), __uint_as_float(kk[e][i].w));
        }
        f[7][0] = e ? pack(0.f, __uint_as_float(kk[e][4].y)) : pack(__uint_as_float(kk[e][4].x), 0.f);
        f[7][1] = e ? pack(0.f, __uint_as_float(kk[e][4].w)) : pack(__uint_as_float(kk[e][4].z), 0.f);
#pragma unroll
        for (int jp = 0; jp < 4; jp++)
          stsm4(srow + e * 8192 + (((2 * jp + stsm_hi) ^ (lane & 7)) << 4), f[2 * jp][0], f[2 * jp][1], f[2 * jp + 1][0], f[2 * jp + 1][1]);
      }
      fence_async_smem();
      bar_wg(c);
      float num[32]; reg_def(num);
      const uint64_t dK = mkdesc(abuf + 24576, 4096, 1024, 1);
      wg_fence();
#pragma unroll
      for (int e = 0; e < 2; e++)
#pragma unroll
        for (int s = 0; s < 4; s++)
          mma_rs_64(num, phiq[e][2 * s], phiq[2 + e][2 * s], s < 3 ? phiq[e][(2 * s + 1) % 7] : 0u, s < 3 ? phiq[2 + e][(2 * s + 1) % 7] : 0u,
                    dK + e * 512 + s * 128, e + s);
      wg_commit();
      wg_wait<0>(); reg_fence(num);
      float rd[4];
#pragma unroll
      for (int i = 0; i < 4; i++) rd[i] = __fdividef(1.f, __shfl_sync(~0u, num[28 + i], lane & ~3) + 1e-6f);
      unsigned char* img = gImg + (size_t)(G * 2 + c) * ABYTES;
#pragma unroll
      for (int j = 0; j < 7; j++) {
        const bool hb = j > 3 || (j == 3 && t >= 2);
        const float r0 = hb ? rd[1] : rd[0], r1 = hb ? rd[3] : rd[2];
        *reinterpret_cast<uint32_t*>(img + slice_off(j, 0)) = pack(num[4 * j] * r0, num[4 * j + 1] * r0);
        *reinterpret_cast<uint32_t*>(img + slice_off(j, 1)) = pack(num[4 * j + 2] * r1, num[4 * j + 3] * r1);
      }
      STAMP(4 + layer * 12);
      gather(fl, img);
      STAMP(5 + layer * 12);
    }
    {
      float acc[28]; reg_def(acc);
      int prev = 0;
#pragma unroll 1
      for (int st = 0; st < 4; st++) {
        mbar_wait(barAc + (st * 7 + 3) / 4 * 8, apar);
        mbar_wait(barAc + (st * 7 + 6) / 4 * 8, apar);
        const uint64_t db = mkdesc(ring.acquire(), 4096, 1024, 1);
        wg_fence();
#pragma unroll
        for (int s = 0; s < 7; s++) { const int ks = st * 7 + s; mma_ss_56(acc, dA + ks * 128, db + s * 128, ks); }
        wg_commit();
        if (st > 0) { wg_wait<1>(); ring.release(prev, elect); }
        prev = ring.advance();
      }
      wg_wait<0>(); reg_fence(acc);
      ring.release(prev, elect);
      unsigned char* img = gImg + (size_t)(32 + G * 2 + c) * ABYTES;
#pragma unroll
      for (int hh = 0; hh < 2; hh++) {
        float s = 0.f, q = 0.f;
#pragma unroll
        for (int j = 0; j < 7; j++) {
          xs[j][hh] = pack(lo(xs[j][hh]) + acc[4 * j + 2 * hh], hi(xs[j][hh]) + acc[4 * j + 2 * hh + 1]);
          *reinterpret_cast<uint32_t*>(img + slice_off(j, hh)) = xs[j][hh];
          s += lo(xs[j][hh]) + hi(xs[j][hh]);
        }
        s += __shfl_xor_sync(~0u, s, 1); s += __shfl_xor_sync(~0u, s, 2);
        s *= 1.f / 56.f;
#pragma unroll
        for (int j = 0; j < 7; j++) { const float a = lo(xs[j][hh]) - s, b = hi(xs[j][hh]) - s; q = fmaf(a, a, q); q = fmaf(b, b, q); }
        q += __shfl_xor_sync(~0u, q, 1); q += __shfl_xor_sync(~0u, q, 2);
        if (t == 0) gStat[(size_t)(row0 + w * 16 + hh * 8 + g) * 8 + r] = make_float2(s, q);
      }
      STAMP(6 + layer * 12);
      gather(fl + 32, img);
      STAMP(7 + layer * 12);
    }
    {
      uint32_t hf[28][2];
      {
        float acc[112]; reg_def(acc);
        int prev = 0;
        load_stats(gStat);
#pragma unroll 1
        for (int st = 0; st < 14; st++) {
          if (!(st & 1)) mbar_wait(barAc + (st >> 1) * 8, apar);
          const uint64_t da = dA + st * 256, db = mkdesc(ring.acquire(), 2048, 512, 2);
          wg_fence();
          mma_ss_224(acc, da, db, st);
          mma_ss_224(acc, da + 128, db + 64, 1);
          wg_commit();
          if (st > 0) { wg_wait<1>(); ring.release(prev, elect); }
          prev = ring.advance();
        }
        finish_stats();
        mbar_wait(barCS + 8, 0);
        wg_wait<0>(); reg_fence(acc);
        ring.release(prev, elect);
        STAMP(8 + layer * 12);
        const float2* bs = reinterpret_cast<const float2*>(sg + OFF_B1) + t;
        const float2* cs = reinterpret_cast<const float2*>(sg + OFF_CS + 768) + t;
        const float mr0 = -mean[0] * rstd[0], mr1 = -mean[1] * rstd[1];
#pragma unroll
        for (int j = 0; j < 28; j++) {
          const float2 b = bs[4 * j], s = cs[4 * j];
          const float h0 = fmaxf(fmaf(acc[4 * j], rstd[0], fmaf(s.x, mr0, b.x)), 0.f), h1 = fmaxf(fmaf(acc[4 * j + 1], rstd[0], fmaf(s.y, mr0, b.y)), 0.f);
          const float h2 = fmaxf(fmaf(acc[4 * j + 2], rstd[1], fmaf(s.x, mr1, b.x)), 0.f), h3 = fmaxf(fmaf(acc[4 * j + 3], rstd[1], fmaf(s.y, mr1, b.y)), 0.f);
          hf[j][0] = pack(h0 * h0, h1 * h1); hf[j][1] = pack(h2 * h2, h3 * h3);
        }
      }
      unsigned char* pdst = gP + (size_t)(((G * 2 + c) * 8 + 2 * w) * 8 + r) * 7168 + lane * 8;
      uint2 pk[8] = {};
#pragma unroll 1
      for (int ch = 0; ch < 7; ch++) {
        float acc[32]; reg_def(acc);
        int sl0 = 0, sl1 = 0;
#pragma unroll
        for (int hk = 0; hk < 2; hk++) {
          const uint64_t db = mkdesc(ring.acquire(), 4096, 1024, 1);
          wg_fence();
#pragma unroll
          for (int s = 0; s < 7; s++) { const int ks = hk * 7 + s; mma_rs_64(acc, hf[2 * ks][0], hf[2 * ks][1], hf[2 * ks + 1][0], hf[2 * ks + 1][1], db + s * 128, ks); }
          wg_commit();
          if (hk) sl1 = ring.advance(); else sl0 = ring.advance();
        }
        if (ch > 0) {
#pragma unroll
          for (int i = 0; i < 8; i++) *reinterpret_cast<uint2*>(pdst + (i & 1) * (8 * 7168) + (i >> 1) * 256) = pk[i];
          pdst += 1024;
        }
        wg_wait<1>(); ring.release(sl0, elect);
        wg_wait<0>(); reg_fence(acc); ring.release(sl1, elect);
#pragma unroll
        for (int i = 0; i < 8; i++) {
          const int b = (i >> 1) * 8 + (i & 1) * 2;
          pk[i] = make_uint2(pack(acc[b], acc[b + 1]), pack(acc[b + 4], acc[b + 5]));
        }
      }
#pragma unroll
      for (int i = 0; i < 8; i++) *reinterpret_cast<uint2*>(pdst + (i & 1) * (8 * 7168) + (i >> 1) * 256) = pk[i];
      STAMP(9 + layer * 12);
    }
    {
      uint32_t bx[14];
#pragma unroll
      for (int j = 0; j < 14; j++) bx[j] = __ldg(reinterpret_cast<const uint32_t*>(b2 + w * 112 + j * 8 + 2 * t));
      __syncwarp();
      if (lane == 0) { flag_arrive(fl + (3 + w) * 32); flag_wait(fl + (3 + (r >> 1)) * 32, epoch * 8); }
      __syncwarp();
      STAMP(10 + layer * 12);
      const unsigned char* psrc = gP + (size_t)(((G * 2 + c) * 8 + r) * 8) * 7168 + w * 1792 + lane * 8;
      unsigned char* img = gImg + (size_t)(64 + G * 2 + c) * ABYTES;
      uint2 pv[8][7];
#pragma unroll
      for (int s = 0; s < 8; s++)
#pragma unroll
        for (int i = 0; i < 7; i++) pv[s][i] = ldcg2(psrc + s * 7168 + i * 256);
      const uint32_t off = w * 14336 + r * 128 + lane * 4;
      unsigned char* dst = layer ? reinterpret_cast<unsigned char*>(out + (size_t)(row0 + r * 8 + g) * DM + w * 112 + 2 * t) : img + off;
      float sm = 0.f, q = 0.f;
#pragma unroll
      for (int j = 0; j < 14; j++) {
        float y0 = lo(bx[j]), y1 = hi(bx[j]);
        const uint32_t xo = lds32(abuf + off + j * 1024);
        y0 += lo(xo); y1 += hi(xo);
#pragma unroll
        for (int s = 0; s < 8; s++) { const uint32_t u = (j & 1) ? pv[s][j >> 1].y : pv[s][j >> 1].x; y0 += lo(u); y1 += hi(u); }
        bx[j] = pack(y0, y1);
        *reinterpret_cast<uint32_t*>(dst + j * (layer ? 16 : 1024)) = bx[j];
        sm += lo(bx[j]) + hi(bx[j]);
      }
      if (layer) break;
      sm += __shfl_xor_sync(~0u, sm, 1); sm += __shfl_xor_sync(~0u, sm, 2);
      sm *= 1.f / 112.f;
#pragma unroll
      for (int j = 0; j < 14; j++) { const float a = lo(bx[j]) - sm, b = hi(bx[j]) - sm; q = fmaf(a, a, q); q = fmaf(b, b, q); }
      q += __shfl_xor_sync(~0u, q, 1); q += __shfl_xor_sync(~0u, q, 2);
      if (t < 2) gStat[(size_t)(2048 + row0 + r * 8 + g) * 8 + 2 * w + t] = make_float2(sm, q * 0.5f);
      STAMP(11);
      gather(fl + 64, img);
      STAMP(12);
    }
  }
  STAMP(30);
  if (tid == 0) asm volatile("red.relaxed.gpu.global.add.u32 [%0], 1;" ::"l"(gFlag + FL_DONE * 32) : "memory");
  }
}

typedef CUresult (*EncFn)(CUtensorMap*, CUtensorMapDataType, cuuint32_t, void*, const cuuint64_t*, const cuuint64_t*,
                          const cuuint32_t*, const cuuint32_t*, CUtensorMapInterleave, CUtensorMapSwizzle,
                          CUtensorMapL2promotion, CUtensorMapFloatOOBfill);

void make_map(EncFn enc, CUtensorMap* m, void* p, int rank, uint64_t d0, uint64_t d1, uint64_t d2, uint64_t s1, uint64_t s2,
              uint32_t b0, uint32_t b1, uint32_t b2, CUtensorMapSwizzle sw) {
  cuuint64_t dims[3] = {d0, d1, d2}, strides[2] = {s1, s2};
  cuuint32_t box[3] = {b0, b1, b2}, es[3] = {1, 1, 1};
  enc(m, CU_TENSOR_MAP_DATA_TYPE_BFLOAT16, rank, p, dims, strides, box, es, CU_TENSOR_MAP_INTERLEAVE_NONE, sw,
      CU_TENSOR_MAP_L2_PROMOTION_L2_128B, CU_TENSOR_MAP_FLOAT_OOB_FILL_NONE);
}

}

extern "C" void kernel_launch(void* const* d_in, const int* in_sizes, int n_in, void* d_out, int out_size) {
  static EncFn enc = nullptr;
  if (!enc) {
    cudaDriverEntryPointQueryResult st;
    void* fn = nullptr;
    cudaGetDriverEntryPoint("cuTensorMapEncodeTiled", &fn, cudaEnableDefault, &st);
    enc = (EncFn)fn;
    cudaFuncSetAttribute(fused_kernel, cudaFuncAttributeMaxDynamicSharedMemorySize, SMEM_BYTES);
  }
  CUtensorMap mQKV, mWO, mW1, mW2, mX;
  make_map(enc, &mX, d_in[0], 2, 448, 2048, 1, 896, 0, 64, 64, 1, CU_TENSOR_MAP_SWIZZLE_128B);
  make_map(enc, &mQKV, d_in[1], 3, 448, 448, 3, 2688, 896, 64, 32, 3, CU_TENSOR_MAP_SWIZZLE_128B);
  make_map(enc, &mWO, d_in[3], 2, 448, 448, 1, 896, 0, 64, 112, 1, CU_TENSOR_MAP_SWIZZLE_128B);
  make_map(enc, &mW1, d_in[5], 3, 32, 448, 56, 3584, 64, 32, 32, 7, CU_TENSOR_MAP_SWIZZLE_64B);
  make_map(enc, &mW2, d_in[7], 2, 448, 1792, 1, 896, 0, 64, 112, 1, CU_TENSOR_MAP_SWIZZLE_128B);
  fused_kernel<<<NCTA, 384, SMEM_BYTES, cudaStreamPerThread>>>(
      mQKV, mWO, mW1, mW2, mX, (const __nv_bfloat16*)d_in[2], (const __nv_bfloat16*)d_in[6],
      (const __nv_bfloat16*)d_in[8], (const __nv_bfloat16*)d_in[1], (const __nv_bfloat16*)d_in[3], (const __nv_bfloat16*)d_in[5],
      (const __nv_bfloat16*)d_in[7], (__nv_bfloat16*)d_out);
}
```

```cpp
#include <cuda_runtime.h>
#include <cuda_bf16.h>
#include <cuda.h>
#include <stdint.h>

namespace {

constexpr int DM = 448, NCTA = 128;
constexpr int ABYTES = 57344;
constexpr int SLOT = 14336, NSLOT = 7;
constexpr int OFF_RING = 2 * ABYTES;
constexpr int OFF_WPHI = OFF_RING + NSLOT * SLOT;
constexpr int OFF_B1 = OFF_WPHI + 8192;
constexpr int OFF_CS = OFF_B1 + 896;
constexpr int OFF_BAR = OFF_CS + 1664;
constexpr int SMEM_BYTES = OFF_BAR + 272 + 1024;
constexpr int TILES_PER_LAYER = 46;

__device__ __align__(1024) unsigned char gP[16 * 2 * 8 * 8 * 7168];
__device__ __align__(1024) unsigned char gImg[3 * 32 * ABYTES];
__device__ __align__(1024) float2 gStat[2 * 2048 * 8];
__device__ __align__(1024) float4 gKV[2 * 8 * 2 * 5 * 128];
__device__ __align__(1024) float4 gCS[8 * 16 * 104];
__device__ __align__(128) unsigned gFlag[(2 * 32 * 7 + 32 + 1 + 16) * 32];
#define STAMP(i)

__device__ __forceinline__ uint32_t smem_u32(const void* p) { return (uint32_t)__cvta_generic_to_shared(p); }
__device__ __forceinline__ void mbar_init(uint32_t b, int c) { asm volatile("mbarrier.init.shared::cta.b64 [%0], %1;" ::"r"(b), "r"(c)); }
__device__ __forceinline__ void mbar_expect(uint32_t b, int bytes) { asm volatile("mbarrier.arrive.expect_tx.shared::cta.b64 _, [%0], %1;" ::"r"(b), "r"(bytes) : "memory"); }
__device__ __forceinline__ void mbar_arrive(uint32_t b) { asm volatile("mbarrier.arrive.shared::cta.b64 _, [%0];" ::"r"(b) : "memory"); }
__device__ __forceinline__ void mbar_wait(uint32_t b, int par) {
  uint32_t ok; int n = 0;
#pragma unroll 1
  while (true) {
    asm volatile("{.reg .pred p; mbarrier.try_wait.parity.shared::cta.b64 p, [%1], %2; selp.u32 %0,1,0,p;}" : "=r"(ok) : "r"(b), "r"(par) : "memory");
    if (ok) break;
    if (++n > (1 << 22)) break;
  }
}
__device__ __forceinline__ void flag_wait(const unsigned* f, unsigned target) {
  unsigned v; int n = 0;
#pragma unroll 1
  while (true) {
    asm volatile("ld.acquire.gpu.global.u32 %0, [%1];" : "=r"(v) : "l"(f) : "memory");
    if ((int)(v - target) >= 0) break;
    if (++n > (1 << 21)) break;
  }
}
__device__ __forceinline__ void flag_arrive(unsigned* f) { asm volatile("red.release.gpu.global.add.u32 [%0], 1;" ::"l"(f) : "memory"); }
__device__ __forceinline__ bool elect_one() {
  uint32_t p; asm volatile("{.reg .pred P; elect.sync _|P, 0xffffffff; selp.u32 %0, 1, 0, P;}" : "=r"(p)); return p;
}
__device__ __forceinline__ void fence_async() { asm volatile("fence.proxy.async.global;" ::: "memory"); }
__device__ __forceinline__ void fence_async_smem() { asm volatile("fence.proxy.async.shared::cta;" ::: "memory"); }
template <int ID, int N> __device__ __forceinline__ void bar_sync() { asm volatile("bar.sync %0, %1;" ::"n"(ID), "n"(N) : "memory"); }
__device__ __forceinline__ void bar_wg(int c) { if (c) bar_sync<2, 128>(); else bar_sync<1, 128>(); }
__device__ __forceinline__ void wg_fence() { asm volatile("wgmma.fence.sync.aligned;" ::: "memory"); }
__device__ __forceinline__ void wg_commit() { asm volatile("wgmma.commit_group.sync.aligned;" ::: "memory"); }
template <int N> __device__ __forceinline__ void wg_wait() { asm volatile("wgmma.wait_group.sync.aligned %0;" ::"n"(N) : "memory"); }
template <int N> __device__ __forceinline__ void reg_fence(float (&d)[N]) {
#pragma unroll
  for (int i = 0; i < N; i++) asm volatile("" : "+f"(d[i])::"memory");
}
template <int N> __device__ __forceinline__ void reg_def(float (&d)[N]) {
#pragma unroll
  for (int i = 0; i < N; i++) d[i] = 0.f;
}
__device__ __forceinline__ uint64_t mkdesc(uint32_t addr, uint32_t lbo, uint32_t sbo, uint64_t swz) {
  return (uint64_t)((addr & 0x3FFFF) >> 4) | ((uint64_t)(lbo >> 4) << 16) | ((uint64_t)(sbo >> 4) << 32) | (swz << 62);
}
__device__ __forceinline__ uint32_t pack(float a, float b) {
  uint32_t r; asm("cvt.rn.bf16x2.f32 %0, %1, %2;" : "=r"(r) : "f"(b), "f"(a)); return r;
}
__device__ __forceinline__ uint32_t relu_sq(float a, float b) {
  uint32_t r; asm("{.reg .b32 v; cvt.rn.relu.bf16x2.f32 v, %1, %2; mul.rn.bf16x2 %0, v, v;}" : "=r"(r) : "f"(b), "f"(a)); return r;
}
__device__ __forceinline__ float lo(uint32_t u) { return __uint_as_float(u << 16); }
__device__ __forceinline__ float hi(uint32_t u) { return __uint_as_float(u & 0xFFFF0000u); }
__device__ __forceinline__ float ex2(float x) { float y; asm("ex2.approx.ftz.f32 %0, %1;" : "=f"(y) : "f"(x)); return y; }
__device__ __forceinline__ void stsm4(uint32_t a, uint32_t r0, uint32_t r1, uint32_t r2, uint32_t r3) {
  asm volatile("stmatrix.sync.aligned.m8n8.x4.shared.b16 [%0], {%1,%2,%3,%4};" ::"r"(a), "r"(r0), "r"(r1), "r"(r2), "r"(r3) : "memory");
}
__device__ __forceinline__ void tma3(uint32_t dst, const CUtensorMap* m, int c0, int c1, int c2, uint32_t bar) {
  asm volatile("cp.async.bulk.tensor.3d.shared::cluster.global.mbarrier::complete_tx::bytes [%0], [%1, {%3,%4,%5}], [%2];"
               ::"r"(dst), "l"(m), "r"(bar), "r"(c0), "r"(c1), "r"(c2) : "memory");
}
__device__ __forceinline__ void tma2(uint32_t dst, const CUtensorMap* m, int c0, int c1, uint32_t bar) {
  asm volatile("cp.async.bulk.tensor.2d.shared::cluster.global.mbarrier::complete_tx::bytes [%0], [%1, {%3,%4}], [%2];"
               ::"r"(dst), "l"(m), "r"(bar), "r"(c0), "r"(c1) : "memory");
}
__device__ __forceinline__ uint32_t lds32(uint32_t a) { uint32_t v; asm volatile("ld.shared.u32 %0, [%1];" : "=r"(v) : "r"(a) : "memory"); return v; }
__device__ __forceinline__ void bulk_ld(uint32_t dst, const void* src, int bytes, uint32_t bar) {
  asm volatile("cp.async.bulk.shared::cluster.global.mbarrier::complete_tx::bytes [%0], [%1], %2, [%3];" ::"r"(dst), "l"(src), "r"(bytes), "r"(bar) : "memory");
}
__device__ __forceinline__ uint4 ldcg4(const void* p) {
  uint4 v; asm volatile("ld.global.cg.v4.u32 {%0,%1,%2,%3}, [%4];" : "=r"(v.x), "=r"(v.y), "=r"(v.z), "=r"(v.w) : "l"(p) : "memory"); return v;
}

__device__ __forceinline__ uint2 ldcg2(const void* p) {
  uint2 v; asm volatile("ld.global.cg.v2.u32 {%0,%1}, [%2];" : "=r"(v.x), "=r"(v.y) : "l"(p) : "memory"); return v;
}

__device__ __forceinline__ void mma_ss_184(float (&d)[92], uint64_t da, uint64_t db, int acc) {
  asm volatile("{.reg .pred p; setp.ne.b32 p, %94, 0;\n"
    "wgmma.mma_async.sync.aligned.m64n184k16.f32.bf16.bf16 {%0,%1,%2,%3,%4,%5,%6,%7,%8,%9,%10,%11,%12,%13,%14,%15,%16,%17,%18,%19,%20,%21,%22,%23,%24,%25,%26,%27,%28,%29,%30,%31,%32,%33,%34,%35,%36,%37,%38,%39,%40,%41,%42,%43,%44,%45,%46,%47,%48,%49,%50,%51,%52,%53,%54,%55,%56,%57,%58,%59,%60,%61,%62,%63,%64,%65,%66,%67,%68,%69,%70,%71,%72,%73,%74,%75,%76,%77,%78,%79,%80,%81,%82,%83,%84,%85,%86,%87,%88,%89,%90,%91}, %92, %93, p, 1, 1, 0, 1;}\n"
    : "+f"(d[0]),"+f"(d[1]),"+f"(d[2]),"+f"(d[3]),"+f"(d[4]),"+f"(d[5]),"+f"(d[6]),"+f"(d[7]),"+f"(d[8]),"+f"(d[9]),"+f"(d[10]),"+f"(d[11]),"+f"(d[12]),"+f"(d[13]),"+f"(d[14]),"+f"(d[15]),"+f"(d[16]),"+f"(d[17]),"+f"(d[18]),"+f"(d[19]),"+f"(d[20]),"+f"(d[21]),"+f"(d[22]),"+f"(d[23]),"+f"(d[24]),"+f"(d[25]),"+f"(d[26]),"+f"(d[27]),"+f"(d[28]),"+f"(d[29]),"+f"(d[30]),"+f"(d[31]),"+f"(d[32]),"+f"(d[33]),"+f"(d[34]),"+f"(d[35]),"+f"(d[36]),"+f"(d[37]),"+f"(d[38]),"+f"(d[39]),"+f"(d[40]),"+f"(d[41]),"+f"(d[42]),"+f"(d[43]),"+f"(d[44]),"+f"(d[45]),"+f"(d[46]),"+f"(d[47]),"+f"(d[48]),"+f"(d[49]),"+f"(d[50]),"+f"(d[51]),"+f"(d[52]),"+f"(d[53]),"+f"(d[54]),"+f"(d[55]),"+f"(d[56]),"+f"(d[57]),"+f"(d[58]),"+f"(d[59]),"+f"(d[60]),"+f"(d[61]),"+f"(d[62]),"+f"(d[63]),"+f"(d[64]),"+f"(d[65]),"+f"(d[66]),"+f"(d[67]),"+f"(d[68]),"+f"(d[69]),"+f"(d[70]),"+f"(d[71]),"+f"(d[72]),"+f"(d[73]),"+f"(d[74]),"+f"(d[75]),"+f"(d[76]),"+f"(d[77]),"+f"(d[78]),"+f"(d[79]),"+f"(d[80]),"+f"(d[81]),"+f"(d[82]),"+f"(d[83]),"+f"(d[84]),"+f"(d[85]),"+f"(d[86]),"+f"(d[87]),"+f"(d[88]),"+f"(d[89]),"+f"(d[90]),"+f"(d[91])
    : "l"(da), "l"(db), "r"(acc));
}
__device__ __forceinline__ void mma_ss_224(float (&d)[112], uint64_t da, uint64_t db, int acc) {
  asm volatile("{.reg .pred p; setp.ne.b32 p, %114, 0;\n"
    "wgmma.mma_async.sync.aligned.m64n224k16.f32.bf16.bf16 {%0,%1,%2,%3,%4,%5,%6,%7,%8,%9,%10,%11,%12,%13,%14,%15,%16,%17,%18,%19,%20,%21,%22,%23,%24,%25,%26,%27,%28,%29,%30,%31,%32,%33,%34,%35,%36,%37,%38,%39,%40,%41,%42,%43,%44,%45,%46,%47,%48,%49,%50,%51,%52,%53,%54,%55,%56,%57,%58,%59,%60,%61,%62,%63,%64,%65,%66,%67,%68,%69,%70,%71,%72,%73,%74,%75,%76,%77,%78,%79,%80,%81,%82,%83,%84,%85,%86,%87,%88,%89,%90,%91,%92,%93,%94,%95,%96,%97,%98,%99,%100,%101,%102,%103,%104,%105,%106,%107,%108,%109,%110,%111}, %112, %113, p, 1, 1, 0, 1;}\n"
    : "+f"(d[0]),"+f"(d[1]),"+f"(d[2]),"+f"(d[3]),"+f"(d[4]),"+f"(d[5]),"+f"(d[6]),"+f"(d[7]),"+f"(d[8]),"+f"(d[9]),"+f"(d[10]),"+f"(d[11]),"+f"(d[12]),"+f"(d[13]),"+f"(d[14]),"+f"(d[15]),"+f"(d[16]),"+f"(d[17]),"+f"(d[18]),"+f"(d[19]),"+f"(d[20]),"+f"(d[21]),"+f"(d[22]),"+f"(d[23]),"+f"(d[24]),"+f"(d[25]),"+f"(d[26]),"+f"(d[27]),"+f"(d[28]),"+f"(d[29]),"+f"(d[30]),"+f"(d[31]),"+f"(d[32]),"+f"(d[33]),"+f"(d[34]),"+f"(d[35]),"+f"(d[36]),"+f"(d[37]),"+f"(d[38]),"+f"(d[39]),"+f"(d[40]),"+f"(d[41]),"+f"(d[42]),"+f"(d[43]),"+f"(d[44]),"+f"(d[45]),"+f"(d[46]),"+f"(d[47]),"+f"(d[48]),"+f"(d[49]),"+f"(d[50]),"+f"(d[51]),"+f"(d[52]),"+f"(d[53]),"+f"(d[54]),"+f"(d[55]),"+f"(d[56]),"+f"(d[57]),"+f"(d[58]),"+f"(d[59]),"+f"(d[60]),"+f"(d[61]),"+f"(d[62]),"+f"(d[63]),"+f"(d[64]),"+f"(d[65]),"+f"(d[66]),"+f"(d[67]),"+f"(d[68]),"+f"(d[69]),"+f"(d[70]),"+f"(d[71]),"+f"(d[72]),"+f"(d[73]),"+f"(d[74]),"+f"(d[75]),"+f"(d[76]),"+f"(d[77]),"+f"(d[78]),"+f"(d[79]),"+f"(d[80]),"+f"(d[81]),"+f"(d[82]),"+f"(d[83]),"+f"(d[84]),"+f"(d[85]),"+f"(d[86]),"+f"(d[87]),"+f"(d[88]),"+f"(d[89]),"+f"(d[90]),"+f"(d[91]),"+f"(d[92]),"+f"(d[93]),"+f"(d[94]),"+f"(d[95]),"+f"(d[96]),"+f"(d[97]),"+f"(d[98]),"+f"(d[99]),"+f"(d[100]),"+f"(d[101]),"+f"(d[102]),"+f"(d[103]),"+f"(d[104]),"+f"(d[105]),"+f"(d[106]),"+f"(d[107]),"+f"(d[108]),"+f"(d[109]),"+f"(d[110]),"+f"(d[111])
    : "l"(da), "l"(db), "r"(acc));
}
__device__ __forceinline__ void mma_ss_56(float (&d)[28], uint64_t da, uint64_t db, int acc) {
  asm volatile("{.reg .pred p; setp.ne.b32 p, %30, 0;\n"
    "wgmma.mma_async.sync.aligned.m64n56k16.f32.bf16.bf16 {%0,%1,%2,%3,%4,%5,%6,%7,%8,%9,%10,%11,%12,%13,%14,%15,%16,%17,%18,%19,%20,%21,%22,%23,%24,%25,%26,%27}, %28, %29, p, 1, 1, 0, 1;}\n"
    : "+f"(d[0]),"+f"(d[1]),"+f"(d[2]),"+f"(d[3]),"+f"(d[4]),"+f"(d[5]),"+f"(d[6]),"+f"(d[7]),"+f"(d[8]),"+f"(d[9]),"+f"(d[10]),"+f"(d[11]),"+f"(d[12]),"+f"(d[13]),"+f"(d[14]),"+f"(d[15]),"+f"(d[16]),"+f"(d[17]),"+f"(d[18]),"+f"(d[19]),"+f"(d[20]),"+f"(d[21]),"+f"(d[22]),"+f"(d[23]),"+f"(d[24]),"+f"(d[25]),"+f"(d[26]),"+f"(d[27])
    : "l"(da), "l"(db), "r"(acc));
}
__device__ __forceinline__ void mma_rs_56(float (&d)[28], uint32_t a0, uint32_t a1, uint32_t a2, uint32_t a3, uint64_t db, int acc) {
  asm volatile("{.reg .pred p; setp.ne.b32 p, %33, 0;\n"
    "wgmma.mma_async.sync.aligned.m64n56k16.f32.bf16.bf16 {%0,%1,%2,%3,%4,%5,%6,%7,%8,%9,%10,%11,%12,%13,%14,%15,%16,%17,%18,%19,%20,%21,%22,%23,%24,%25,%26,%27}, {%28,%29,%30,%31}, %32, p, 1, 1, 1;}\n"
    : "+f"(d[0]),"+f"(d[1]),"+f"(d[2]),"+f"(d[3]),"+f"(d[4]),"+f"(d[5]),"+f"(d[6]),"+f"(d[7]),"+f"(d[8]),"+f"(d[9]),"+f"(d[10]),"+f"(d[11]),"+f"(d[12]),"+f"(d[13]),"+f"(d[14]),"+f"(d[15]),"+f"(d[16]),"+f"(d[17]),"+f"(d[18]),"+f"(d[19]),"+f"(d[20]),"+f"(d[21]),"+f"(d[22]),"+f"(d[23]),"+f"(d[24]),"+f"(d[25]),"+f"(d[26]),"+f"(d[27])
    : "r"(a0), "r"(a1), "r"(a2), "r"(a3), "l"(db), "r"(acc));
}
__device__ __forceinline__ void mma_ss_64t(float (&d)[32], uint64_t da, uint64_t db, int acc) {
  asm volatile("{.reg .pred p; setp.ne.b32 p, %34, 0;\n"
    "wgmma.mma_async.sync.aligned.m64n64k16.f32.bf16.bf16 {%0,%1,%2,%3,%4,%5,%6,%7,%8,%9,%10,%11,%12,%13,%14,%15,%16,%17,%18,%19,%20,%21,%22,%23,%24,%25,%26,%27,%28,%29,%30,%31}, %32, %33, p, 1, 1, 1, 1;}\n"
    : "+f"(d[0]),"+f"(d[1]),"+f"(d[2]),"+f"(d[3]),"+f"(d[4]),"+f"(d[5]),"+f"(d[6]),"+f"(d[7]),"+f"(d[8]),"+f"(d[9]),"+f"(d[10]),"+f"(d[11]),"+f"(d[12]),"+f"(d[13]),"+f"(d[14]),"+f"(d[15]),"+f"(d[16]),"+f"(d[17]),"+f"(d[18]),"+f"(d[19]),"+f"(d[20]),"+f"(d[21]),"+f"(d[22]),"+f"(d[23]),"+f"(d[24]),"+f"(d[25]),"+f"(d[26]),"+f"(d[27]),"+f"(d[28]),"+f"(d[29]),"+f"(d[30]),"+f"(d[31])
    : "l"(da), "l"(db), "r"(acc));
}
__device__ __forceinline__ void mma_rs_64(float (&d)[32], uint32_t a0, uint32_t a1, uint32_t a2, uint32_t a3, uint64_t db, int acc) {
  asm volatile("{.reg .pred p; setp.ne.b32 p, %37, 0;\n"
    "wgmma.mma_async.sync.aligned.m64n64k16.f32.bf16.bf16 {%0,%1,%2,%3,%4,%5,%6,%7,%8,%9,%10,%11,%12,%13,%14,%15,%16,%17,%18,%19,%20,%21,%22,%23,%24,%25,%26,%27,%28,%29,%30,%31}, {%32,%33,%34,%35}, %36, p, 1, 1, 1;}\n"
    : "+f"(d[0]),"+f"(d[1]),"+f"(d[2]),"+f"(d[3]),"+f"(d[4]),"+f"(d[5]),"+f"(d[6]),"+f"(d[7]),"+f"(d[8]),"+f"(d[9]),"+f"(d[10]),"+f"(d[11]),"+f"(d[12]),"+f"(d[13]),"+f"(d[14]),"+f"(d[15]),"+f"(d[16]),"+f"(d[17]),"+f"(d[18]),"+f"(d[19]),"+f"(d[20]),"+f"(d[21]),"+f"(d[22]),"+f"(d[23]),"+f"(d[24]),"+f"(d[25]),"+f"(d[26]),"+f"(d[27]),"+f"(d[28]),"+f"(d[29]),"+f"(d[30]),"+f"(d[31])
    : "r"(a0), "r"(a1), "r"(a2), "r"(a3), "l"(db), "r"(acc));
}

__device__ __forceinline__ void dual_softmax(const float (&p)[28], uint32_t (&phi)[4][7]) {
  constexpr float L2E = 1.4426950408889634f;
#pragma unroll
  for (int i = 0; i < 4; i++) {
    float mx = p[i], mn = p[i];
#pragma unroll
    for (int j = 1; j < 7; j++) { mx = fmaxf(mx, p[4 * j + i]); mn = fminf(mn, p[4 * j + i]); }
    mx = fmaxf(mx, __shfl_xor_sync(~0u, mx, 1)); mn = fminf(mn, __shfl_xor_sync(~0u, mn, 1));
    mx = fmaxf(mx, __shfl_xor_sync(~0u, mx, 2)); mn = fminf(mn, __shfl_xor_sync(~0u, mn, 2));
    float a[7], b[7], sa = 0.f, sb = 0.f;
    const float mxl = mx * L2E, mnl = mn * L2E;
#pragma unroll
    for (int j = 0; j < 7; j++) {
      a[j] = ex2(fmaf(p[4 * j + i], L2E, -mxl)); b[j] = ex2(fmaf(p[4 * j + i], -L2E, mnl));
      sa += a[j]; sb += b[j];
    }
    sa += __shfl_xor_sync(~0u, sa, 1); sb += __shfl_xor_sync(~0u, sb, 1);
    sa += __shfl_xor_sync(~0u, sa, 2); sb += __shfl_xor_sync(~0u, sb, 2);
    const float ra = __fdividef(1.f, sa), rb = __fdividef(1.f, sb);
#pragma unroll
    for (int j = 0; j < 7; j++) phi[i][j] = pack(a[j] * ra, b[j] * rb);
  }
}

struct Ring {
  uint32_t full, empty, base; int slot, par;
  __device__ __forceinline__ uint32_t acquire() { mbar_wait(full + slot * 8, par); return base + slot * SLOT; }
  __device__ __forceinline__ int advance() { int s = slot; if (++slot == NSLOT) { slot = 0; par ^= 1; } return s; }
  __device__ __forceinline__ void release(int s, bool elect) { if (elect) mbar_arrive(empty + s * 8); }
};
constexpr int UNR = 14;
constexpr int FL_KV = 448, FL_CS = FL_KV + 16, FL_DONE = FL_KV + 32;

__global__ void __launch_bounds__(384, 1)
fused_kernel(const __grid_constant__ CUtensorMap mQKV, const __grid_constant__ CUtensorMap mWO,
             const __grid_constant__ CUtensorMap mW1, const __grid_constant__ CUtensorMap mW2,
             const __grid_constant__ CUtensorMap mX, const __nv_bfloat16* __restrict__ wphi,
             const __nv_bfloat16* __restrict__ b1, const __nv_bfloat16* __restrict__ b2,
             const __nv_bfloat16* __restrict__ wqkv, const __nv_bfloat16* __restrict__ wo, const __nv_bfloat16* __restrict__ w1,
             const __nv_bfloat16* __restrict__ w2, __nv_bfloat16* __restrict__ out) {
  extern __shared__ unsigned char smem_raw[];
  const uint32_t sb = (smem_u32(smem_raw) + 1023) & ~1023u;
  unsigned char* sg = smem_raw + (sb - smem_u32(smem_raw));
  const int tid = threadIdx.x, lane = tid & 31;
  const int G = blockIdx.x >> 3, r = blockIdx.x & 7;
  const uint32_t barFull = sb + OFF_BAR, barEmpty = barFull + 56, barA = barEmpty + 56, barCS = barA + 112, barX = barCS + 16;
  const int warp = __shfl_sync(~0u, tid >> 5, 0);
  uint32_t wv[7], bv;
#pragma unroll
  for (int i = 0; i < 7; i++)
    wv[i] = __ldg(reinterpret_cast<const unsigned short*>(wphi) + (56 * r + i * 8 + (warp & 7)) * 28 + min(lane, 27));
  bv = __ldg(reinterpret_cast<const unsigned short*>(b1) + 224 * r + min(tid, 223));
  if (lane == 0) {
    if (warp >= 10) {
      const int cc = warp - 10;
      mbar_init(barX + cc * 8, 1);
      fence_async_smem();
      mbar_expect(barX + cc * 8, ABYTES);
#pragma unroll 1
      for (int k = 0; k < 7; k++) tma2(sb + cc * ABYTES + k * 8192, &mX, 64 * k, G * 128 + 64 * cc, barX + cc * 8);
    } else if (warp < 7) { mbar_init(barFull + warp * 8, 1); mbar_init(barEmpty + warp * 8, 2); mbar_init(barA + warp * 8, 1); mbar_init(barA + 56 + warp * 8, 1); }
    else if (warp < 9) mbar_init(barCS + (warp - 7) * 8, 96);
    else
      asm volatile("cp.async.bulk.prefetch.L2.global [%0], %1;" ::"l"((const char*)wqkv + blockIdx.x * 9408), "r"(9408) : "memory");
    asm volatile("fence.mbarrier_init.release.cluster;" ::: "memory");
  }
  if (tid < 192) reinterpret_cast<float*>(sg + OFF_CS)[tid] = 0.f;
  __syncthreads();
  const int wgid = warp >> 2;
  if (wgid == 2) {
    asm volatile("setmaxnreg.dec.sync.aligned.u32 40;");
    if (warp == 8) {
      int slot = 0, par = 1;
#pragma unroll 1
      for (int it = 0; it < 2 * TILES_PER_LAYER; it++) {
        const int i = it >= TILES_PER_LAYER ? it - TILES_PER_LAYER : it;
        mbar_wait(barEmpty + slot * 8, par);
        const uint32_t dst = sb + OFF_RING + slot * SLOT, fb = barFull + slot * 8;
        if (elect_one()) {
          mbar_expect(fb, i < 14 ? 12288 : SLOT);
          if (i < 14) tma3(dst, &mQKV, 56 * r, 32 * i, 0, fb);
          else if (i < 18) tma2(dst, &mWO, 56 * r, 112 * (i - 14), fb);
          else if (i < 32) tma3(dst, &mW1, 0, 32 * (i - 18), 7 * r, fb);
          else tma2(dst, &mW2, 64 * ((i - 32) >> 1), 224 * r + 112 * (i & 1), fb);
        }
        if (++slot == NSLOT) { slot = 0; par ^= 1; }
      }
    } else {
      unsigned ep;
      asm volatile("ld.relaxed.gpu.global.u32 %0, [%1];" : "=r"(ep) : "l"(gFlag + FL_DONE * 32) : "memory");
      const int idx = tid - 288;
      ep = (ep / NCTA + 1) * 3;
      if (G == 0) {
#pragma unroll 1
        for (int i = idx; i < 2 * 1280; i += 96) gKV[((i >= 1280) * 7 + r) * 1280 + i] = make_float4(0.f, 0.f, 0.f, 0.f);
        __syncwarp();
        if (lane == 0) flag_arrive(gFlag + (FL_CS + r) * 32);
      }
      mbar_wait(barFull + 48, 0); mbar_wait(barFull + 48, 1);
      if (idx < 2) {
        const char* pf = idx ? (const char*)w2 + blockIdx.x * 12544 : (const char*)wo + blockIdx.x * 3136;
        asm volatile("cp.async.bulk.prefetch.L2.global [%0], %1;" ::"l"(pf), "r"(idx ? 12544 : 3136) : "memory");
      }
      if (lane == 0) flag_wait(gFlag + (FL_CS + r) * 32, ep);
      __syncwarp();
      mbar_arrive(barCS);
#pragma unroll 1
      for (int ps = 0; ps < 3; ps++) {
        const int nch = ps ? 14 : 21, ch = min(idx >> 2, nch - 1), p = ch / 7, k0 = G * 28 + (idx & 3) * 7;
        const uint4* src = ps ? reinterpret_cast<const uint4*>(w1 + (size_t)k0 * 1792 + 224 * r) + (ps - 1) * 14 + ch
                              : reinterpret_cast<const uint4*>(wqkv + (size_t)k0 * 1344 + p * 448 + 56 * r) + (ch - 7 * p);
        uint4 cu[7];
#pragma unroll
        for (int i = 0; i < 7; i++) cu[i] = __ldg(src + i * (ps ? 224 : 168));
        float s[8] = {};
#pragma unroll
        for (int i = 0; i < 7; i++) { s[0] += lo(cu[i].x); s[1] += hi(cu[i].x); s[2] += lo(cu[i].y); s[3] += hi(cu[i].y); s[4] += lo(cu[i].z); s[5] += hi(cu[i].z); s[6] += lo(cu[i].w); s[7] += hi(cu[i].w); }
#pragma unroll
        for (int i = 0; i < 8; i++) { s[i] += __shfl_xor_sync(~0u, s[i], 1); s[i] += __shfl_xor_sync(~0u, s[i], 2); }
        if ((idx & 3) < 2 && idx < nch * 4) gCS[(r * 16 + G) * 104 + (ps ? 10 + ps * 14 + ch : ch + p) * 2 + (idx & 1)] = (idx & 1) ? make_float4(s[4], s[5], s[6], s[7]) : make_float4(s[0], s[1], s[2], s[3]);
      }
      __syncwarp();
      if (lane == 0) { flag_arrive(gFlag + (FL_CS + 8 + r) * 32); flag_wait(gFlag + (FL_CS + 8 + r) * 32, ep * 16); }
      __syncwarp();
#pragma unroll 1
      for (int j = idx; j < 208; j += 96) {
        float2 a = make_float2(0.f, 0.f);
#pragma unroll 8
        for (int i = 0; i < 16; i++) { const float2 v = __ldcg(reinterpret_cast<const float2*>(gCS + (r * 16 + i) * 104) + j); a.x += v.x; a.y += v.y; }
        reinterpret_cast<float2*>(sg + OFF_CS)[j] = a;
      }
      mbar_arrive(barCS + 8);
    }
  } else {
  asm volatile("setmaxnreg.inc.sync.aligned.u32 232;");
  const int c = wgid, w = warp & 3, g = lane >> 2, t = lane & 3;
  int elect_i = (tid & 127) == 0;
  asm volatile("" : "+r"(elect_i));
  const bool elect = elect_i;
  const uint32_t abuf = sb + c * ABYTES, barAc = barA + c * 56;
  const int row0 = G * 128 + c * 64;
  unsigned epoch;
  asm volatile("ld.relaxed.gpu.global.u32 %0, [%1];" : "=r"(epoch) : "l"(gFlag + FL_DONE * 32) : "memory");
  STAMP(24);
  float mean[2], rstd[2];
  uint4 su[2] = {};
  uint32_t xs[7][2];
  {
#pragma unroll
    for (int i = 0; i < 8; i++) {
      const int k = i * 8 + (tid >> 5);
      *reinterpret_cast<uint32_t*>(sg + OFF_WPHI + k * 128 + ((g ^ (k & 7)) << 4) + t * 4) = (i < 7 && lane < 28) ? wv[i % 7] << (k >= 28 ? 16 : 0) : 0u;
    }
    if (tid < 224) reinterpret_cast<uint32_t*>(sg + OFF_B1)[tid] = bv << 16;
    mbar_wait(barX + c * 8, 0);
    STAMP(25);
#pragma unroll
    for (int j = 0; j < 7; j++) {
      const int ci = 7 * r + j;
      const uint32_t a = abuf + (ci >> 3) * 8192 + (w * 16 + g) * 128 + (((ci & 7) ^ g) << 4) + t * 4;
      xs[j][0] = lds32(a); xs[j][1] = lds32(a + 1024);
    }
    __syncwarp();
#pragma unroll 1
    for (int hh = 0; hh < 2; hh++) {
      uint4* p = reinterpret_cast<uint4*>(sg + c * ABYTES + (w * 16 + hh * 8 + g) * 128) + t;
      uint4 v[14];
#pragma unroll
      for (int k = 0; k < 14; k++) v[k] = p[(k >> 1) * 512 + ((k ^ g) & 1) * 4];
      float a8[8] = {};
#pragma unroll
      for (int k = 0; k < 14; k++) {
        const uint32_t e[4] = {v[k].x, v[k].y, v[k].z, v[k].w};
#pragma unroll
        for (int z = 0; z < 4; z++) { a8[2 * z] += lo(e[z]); a8[2 * z + 1] += hi(e[z]); }
      }
      float sm = ((a8[0] + a8[1]) + (a8[2] + a8[3])) + ((a8[4] + a8[5]) + (a8[6] + a8[7]));
      sm += __shfl_xor_sync(~0u, sm, 1); sm += __shfl_xor_sync(~0u, sm, 2);
      sm *= 1.f / DM;
#pragma unroll
      for (int k = 0; k < 14; k++) {
        const uint32_t e[4] = {v[k].x, v[k].y, v[k].z, v[k].w};
#pragma unroll
        for (int z = 0; z < 4; z++) {
          const float a = lo(e[z]) - sm, b = hi(e[z]) - sm;
          a8[2 * z] = fmaf(a, a, k ? a8[2 * z] : 0.f); a8[2 * z + 1] = fmaf(b, b, k ? a8[2 * z + 1] : 0.f);
        }
      }
      float q = ((a8[0] + a8[1]) + (a8[2] + a8[3])) + ((a8[4] + a8[5]) + (a8[6] + a8[7]));
      q += __shfl_xor_sync(~0u, q, 1); q += __shfl_xor_sync(~0u, q, 2);
      q = rsqrtf(q * (1.f / DM) + 1e-5f);
      sm *= -q;
#pragma unroll
      for (int k = 0; k < 14; k++)
        p[(k >> 1) * 512 + ((k ^ g) & 1) * 4] = make_uint4(pack(fmaf(lo(v[k].x), q, sm), fmaf(hi(v[k].x), q, sm)), pack(fmaf(lo(v[k].y), q, sm), fmaf(hi(v[k].y), q, sm)),
                                                           pack(fmaf(lo(v[k].z), q, sm), fmaf(hi(v[k].z), q, sm)), pack(fmaf(lo(v[k].w), q, sm), fmaf(hi(v[k].w), q, sm)));
    }
    fence_async_smem();
    bar_sync<3, 256>();
    epoch = epoch / NCTA + 1;
    mean[0] = mean[1] = 0.f; rstd[0] = rstd[1] = 1.f;
  }
  STAMP(0);
  Ring ring{barFull, barEmpty, sb + OFF_RING, 0, 0};
  int apar = 1;
  const uint32_t stsm_off = (w * 16 + ((lane >> 3) & 1) * 8 + (lane & 7)) * 128;
  const uint32_t stsm_hi = lane >> 4;
  const uint64_t dA = mkdesc(abuf, 1024, 128, 0);

  auto gather = [&](unsigned* fl, const unsigned char* img) {
    __syncwarp();
    if (lane == 0) {
      flag_arrive(fl);
      STAMP(27);
      flag_wait(fl, epoch * 32);
      STAMP(28);
      fence_async();
      mbar_expect(barAc + w * 8, 8192); bulk_ld(abuf + w * 8192, img + w * 8192, 8192, barAc + w * 8);
      if (w < 3) { mbar_expect(barAc + 32 + w * 8, 8192); bulk_ld(abuf + 32768 + w * 8192, img + 32768 + w * 8192, 8192, barAc + 32 + w * 8); }
    }
    __syncwarp();
    apar ^= 1;
  };
  auto slice_off = [&](int j, int hh) -> uint32_t {
    return (7 * r + j) * 1024 + (w * 2 + hh) * 128 + lane * 4;
  };
  auto load_stats = [&](const float2* st) {
    mbar_wait(barAc, apar);
#pragma unroll
    for (int hh = 0; hh < 2; hh++) su[hh] = ldcg4(st + (size_t)(row0 + w * 16 + hh * 8 + g) * 8 + 2 * t);
  };
  auto finish_stats = [&]() {
#pragma unroll
    for (int hh = 0; hh < 2; hh++) {
      const float m0 = __uint_as_float(su[hh].x), m1 = __uint_as_float(su[hh].z);
      float m = m0 + m1;
      m += __shfl_xor_sync(~0u, m, 1); m += __shfl_xor_sync(~0u, m, 2);
      m *= 0.125f;
      float q = __uint_as_float(su[hh].y) + __uint_as_float(su[hh].w) + 56.f * ((m0 - m) * (m0 - m) + (m1 - m) * (m1 - m));
      q += __shfl_xor_sync(~0u, q, 1); q += __shfl_xor_sync(~0u, q, 2);
      mean[hh] = m; rstd[hh] = rsqrtf(q * (1.f / DM) + 1e-5f);
    }
  };

#pragma unroll 1
  for (int layer = 0; layer < 2; layer++) {
    unsigned* const fl = gFlag + (layer * 32 + G * 2 + c) * 7 * 32;
    uint32_t phiq[4][7];
    {
      float acc[92]; reg_def(acc);
      int prev = 0, prev2 = 0;
      const uint64_t dQ = layer ? dA : mkdesc(abuf, 16, 1024, 1);
      const int kstep = layer ? 128 : 2;
      if (layer) load_stats(gStat + 2048 * 8);
#pragma unroll UNR
      for (int st = 0; st < 14; st++) {
        if (!(st & 1) && layer) mbar_wait(barAc + (st >> 1) * 8, apar);
        const uint64_t da = dQ + (st >> 1) * 512 + (st & 1) * 2 * kstep, db = mkdesc(ring.acquire(), 4096, 1024, 1);
        wg_fence();
        mma_ss_184(acc, da, db, 1);
        mma_ss_184(acc, da + kstep, db + 128, 1);
        wg_commit();
        if (st > 1) { wg_wait<2>(); ring.release(prev2, elect); }
        prev2 = prev; prev = ring.advance();
      }
      if (layer) {
        finish_stats();
#pragma unroll
        for (int j = 0; j < 7; j++) { xs[j][0] = lds32(abuf + slice_off(j, 0)); xs[j][1] = lds32(abuf + slice_off(j, 1)); }
      }
      wg_wait<0>(); reg_fence(acc);
      ring.release(prev2, elect); ring.release(prev, elect);
      STAMP(1 + layer * 12);
      uint32_t f[3][14];
      {
        const float2* cs = reinterpret_cast<const float2*>(sg + OFF_CS) + t;
        const float mr0 = -mean[0] * rstd[0], mr1 = -mean[1] * rstd[1];
#pragma unroll
        for (int p = 0; p < 3; p++)
#pragma unroll
          for (int j = 0; j < 7; j++) {
            const float2 s = cs[p * 32 + j * 4];
            const int b = p * 32 + j * 4;
            f[p][2 * j] = pack(fmaf(acc[b], rstd[0], s.x * mr0), fmaf(acc[b + 1], rstd[0], s.y * mr0));
            f[p][2 * j + 1] = pack(fmaf(acc[b + 2], rstd[1], s.x * mr1), fmaf(acc[b + 3], rstd[1], s.y * mr1));
          }
      }
      float pk[28], pq[28]; reg_def(pk); reg_def(pq);
      const uint64_t dW = mkdesc(sb + OFF_WPHI, 4096, 1024, 1);
      wg_fence();
#pragma unroll
      for (int s = 0; s < 4; s++)
        mma_rs_56(pk, f[1][4 * s], f[1][4 * s + 1], s < 3 ? f[1][(4 * s + 2) % 14] : 0u, s < 3 ? f[1][(4 * s + 3) % 14] : 0u, dW + s * 128, s);
      wg_commit();
#pragma unroll
      for (int s = 0; s < 4; s++)
        mma_rs_56(pq, f[0][4 * s], f[0][4 * s + 1], s < 3 ? f[0][(4 * s + 2) % 14] : 0u, s < 3 ? f[0][(4 * s + 3) % 14] : 0u, dW + s * 128, s);
      wg_commit();
      bar_wg(c);
      const uint32_t srow = abuf + stsm_off, ones = t == 0 ? 0x3F803F80u : 0u;
#pragma unroll
      for (int jp = 0; jp < 4; jp++)
        stsm4(srow + 16384 + (((2 * jp + stsm_hi) ^ (lane & 7)) << 4), f[2][4 * jp], f[2][4 * jp + 1],
              jp < 3 ? f[2][(4 * jp + 2) % 14] : ones, jp < 3 ? f[2][(4 * jp + 3) % 14] : ones);
      wg_wait<0>(); reg_fence(pk); reg_fence(pq);
#pragma unroll 1
      for (int pass = 0; pass < 2; pass++) {
        dual_softmax(pk, phiq);
        if (pass) break;
#pragma unroll
        for (int e = 0; e < 2; e++)
#pragma unroll
          for (int jp = 0; jp < 4; jp++)
            stsm4(srow + e * 8192 + (((2 * jp + stsm_hi) ^ (lane & 7)) << 4), phiq[e][2 * jp], phiq[2 + e][2 * jp],
                  jp < 3 ? phiq[e][(2 * jp + 1) % 7] : 0u, jp < 3 ? phiq[2 + e][(2 * jp + 1) % 7] : 0u);
        fence_async_smem();
        bar_sync<3, 256>();
        float kv[32]; reg_def(kv);
        const uint64_t dP = mkdesc(sb + c * 8192, 4096, 1024, 1), dV = mkdesc(sb + 16384, 4096, 1024, 1);
        wg_fence();
#pragma unroll
        for (int s = 0; s < 8; s++) mma_ss_64t(kv, dP + (s >> 2) * (ABYTES / 16) + (s & 3) * 128, dV + (s >> 2) * (ABYTES / 16) + (s & 3) * 128, s);
        wg_commit();
        mbar_wait(barCS, 0);
        wg_wait<0>(); reg_fence(kv);
        float4* kvg = gKV + ((layer * 8 + r) * 2 + c) * 640 + (tid & 127);
#pragma unroll
        for (int i = 0; i < 5; i++) {
          float v0, v1, v2, v3;
          if (i == 4) { v0 = kv[28]; v1 = kv[29]; v2 = kv[30]; v3 = kv[31]; }
          else { v0 = c ? kv[12 + 4 * i] : kv[4 * i]; v1 = c ? kv[13 + 4 * i] : kv[1 + 4 * i]; v2 = c ? kv[14 + 4 * i] : kv[2 + 4 * i]; v3 = c ? kv[15 + 4 * i] : kv[3 + 4 * i]; }
          const bool use = i == 4 ? t == 0 : (i == 0 ? (c == 0 || t >= 2) : (i == 3 ? (c == 1 || t < 2) : true));
          if (use) asm volatile("red.relaxed.gpu.global.add.v4.f32 [%0], {%1,%2,%3,%4};" ::"l"(kvg + i * 128), "f"(v0), "f"(v1), "f"(v2), "f"(v3) : "memory");
        }
        __syncwarp();
        if (lane == 0) flag_arrive(gFlag + (FL_KV + layer * 8 + r) * 32);
        __syncwarp();
        STAMP(2 + layer * 12);
#pragma unroll
        for (int i = 0; i < 28; i++) pk[i] = pq[i];
      }
    }
    {
      if (elect) flag_wait(gFlag + (FL_KV + layer * 8 + r) * 32, epoch * 128);
      bar_wg(c);
      STAMP(3 + layer * 12);
      const float4* kvg = gKV + (layer * 8 + r) * 1280 + (tid & 127);
      uint4 kk[2][5];
#pragma unroll
      for (int e = 0; e < 2; e++)
#pragma unroll
        for (int i = 0; i < 5; i++) kk[e][i] = ldcg4(kvg + e * 640 + i * 128);
      const uint32_t srow = abuf + 24576 + stsm_off;
#pragma unroll
      for (int e = 0; e < 2; e++) {
        uint32_t f[8][2];
#pragma unroll
        for (int j = 0; j < 8; j++) { f[j][0] = 0u; f[j][1] = 0u; }
#pragma unroll
        for (int i = 0; i < 4; i++) {
          f[i + 3 * e][0] = pack(__uint_as_float(kk[e][i].x), __uint_as_float(kk[e][i].y));
          f[i + 3 * e][1] = pack(__uint_as_float(kk[e][i].z), __uint_as_float(kk[e][i].w));
        }
        f[7][0] = e ? pack(0.f, __uint_as_float(kk[e][4].y)) : pack(__uint_as_float(kk[e][4].x), 0.f);
        f[7][1] = e ? pack(0.f, __uint_as_float(kk[e][4].w)) : pack(__uint_as_float(kk[e][4].z), 0.f);
#pragma unroll
        for (int jp = 0; jp < 4; jp++)
          stsm4(srow + e * 8192 + (((2 * jp + stsm_hi) ^ (lane & 7)) << 4), f[2 * jp][0], f[2 * jp][1], f[2 * jp + 1][0], f[2 * jp + 1][1]);
      }
      fence_async_smem();
      bar_wg(c);
      float num[32]; reg_def(num);
      const uint64_t dK = mkdesc(abuf + 24576, 4096, 1024, 1);
      wg_fence();
#pragma unroll
      for (int e = 0; e < 2; e++)
#pragma unroll
        for (int s = 0; s < 4; s++)
          mma_rs_64(num, phiq[e][2 * s], phiq[2 + e][2 * s], s < 3 ? phiq[e][(2 * s + 1) % 7] : 0u, s < 3 ? phiq[2 + e][(2 * s + 1) % 7] : 0u,
                    dK + e * 512 + s * 128, e + s);
      wg_commit();
      wg_wait<0>(); reg_fence(num);
      float rd[4];
#pragma unroll
      for (int i = 0; i < 4; i++) rd[i] = __fdividef(1.f, __shfl_sync(~0u, num[28 + i], lane & ~3) + 1e-6f);
      unsigned char* img = gImg + (size_t)(G * 2 + c) * ABYTES;
#pragma unroll
      for (int j = 0; j < 7; j++) {
        const bool hb = j > 3 || (j == 3 && t >= 2);
        const float r0 = hb ? rd[1] : rd[0], r1 = hb ? rd[3] : rd[2];
        *reinterpret_cast<uint32_t*>(img + slice_off(j, 0)) = pack(num[4 * j] * r0, num[4 * j + 1] * r0);
        *reinterpret_cast<uint32_t*>(img + slice_off(j, 1)) = pack(num[4 * j + 2] * r1, num[4 * j + 3] * r1);
      }
      STAMP(4 + layer * 12);
      gather(fl, img);
      STAMP(5 + layer * 12);
    }
    {
      float acc[28]; reg_def(acc);
      int sl[4];
#pragma unroll
      for (int st = 0; st < 4; st++) {
        const uint64_t db = mkdesc(ring.acquire(), 4096, 1024, 1);
        sl[st] = ring.advance();
#pragma unroll
        for (int s = 0; s < 7; s++) {
          const int ks = st * 7 + s;
          if (!(ks & 3)) mbar_wait(barAc + (ks >> 2) * 8, apar);
          if (!(ks & 3) || !s) wg_fence();
          mma_ss_56(acc, dA + ks * 128, db + s * 128, 1);
        }
        wg_commit();
      }
      wg_wait<0>(); reg_fence(acc);
#pragma unroll
      for (int st = 0; st < 4; st++) ring.release(sl[st], elect);
      unsigned char* img = gImg + (size_t)(32 + G * 2 + c) * ABYTES;
#pragma unroll
      for (int hh = 0; hh < 2; hh++) {
        float s = 0.f, q = 0.f;
#pragma unroll
        for (int j = 0; j < 7; j++) {
          xs[j][hh] = pack(lo(xs[j][hh]) + acc[4 * j + 2 * hh], hi(xs[j][hh]) + acc[4 * j + 2 * hh + 1]);
          *reinterpret_cast<uint32_t*>(img + slice_off(j, hh)) = xs[j][hh];
          s += lo(xs[j][hh]) + hi(xs[j][hh]);
        }
        s += __shfl_xor_sync(~0u, s, 1); s += __shfl_xor_sync(~0u, s, 2);
        s *= 1.f / 56.f;
#pragma unroll
        for (int j = 0; j < 7; j++) { const float a = lo(xs[j][hh]) - s, b = hi(xs[j][hh]) - s; q = fmaf(a, a, q); q = fmaf(b, b, q); }
        q += __shfl_xor_sync(~0u, q, 1); q += __shfl_xor_sync(~0u, q, 2);
        if (t == 0) gStat[(size_t)(row0 + w * 16 + hh * 8 + g) * 8 + r] = make_float2(s, q);
      }
#pragma unroll
      for (int j = 0; j < 7; j++) xs[j][0] = xs[j][1] = 0u;
      STAMP(6 + layer * 12);
      gather(fl + 32, img);
      STAMP(7 + layer * 12);
    }
    {
      uint32_t hf[28][2];
      {
        float acc[112]; reg_def(acc);
        int prev = 0, prev2 = 0;
        load_stats(gStat);
#pragma unroll UNR
        for (int st = 0; st < 14; st++) {
          if (!(st & 1)) mbar_wait(barAc + (st >> 1) * 8, apar);
          const uint64_t da = dA + st * 256, db = mkdesc(ring.acquire(), 2048, 512, 2);
          wg_fence();
          mma_ss_224(acc, da, db, 1);
          mma_ss_224(acc, da + 128, db + 64, 1);
          wg_commit();
          if (st > 1) { wg_wait<2>(); ring.release(prev2, elect); }
          prev2 = prev; prev = ring.advance();
        }
        finish_stats();
        mbar_wait(barCS + 8, 0);
        wg_wait<0>(); reg_fence(acc);
        ring.release(prev2, elect); ring.release(prev, elect);
        STAMP(8 + layer * 12);
        const float2* bs = reinterpret_cast<const float2*>(sg + OFF_B1) + t;
        const float2* cs = reinterpret_cast<const float2*>(sg + OFF_CS + 768) + t;
        const float mr0 = -mean[0] * rstd[0], mr1 = -mean[1] * rstd[1];
#pragma unroll
        for (int j = 0; j < 28; j++) {
          const float2 b = bs[4 * j], s = cs[4 * j];
          hf[j][0] = relu_sq(fmaf(acc[4 * j], rstd[0], fmaf(s.x, mr0, b.x)), fmaf(acc[4 * j + 1], rstd[0], fmaf(s.y, mr0, b.y)));
          hf[j][1] = relu_sq(fmaf(acc[4 * j + 2], rstd[1], fmaf(s.x, mr1, b.x)), fmaf(acc[4 * j + 3], rstd[1], fmaf(s.y, mr1, b.y)));
        }
      }
      unsigned char* pdst = gP + (size_t)(((G * 2 + c) * 8 + 2 * w) * 8 + r) * 7168 + lane * 8;
      uint2 pk[8] = {};
#pragma unroll 1
      for (int ch = 0; ch < 7; ch++) {
        float acc[32]; reg_def(acc);
        int sl0 = 0, sl1 = 0;
#pragma unroll
        for (int hk = 0; hk < 2; hk++) {
          const uint64_t db = mkdesc(ring.acquire(), 4096, 1024, 1);
          wg_fence();
#pragma unroll
          for (int s = 0; s < 7; s++) { const int ks = hk * 7 + s; mma_rs_64(acc, hf[2 * ks][0], hf[2 * ks][1], hf[2 * ks + 1][0], hf[2 * ks + 1][1], db + s * 128, ks); }
          wg_commit();
          if (hk) sl1 = ring.advance(); else sl0 = ring.advance();
        }
        if (ch > 0) {
#pragma unroll
          for (int i = 0; i < 8; i++) *reinterpret_cast<uint2*>(pdst + (i & 1) * (8 * 7168) + (i >> 1) * 256) = pk[i];
          pdst += 1024;
        }
        wg_wait<1>(); ring.release(sl0, elect);
        wg_wait<0>(); reg_fence(acc); ring.release(sl1, elect);
#pragma unroll
        for (int i = 0; i < 8; i++) {
          const int b = (i >> 1) * 8 + (i & 1) * 2;
          pk[i] = make_uint2((pack(acc[b], acc[b + 1]) & ~1u) | (layer ^ 1), pack(acc[b + 4], acc[b + 5]));
        }
      }
#pragma unroll
      for (int i = 0; i < 8; i++) *reinterpret_cast<uint2*>(pdst + (i & 1) * (8 * 7168) + (i >> 1) * 256) = pk[i];
      STAMP(9 + layer * 12);
    }
    {
      uint32_t bx[14];
#pragma unroll
      for (int j = 0; j < 14; j++) bx[j] = __ldg(reinterpret_cast<const uint32_t*>(b2 + (j >> 1) * 64 + w * 16 + (j & 1) * 8 + 2 * t));
      const unsigned char* psrc = gP + (size_t)(((G * 2 + c) * 8 + r) * 8) * 7168 + w * 256 + lane * 8;
      unsigned char* img = gImg + (size_t)(64 + G * 2 + c) * ABYTES;
      uint2 pv[8][7] = {};
      uint32_t need = 0x7F;
#pragma unroll 1
      for (int n = 0; need && n < (1 << 16); n++) {
#pragma unroll
        for (int i = 0; i < 7; i++)
          if (need >> i & 1) {
#pragma unroll
            for (int s = 0; s < 8; s++) pv[s][i] = ldcg2(psrc + s * 7168 + i * 1024);
          }
        uint32_t bad = 0;
#pragma unroll
        for (int i = 0; i < 7; i++) {
          const uint32_t all = pv[0][i].x & pv[1][i].x & pv[2][i].x & pv[3][i].x & pv[4][i].x & pv[5][i].x & pv[6][i].x & pv[7][i].x;
          const uint32_t any = pv[0][i].x | pv[1][i].x | pv[2][i].x | pv[3][i].x | pv[4][i].x | pv[5][i].x | pv[6][i].x | pv[7][i].x;
          bad |= ((layer ? any : ~all) & 1u) << i;
        }
        need = __reduce_or_sync(~0u, bad);
      }
      STAMP(10 + layer * 12);
      const uint32_t off = w * 2048 + r * 128 + lane * 4;
      unsigned char* dst = layer ? reinterpret_cast<unsigned char*>(out + (size_t)(row0 + r * 8 + g) * DM + w * 16 + 2 * t) : img + off;
      float sm = 0.f, q = 0.f;
#pragma unroll
      for (int j = 0; j < 14; j++) {
        float y0 = lo(bx[j]), y1 = hi(bx[j]);
        const uint32_t xo = lds32(abuf + off + (j >> 1) * 8192 + (j & 1) * 1024);
        y0 += lo(xo); y1 += hi(xo);
#pragma unroll
        for (int s = 0; s < 8; s++) { const uint32_t u = (j & 1) ? pv[s][j >> 1].y : pv[s][j >> 1].x; y0 += lo(u); y1 += hi(u); }
        bx[j] = pack(y0, y1);
        *reinterpret_cast<uint32_t*>(dst + ((j >> 1) * 8 + (j & 1)) * (layer ? 16 : 1024)) = bx[j];
        sm += lo(bx[j]) + hi(bx[j]);
      }
      if (layer) break;
      sm += __shfl_xor_sync(~0u, sm, 1); sm += __shfl_xor_sync(~0u, sm, 2);
      sm *= 1.f / 112.f;
#pragma unroll
      for (int j = 0; j < 14; j++) { const float a = lo(bx[j]) - sm, b = hi(bx[j]) - sm; q = fmaf(a, a, q); q = fmaf(b, b, q); }
      q += __shfl_xor_sync(~0u, q, 1); q += __shfl_xor_sync(~0u, q, 2);
      if (t < 2) gStat[(size_t)(2048 + row0 + r * 8 + g) * 8 + 2 * w + t] = make_float2(sm, q * 0.5f);
      STAMP(11);
      gather(fl + 64, img);
      STAMP(12);
    }
  }
  STAMP(30);
  if (tid == 0) asm volatile("red.relaxed.gpu.global.add.u32 [%0], 1;" ::"l"(gFlag + FL_DONE * 32) : "memory");
  }
}

typedef CUresult (*EncFn)(CUtensorMap*, CUtensorMapDataType, cuuint32_t, void*, const cuuint64_t*, const cuuint64_t*,
                          const cuuint32_t*, const cuuint32_t*, CUtensorMapInterleave, CUtensorMapSwizzle,
                          CUtensorMapL2promotion, CUtensorMapFloatOOBfill);

void make_map(EncFn enc, CUtensorMap* m, void* p, int rank, uint64_t d0, uint64_t d1, uint64_t d2, uint64_t s1, uint64_t s2,
              uint32_t b0, uint32_t b1, uint32_t b2, CUtensorMapSwizzle sw) {
  cuuint64_t dims[3] = {d0, d1, d2}, strides[2] = {s1, s2};
  cuuint32_t box[3] = {b0, b1, b2}, es[3] = {1, 1, 1};
  enc(m, CU_TENSOR_MAP_DATA_TYPE_BFLOAT16, rank, p, dims, strides, box, es, CU_TENSOR_MAP_INTERLEAVE_NONE, sw,
      CU_TENSOR_MAP_L2_PROMOTION_L2_128B, CU_TENSOR_MAP_FLOAT_OOB_FILL_NONE);
}

}

extern "C" void kernel_launch(void* const* d_in, const int* in_sizes, int n_in, void* d_out, int out_size) {
  static EncFn enc = nullptr;
  if (!enc) {
    cudaDriverEntryPointQueryResult st;
    void* fn = nullptr;
    cudaGetDriverEntryPoint("cuTensorMapEncodeTiled", &fn, cudaEnableDefault, &st);
    enc = (EncFn)fn;
    cudaFuncSetAttribute(fused_kernel, cudaFuncAttributeMaxDynamicSharedMemorySize, SMEM_BYTES);
  }
  CUtensorMap mQKV, mWO, mW1, mW2, mX;
  make_map(enc, &mX, d_in[0], 2, 448, 2048, 1, 896, 0, 64, 64, 1, CU_TENSOR_MAP_SWIZZLE_128B);
  make_map(enc, &mQKV, d_in[1], 3, 448, 448, 3, 2688, 896, 64, 32, 3, CU_TENSOR_MAP_SWIZZLE_128B);
  make_map(enc, &mWO, d_in[3], 2, 448, 448, 1, 896, 0, 64, 112, 1, CU_TENSOR_MAP_SWIZZLE_128B);
  make_map(enc, &mW1, d_in[5], 3, 32, 448, 56, 3584, 64, 32, 32, 7, CU_TENSOR_MAP_SWIZZLE_64B);
  make_map(enc, &mW2, d_in[7], 2, 448, 1792, 1, 896, 0, 64, 112, 1, CU_TENSOR_MAP_SWIZZLE_128B);
  fused_kernel<<<NCTA, 384, SMEM_BYTES, cudaStreamPerThread>>>(
      mQKV, mWO, mW1, mW2, mX, (const __nv_bfloat16*)d_in[2], (const __nv_bfloat16*)d_in[6],
      (const __nv_bfloat16*)d_in[8], (const __nv_bfloat16*)d_in[1], (const __nv_bfloat16*)d_in[3], (const __nv_bfloat16*)d_in[5],
      (const __nv_bfloat16*)d_in[7], (__nv_bfloat16*)d_out);
}
```

```cpp
#include <cuda_runtime.h>
#include <cuda_bf16.h>
#include <cuda.h>
#include <stdint.h>

namespace {

constexpr int DM = 448, NCTA = 128;
constexpr int ABYTES = 57344;
constexpr int SLOT = 14336, NSLOT = 7;
constexpr int OFF_RING = 2 * ABYTES;
constexpr int OFF_WPHI = OFF_RING + NSLOT * SLOT;
constexpr int OFF_B1 = OFF_WPHI + 8192;
constexpr int OFF_CS = OFF_B1 + 896;
constexpr int OFF_BAR = OFF_CS + 1664;
constexpr int SMEM_BYTES = OFF_BAR + 272 + 1024;
constexpr int TILES_PER_LAYER = 46;

__device__ __align__(1024) unsigned char gP[16 * 2 * 8 * 8 * 7168];
__device__ __align__(1024) unsigned char gImg[3 * 32 * ABYTES];
__device__ __align__(1024) float2 gStat[2 * 2048 * 8];
__device__ __align__(1024) float4 gKV[2 * 8 * 2 * 5 * 128];
__device__ __align__(1024) float4 gCS[8 * 16 * 104];
__device__ __align__(128) unsigned gFlag[(2 * 32 * 7 + 32 + 1 + 16) * 32];
#define STAMP(i)

__device__ __forceinline__ uint32_t smem_u32(const void* p) { return (uint32_t)__cvta_generic_to_shared(p); }
__device__ __forceinline__ void mbar_init(uint32_t b, int c) { asm volatile("mbarrier.init.shared::cta.b64 [%0], %1;" ::"r"(b), "r"(c)); }
__device__ __forceinline__ void mbar_expect(uint32_t b, int bytes) { asm volatile("mbarrier.arrive.expect_tx.shared::cta.b64 _, [%0], %1;" ::"r"(b), "r"(bytes) : "memory"); }
__device__ __forceinline__ void mbar_arrive(uint32_t b) { asm volatile("mbarrier.arrive.shared::cta.b64 _, [%0];" ::"r"(b) : "memory"); }
__device__ __forceinline__ void mbar_wait(uint32_t b, int par) {
  uint32_t ok; int n = 0;
#pragma unroll 1
  while (true) {
    asm volatile("{.reg .pred p; mbarrier.try_wait.parity.shared::cta.b64 p, [%1], %2; selp.u32 %0,1,0,p;}" : "=r"(ok) : "r"(b), "r"(par) : "memory");
    if (ok) break;
    if (++n > (1 << 22)) break;
  }
}
__device__ __forceinline__ void flag_wait(const unsigned* f, unsigned target) {
  unsigned v; int n = 0;
#pragma unroll 1
  while (true) {
    asm volatile("ld.acquire.gpu.global.u32 %0, [%1];" : "=r"(v) : "l"(f) : "memory");
    if ((int)(v - target) >= 0) break;
    if (++n > (1 << 21)) break;
  }
}
__device__ __forceinline__ void flag_arrive(unsigned* f) { asm volatile("red.release.gpu.global.add.u32 [%0], 1;" ::"l"(f) : "memory"); }
__device__ __forceinline__ bool elect_one() {
  uint32_t p; asm volatile("{.reg .pred P; elect.sync _|P, 0xffffffff; selp.u32 %0, 1, 0, P;}" : "=r"(p)); return p;
}
__device__ __forceinline__ void fence_async() { asm volatile("fence.proxy.async.global;" ::: "memory"); }
__device__ __forceinline__ void fence_async_smem() { asm volatile("fence.proxy.async.shared::cta;" ::: "memory"); }
template <int ID, int N> __device__ __forceinline__ void bar_sync() { asm volatile("bar.sync %0, %1;" ::"n"(ID), "n"(N) : "memory"); }
__device__ __forceinline__ void bar_wg(int c) { if (c) bar_sync<2, 128>(); else bar_sync<1, 128>(); }
__device__ __forceinline__ void wg_fence() { asm volatile("wgmma.fence.sync.aligned;" ::: "memory"); }
__device__ __forceinline__ void wg_commit() { asm volatile("wgmma.commit_group.sync.aligned;" ::: "memory"); }
template <int N> __device__ __forceinline__ void wg_wait() { asm volatile("wgmma.wait_group.sync.aligned %0;" ::"n"(N) : "memory"); }
template <int N> __device__ __forceinline__ void reg_fence(float (&d)[N]) {
#pragma unroll
  for (int i = 0; i < N; i++) asm volatile("" : "+f"(d[i])::"memory");
}
template <int N> __device__ __forceinline__ void reg_def(float (&d)[N]) {
#pragma unroll
  for (int i = 0; i < N; i++) d[i] = 0.f;
}
__device__ __forceinline__ uint64_t mkdesc(uint32_t addr, uint32_t lbo, uint32_t sbo, uint64_t swz) {
  return (uint64_t)((addr & 0x3FFFF) >> 4) | ((uint64_t)(lbo >> 4) << 16) | ((uint64_t)(sbo >> 4) << 32) | (swz << 62);
}
__device__ __forceinline__ uint32_t pack(float a, float b) {
  uint32_t r; asm("cvt.rn.bf16x2.f32 %0, %1, %2;" : "=r"(r) : "f"(b), "f"(a)); return r;
}
__device__ __forceinline__ uint32_t relu_sq(float a, float b) {
  uint32_t r; asm("{.reg .b32 v; cvt.rn.relu.bf16x2.f32 v, %1, %2; mul.rn.bf16x2 %0, v, v;}" : "=r"(r) : "f"(b), "f"(a)); return r;
}
__device__ __forceinline__ float lo(uint32_t u) { return __uint_as_float(u << 16); }
__device__ __forceinline__ float hi(uint32_t u) { return __uint_as_float(u & 0xFFFF0000u); }
__device__ __forceinline__ float ex2(float x) { float y; asm("ex2.approx.ftz.f32 %0, %1;" : "=f"(y) : "f"(x)); return y; }
__device__ __forceinline__ void stsm4(uint32_t a, uint32_t r0, uint32_t r1, uint32_t r2, uint32_t r3) {
  asm volatile("stmatrix.sync.aligned.m8n8.x4.shared.b16 [%0], {%1,%2,%3,%4};" ::"r"(a), "r"(r0), "r"(r1), "r"(r2), "r"(r3) : "memory");
}
__device__ __forceinline__ void tma3(uint32_t dst, const CUtensorMap* m, int c0, int c1, int c2, uint32_t bar) {
  asm volatile("cp.async.bulk.tensor.3d.shared::cluster.global.mbarrier::complete_tx::bytes [%0], [%1, {%3,%4,%5}], [%2];"
               ::"r"(dst), "l"(m), "r"(bar), "r"(c0), "r"(c1), "r"(c2) : "memory");
}
__device__ __forceinline__ void tma2(uint32_t dst, const CUtensorMap* m, int c0, int c1, uint32_t bar) {
  asm volatile("cp.async.bulk.tensor.2d.shared::cluster.global.mbarrier::complete_tx::bytes [%0], [%1, {%3,%4}], [%2];"
               ::"r"(dst), "l"(m), "r"(bar), "r"(c0), "r"(c1) : "memory");
}
__device__ __forceinline__ uint32_t lds32(uint32_t a) { uint32_t v; asm volatile("ld.shared.u32 %0, [%1];" : "=r"(v) : "r"(a) : "memory"); return v; }
__device__ __forceinline__ void bulk_ld(uint32_t dst, const void* src, int bytes, uint32_t bar) {
  asm volatile("cp.async.bulk.shared::cluster.global.mbarrier::complete_tx::bytes [%0], [%1], %2, [%3];" ::"r"(dst), "l"(src), "r"(bytes), "r"(bar) : "memory");
}
__device__ __forceinline__ uint4 ldcg4(const void* p) {
  uint4 v; asm volatile("ld.global.cg.v4.u32 {%0,%1,%2,%3}, [%4];" : "=r"(v.x), "=r"(v.y), "=r"(v.z), "=r"(v.w) : "l"(p) : "memory"); return v;
}

__device__ __forceinline__ uint2 ldcg2(const void* p) {
  uint2 v; asm volatile("ld.global.cg.v2.u32 {%0,%1}, [%2];" : "=r"(v.x), "=r"(v.y) : "l"(p) : "memory"); return v;
}

__device__ __forceinline__ void mma_ss_184(float (&d)[92], uint64_t da, uint64_t db, int acc) {
  asm volatile("{.reg .pred p; setp.ne.b32 p, %94, 0;\n"
    "wgmma.mma_async.sync.aligned.m64n184k16.f32.bf16.bf16 {%0,%1,%2,%3,%4,%5,%6,%7,%8,%9,%10,%11,%12,%13,%14,%15,%16,%17,%18,%19,%20,%21,%22,%23,%24,%25,%26,%27,%28,%29,%30,%31,%32,%33,%34,%35,%36,%37,%38,%39,%40,%41,%42,%43,%44,%45,%46,%47,%48,%49,%50,%51,%52,%53,%54,%55,%56,%57,%58,%59,%60,%61,%62,%63,%64,%65,%66,%67,%68,%69,%70,%71,%72,%73,%74,%75,%76,%77,%78,%79,%80,%81,%82,%83,%84,%85,%86,%87,%88,%89,%90,%91}, %92, %93, p, 1, 1, 0, 1;}\n"
    : "+f"(d[0]),"+f"(d[1]),"+f"(d[2]),"+f"(d[3]),"+f"(d[4]),"+f"(d[5]),"+f"(d[6]),"+f"(d[7]),"+f"(d[8]),"+f"(d[9]),"+f"(d[10]),"+f"(d[11]),"+f"(d[12]),"+f"(d[13]),"+f"(d[14]),"+f"(d[15]),"+f"(d[16]),"+f"(d[17]),"+f"(d[18]),"+f"(d[19]),"+f"(d[20]),"+f"(d[21]),"+f"(d[22]),"+f"(d[23]),"+f"(d[24]),"+f"(d[25]),"+f"(d[26]),"+f"(d[27]),"+f"(d[28]),"+f"(d[29]),"+f"(d[30]),"+f"(d[31]),"+f"(d[32]),"+f"(d[33]),"+f"(d[34]),"+f"(d[35]),"+f"(d[36]),"+f"(d[37]),"+f"(d[38]),"+f"(d[39]),"+f"(d[40]),"+f"(d[41]),"+f"(d[42]),"+f"(d[43]),"+f"(d[44]),"+f"(d[45]),"+f"(d[46]),"+f"(d[47]),"+f"(d[48]),"+f"(d[49]),"+f"(d[50]),"+f"(d[51]),"+f"(d[52]),"+f"(d[53]),"+f"(d[54]),"+f"(d[55]),"+f"(d[56]),"+f"(d[57]),"+f"(d[58]),"+f"(d[59]),"+f"(d[60]),"+f"(d[61]),"+f"(d[62]),"+f"(d[63]),"+f"(d[64]),"+f"(d[65]),"+f"(d[66]),"+f"(d[67]),"+f"(d[68]),"+f"(d[69]),"+f"(d[70]),"+f"(d[71]),"+f"(d[72]),"+f"(d[73]),"+f"(d[74]),"+f"(d[75]),"+f"(d[76]),"+f"(d[77]),"+f"(d[78]),"+f"(d[79]),"+f"(d[80]),"+f"(d[81]),"+f"(d[82]),"+f"(d[83]),"+f"(d[84]),"+f"(d[85]),"+f"(d[86]),"+f"(d[87]),"+f"(d[88]),"+f"(d[89]),"+f"(d[90]),"+f"(d[91])
    : "l"(da), "l"(db), "r"(acc));
}
__device__ __forceinline__ void mma_ss_224(float (&d)[112], uint64_t da, uint64_t db, int acc) {
  asm volatile("{.reg .pred p; setp.ne.b32 p, %114, 0;\n"
    "wgmma.mma_async.sync.aligned.m64n224k16.f32.bf16.bf16 {%0,%1,%2,%3,%4,%5,%6,%7,%8,%9,%10,%11,%12,%13,%14,%15,%16,%17,%18,%19,%20,%21,%22,%23,%24,%25,%26,%27,%28,%29,%30,%31,%32,%33,%34,%35,%36,%37,%38,%39,%40,%41,%42,%43,%44,%45,%46,%47,%48,%49,%50,%51,%52,%53,%54,%55,%56,%57,%58,%59,%60,%61,%62,%63,%64,%65,%66,%67,%68,%69,%70,%71,%72,%73,%74,%75,%76,%77,%78,%79,%80,%81,%82,%83,%84,%85,%86,%87,%88,%89,%90,%91,%92,%93,%94,%95,%96,%97,%98,%99,%100,%101,%102,%103,%104,%105,%106,%107,%108,%109,%110,%111}, %112, %113, p, 1, 1, 0, 1;}\n"
    : "+f"(d[0]),"+f"(d[1]),"+f"(d[2]),"+f"(d[3]),"+f"(d[4]),"+f"(d[5]),"+f"(d[6]),"+f"(d[7]),"+f"(d[8]),"+f"(d[9]),"+f"(d[10]),"+f"(d[11]),"+f"(d[12]),"+f"(d[13]),"+f"(d[14]),"+f"(d[15]),"+f"(d[16]),"+f"(d[17]),"+f"(d[18]),"+f"(d[19]),"+f"(d[20]),"+f"(d[21]),"+f"(d[22]),"+f"(d[23]),"+f"(d[24]),"+f"(d[25]),"+f"(d[26]),"+f"(d[27]),"+f"(d[28]),"+f"(d[29]),"+f"(d[30]),"+f"(d[31]),"+f"(d[32]),"+f"(d[33]),"+f"(d[34]),"+f"(d[35]),"+f"(d[36]),"+f"(d[37]),"+f"(d[38]),"+f"(d[39]),"+f"(d[40]),"+f"(d[41]),"+f"(d[42]),"+f"(d[43]),"+f"(d[44]),"+f"(d[45]),"+f"(d[46]),"+f"(d[47]),"+f"(d[48]),"+f"(d[49]),"+f"(d[50]),"+f"(d[51]),"+f"(d[52]),"+f"(d[53]),"+f"(d[54]),"+f"(d[55]),"+f"(d[56]),"+f"(d[57]),"+f"(d[58]),"+f"(d[59]),"+f"(d[60]),"+f"(d[61]),"+f"(d[62]),"+f"(d[63]),"+f"(d[64]),"+f"(d[65]),"+f"(d[66]),"+f"(d[67]),"+f"(d[68]),"+f"(d[69]),"+f"(d[70]),"+f"(d[71]),"+f"(d[72]),"+f"(d[73]),"+f"(d[74]),"+f"(d[75]),"+f"(d[76]),"+f"(d[77]),"+f"(d[78]),"+f"(d[79]),"+f"(d[80]),"+f"(d[81]),"+f"(d[82]),"+f"(d[83]),"+f"(d[84]),"+f"(d[85]),"+f"(d[86]),"+f"(d[87]),"+f"(d[88]),"+f"(d[89]),"+f"(d[90]),"+f"(d[91]),"+f"(d[92]),"+f"(d[93]),"+f"(d[94]),"+f"(d[95]),"+f"(d[96]),"+f"(d[97]),"+f"(d[98]),"+f"(d[99]),"+f"(d[100]),"+f"(d[101]),"+f"(d[102]),"+f"(d[103]),"+f"(d[104]),"+f"(d[105]),"+f"(d[106]),"+f"(d[107]),"+f"(d[108]),"+f"(d[109]),"+f"(d[110]),"+f"(d[111])
    : "l"(da), "l"(db), "r"(acc));
}
__device__ __forceinline__ void mma_ss_56(float (&d)[28], uint64_t da, uint64_t db, int acc) {
  asm volatile("{.reg .pred p; setp.ne.b32 p, %30, 0;\n"
    "wgmma.mma_async.sync.aligned.m64n56k16.f32.bf16.bf16 {%0,%1,%2,%3,%4,%5,%6,%7,%8,%9,%10,%11,%12,%13,%14,%15,%16,%17,%18,%19,%20,%21,%22,%23,%24,%25,%26,%27}, %28, %29, p, 1, 1, 0, 1;}\n"
    : "+f"(d[0]),"+f"(d[1]),"+f"(d[2]),"+f"(d[3]),"+f"(d[4]),"+f"(d[5]),"+f"(d[6]),"+f"(d[7]),"+f"(d[8]),"+f"(d[9]),"+f"(d[10]),"+f"(d[11]),"+f"(d[12]),"+f"(d[13]),"+f"(d[14]),"+f"(d[15]),"+f"(d[16]),"+f"(d[17]),"+f"(d[18]),"+f"(d[19]),"+f"(d[20]),"+f"(d[21]),"+f"(d[22]),"+f"(d[23]),"+f"(d[24]),"+f"(d[25]),"+f"(d[26]),"+f"(d[27])
    : "l"(da), "l"(db), "r"(acc));
}
__device__ __forceinline__ void mma_rs_56(float (&d)[28], uint32_t a0, uint32_t a1, uint32_t a2, uint32_t a3, uint64_t db, int acc) {
  asm volatile("{.reg .pred p; setp.ne.b32 p, %33, 0;\n"
    "wgmma.mma_async.sync.aligned.m64n56k16.f32.bf16.bf16 {%0,%1,%2,%3,%4,%5,%6,%7,%8,%9,%10,%11,%12,%13,%14,%15,%16,%17,%18,%19,%20,%21,%22,%23,%24,%25,%26,%27}, {%28,%29,%30,%31}, %32, p, 1, 1, 1;}\n"
    : "+f"(d[0]),"+f"(d[1]),"+f"(d[2]),"+f"(d[3]),"+f"(d[4]),"+f"(d[5]),"+f"(d[6]),"+f"(d[7]),"+f"(d[8]),"+f"(d[9]),"+f"(d[10]),"+f"(d[11]),"+f"(d[12]),"+f"(d[13]),"+f"(d[14]),"+f"(d[15]),"+f"(d[16]),"+f"(d[17]),"+f"(d[18]),"+f"(d[19]),"+f"(d[20]),"+f"(d[21]),"+f"(d[22]),"+f"(d[23]),"+f"(d[24]),"+f"(d[25]),"+f"(d[26]),"+f"(d[27])
    : "r"(a0), "r"(a1), "r"(a2), "r"(a3), "l"(db), "r"(acc));
}
__device__ __forceinline__ void mma_ss_64t(float (&d)[32], uint64_t da, uint64_t db, int acc) {
  asm volatile("{.reg .pred p; setp.ne.b32 p, %34, 0;\n"
    "wgmma.mma_async.sync.aligned.m64n64k16.f32.bf16.bf16 {%0,%1,%2,%3,%4,%5,%6,%7,%8,%9,%10,%11,%12,%13,%14,%15,%16,%17,%18,%19,%20,%21,%22,%23,%24,%25,%26,%27,%28,%29,%30,%31}, %32, %33, p, 1, 1, 1, 1;}\n"
    : "+f"(d[0]),"+f"(d[1]),"+f"(d[2]),"+f"(d[3]),"+f"(d[4]),"+f"(d[5]),"+f"(d[6]),"+f"(d[7]),"+f"(d[8]),"+f"(d[9]),"+f"(d[10]),"+f"(d[11]),"+f"(d[12]),"+f"(d[13]),"+f"(d[14]),"+f"(d[15]),"+f"(d[16]),"+f"(d[17]),"+f"(d[18]),"+f"(d[19]),"+f"(d[20]),"+f"(d[21]),"+f"(d[22]),"+f"(d[23]),"+f"(d[24]),"+f"(d[25]),"+f"(d[26]),"+f"(d[27]),"+f"(d[28]),"+f"(d[29]),"+f"(d[30]),"+f"(d[31])
    : "l"(da), "l"(db), "r"(acc));
}
__device__ __forceinline__ void mma_rs_64(float (&d)[32], uint32_t a0, uint32_t a1, uint32_t a2, uint32_t a3, uint64_t db, int acc) {
  asm volatile("{.reg .pred p; setp.ne.b32 p, %37, 0;\n"
    "wgmma.mma_async.sync.aligned.m64n64k16.f32.bf16.bf16 {%0,%1,%2,%3,%4,%5,%6,%7,%8,%9,%10,%11,%12,%13,%14,%15,%16,%17,%18,%19,%20,%21,%22,%23,%24,%25,%26,%27,%28,%29,%30,%31}, {%32,%33,%34,%35}, %36, p, 1, 1, 1;}\n"
    : "+f"(d[0]),"+f"(d[1]),"+f"(d[2]),"+f"(d[3]),"+f"(d[4]),"+f"(d[5]),"+f"(d[6]),"+f"(d[7]),"+f"(d[8]),"+f"(d[9]),"+f"(d[10]),"+f"(d[11]),"+f"(d[12]),"+f"(d[13]),"+f"(d[14]),"+f"(d[15]),"+f"(d[16]),"+f"(d[17]),"+f"(d[18]),"+f"(d[19]),"+f"(d[20]),"+f"(d[21]),"+f"(d[22]),"+f"(d[23]),"+f"(d[24]),"+f"(d[25]),"+f"(d[26]),"+f"(d[27]),"+f"(d[28]),"+f"(d[29]),"+f"(d[30]),"+f"(d[31])
    : "r"(a0), "r"(a1), "r"(a2), "r"(a3), "l"(db), "r"(acc));
}

__device__ __forceinline__ void dual_softmax(const float (&p)[28], uint32_t (&phi)[4][7]) {
  constexpr float L2E = 1.4426950408889634f;
#pragma unroll
  for (int i = 0; i < 4; i++) {
    float mx = p[i], mn = p[i];
#pragma unroll
    for (int j = 1; j < 7; j++) { mx = fmaxf(mx, p[4 * j + i]); mn = fminf(mn, p[4 * j + i]); }
    mx = fmaxf(mx, __shfl_xor_sync(~0u, mx, 1)); mn = fminf(mn, __shfl_xor_sync(~0u, mn, 1));
    mx = fmaxf(mx, __shfl_xor_sync(~0u, mx, 2)); mn = fminf(mn, __shfl_xor_sync(~0u, mn, 2));
    float a[7], b[7], sa = 0.f, sb = 0.f;
    const float mxl = mx * L2E, mnl = mn * L2E;
#pragma unroll
    for (int j = 0; j < 7; j++) {
      a[j] = ex2(fmaf(p[4 * j + i], L2E, -mxl)); b[j] = ex2(fmaf(p[4 * j + i], -L2E, mnl));
      sa += a[j]; sb += b[j];
    }
    sa += __shfl_xor_sync(~0u, sa, 1); sb += __shfl_xor_sync(~0u, sb, 1);
    sa += __shfl_xor_sync(~0u, sa, 2); sb += __shfl_xor_sync(~0u, sb, 2);
    const float ra = __fdividef(1.f, sa), rb = __fdividef(1.f, sb);
#pragma unroll
    for (int j = 0; j < 7; j++) phi[i][j] = pack(a[j] * ra, b[j] * rb);
  }
}

struct Ring {
  uint32_t full, empty, base; int slot, par;
  __device__ __forceinline__ uint32_t acquire() { mbar_wait(full + slot * 8, par); return base + slot * SLOT; }
  __device__ __forceinline__ int advance() { int s = slot; if (++slot == NSLOT) { slot = 0; par ^= 1; } return s; }
  __device__ __forceinline__ void release(int s, bool elect) { if (elect) mbar_arrive(empty + s * 8); }
};
constexpr int UNR = 14;
constexpr int FL_KV = 448, FL_CS = FL_KV + 16, FL_DONE = FL_KV + 32;

__global__ void __launch_bounds__(384, 1)
fused_kernel(const __grid_constant__ CUtensorMap mQKV, const __grid_constant__ CUtensorMap mWO,
             const __grid_constant__ CUtensorMap mW1, const __grid_constant__ CUtensorMap mW2,
             const __grid_constant__ CUtensorMap mX, const __nv_bfloat16* __restrict__ wphi,
             const __nv_bfloat16* __restrict__ b1, const __nv_bfloat16* __restrict__ b2,
             const __nv_bfloat16* __restrict__ wqkv, const __nv_bfloat16* __restrict__ wo, const __nv_bfloat16* __restrict__ w1,
             const __nv_bfloat16* __restrict__ w2, __nv_bfloat16* __restrict__ out) {
  extern __shared__ unsigned char smem_raw[];
  const uint32_t sb = (smem_u32(smem_raw) + 1023) & ~1023u;
  unsigned char* sg = smem_raw + (sb - smem_u32(smem_raw));
  const int tid = threadIdx.x, lane = tid & 31;
  const int G = blockIdx.x >> 3, r = blockIdx.x & 7;
  const uint32_t barFull = sb + OFF_BAR, barEmpty = barFull + 56, barA = barEmpty + 56, barCS = barA + 112, barX = barCS + 16;
  const int warp = __shfl_sync(~0u, tid >> 5, 0);
  uint32_t wv[7], bv;
#pragma unroll
  for (int i = 0; i < 7; i++)
    wv[i] = __ldg(reinterpret_cast<const unsigned short*>(wphi) + (56 * r + i * 8 + (warp & 7)) * 28 + min(lane, 27));
  bv = __ldg(reinterpret_cast<const unsigned short*>(b1) + 224 * r + min(tid, 223));
  if (lane == 0) {
    if (warp >= 10) {
      const int cc = warp - 10;
      mbar_init(barX + cc * 8, 1);
      fence_async_smem();
      mbar_expect(barX + cc * 8, ABYTES);
#pragma unroll 1
      for (int k = 0; k < 7; k++) tma2(sb + cc * ABYTES + k * 8192, &mX, 64 * k, G * 128 + 64 * cc, barX + cc * 8);
    } else if (warp < 7) { mbar_init(barFull + warp * 8, 1); mbar_init(barEmpty + warp * 8, 2); mbar_init(barA + warp * 8, 1); mbar_init(barA + 56 + warp * 8, 1); }
    else if (warp < 9) mbar_init(barCS + (warp - 7) * 8, 96);
    else
      asm volatile("cp.async.bulk.prefetch.L2.global [%0], %1;" ::"l"((const char*)wqkv + blockIdx.x * 9408), "r"(9408) : "memory");
    asm volatile("fence.mbarrier_init.release.cluster;" ::: "memory");
  }
  if (tid < 192) reinterpret_cast<float*>(sg + OFF_CS)[tid] = 0.f;
  __syncthreads();
  const int wgid = warp >> 2;
  if (wgid == 2) {
    asm volatile("setmaxnreg.dec.sync.aligned.u32 40;");
    if (warp == 8) {
      int slot = 0, par = 1;
#pragma unroll 1
      for (int it = 0; it < 2 * TILES_PER_LAYER; it++) {
        const int i = it >= TILES_PER_LAYER ? it - TILES_PER_LAYER : it;
        mbar_wait(barEmpty + slot * 8, par);
        const uint32_t dst = sb + OFF_RING + slot * SLOT, fb = barFull + slot * 8;
        if (elect_one()) {
          mbar_expect(fb, i < 14 ? 12288 : SLOT);
          if (i < 14) tma3(dst, &mQKV, 56 * r, 32 * i, 0, fb);
          else if (i < 18) tma2(dst, &mWO, 56 * r, 112 * (i - 14), fb);
          else if (i < 32) tma3(dst, &mW1, 0, 32 * (i - 18), 7 * r, fb);
          else tma2(dst, &mW2, 64 * ((i - 32) >> 1), 224 * r + 112 * (i & 1), fb);
        }
        if (++slot == NSLOT) { slot = 0; par ^= 1; }
      }
    } else {
      unsigned ep;
      asm volatile("ld.relaxed.gpu.global.u32 %0, [%1];" : "=r"(ep) : "l"(gFlag + FL_DONE * 32) : "memory");
      const int idx = tid - 288;
      ep = (ep / NCTA + 1) * 3;
      if (G == 0) {
#pragma unroll 1
        for (int i = idx; i < 2 * 1280; i += 96) gKV[((i >= 1280) * 7 + r) * 1280 + i] = make_float4(0.f, 0.f, 0.f, 0.f);
        __syncwarp();
        if (lane == 0) flag_arrive(gFlag + (FL_CS + r) * 32);
      }
      mbar_wait(barFull + 48, 0); mbar_wait(barFull + 48, 1);
      if (idx < 2) {
        const char* pf = idx ? (const char*)w2 + blockIdx.x * 12544 : (const char*)wo + blockIdx.x * 3136;
        asm volatile("cp.async.bulk.prefetch.L2.global [%0], %1;" ::"l"(pf), "r"(idx ? 12544 : 3136) : "memory");
      }
      if (lane == 0) flag_wait(gFlag + (FL_CS + r) * 32, ep);
      __syncwarp();
      mbar_arrive(barCS);
#pragma unroll 1
      for (int ps = 0; ps < 3; ps++) {
        const int nch = ps ? 14 : 21, ch = min(idx >> 2, nch - 1), p = ch / 7, k0 = G * 28 + (idx & 3) * 7;
        const uint4* src = ps ? reinterpret_cast<const uint4*>(w1 + (size_t)k0 * 1792 + 224 * r) + (ps - 1) * 14 + ch
                              : reinterpret_cast<const uint4*>(wqkv + (size_t)k0 * 1344 + p * 448 + 56 * r) + (ch - 7 * p);
        uint4 cu[7];
#pragma unroll
        for (int i = 0; i < 7; i++) cu[i] = __ldg(src + i * (ps ? 224 : 168));
        float s[8] = {};
#pragma unroll
        for (int i = 0; i < 7; i++) { s[0] += lo(cu[i].x); s[1] += hi(cu[i].x); s[2] += lo(cu[i].y); s[3] += hi(cu[i].y); s[4] += lo(cu[i].z); s[5] += hi(cu[i].z); s[6] += lo(cu[i].w); s[7] += hi(cu[i].w); }
#pragma unroll
        for (int i = 0; i < 8; i++) { s[i] += __shfl_xor_sync(~0u, s[i], 1); s[i] += __shfl_xor_sync(~0u, s[i], 2); }
        if ((idx & 3) < 2 && idx < nch * 4) gCS[(r * 16 + G) * 104 + (ps ? 10 + ps * 14 + ch : ch + p) * 2 + (idx & 1)] = (idx & 1) ? make_float4(s[4], s[5], s[6], s[7]) : make_float4(s[0], s[1], s[2], s[3]);
      }
      __syncwarp();
      if (lane == 0) { flag_arrive(gFlag + (FL_CS + 8 + r) * 32); flag_wait(gFlag + (FL_CS + 8 + r) * 32, ep * 16); }
      __syncwarp();
#pragma unroll 1
      for (int j = idx; j < 208; j += 96) {
        float2 a = make_float2(0.f, 0.f);
#pragma unroll 8
        for (int i = 0; i < 16; i++) { const float2 v = __ldcg(reinterpret_cast<const float2*>(gCS + (r * 16 + i) * 104) + j); a.x += v.x; a.y += v.y; }
        reinterpret_cast<float2*>(sg + OFF_CS)[j] = a;
      }
      mbar_arrive(barCS + 8);
    }
  } else {
  asm volatile("setmaxnreg.inc.sync.aligned.u32 232;");
  const int c = wgid, w = warp & 3, g = lane >> 2, t = lane & 3;
  int elect_i = (tid & 127) == 0;
  asm volatile("" : "+r"(elect_i));
  const bool elect = elect_i;
  const uint32_t abuf = sb + c * ABYTES, barAc = barA + c * 56;
  const int row0 = G * 128 + c * 64;
  unsigned epoch;
  asm volatile("ld.relaxed.gpu.global.u32 %0, [%1];" : "=r"(epoch) : "l"(gFlag + FL_DONE * 32) : "memory");
  STAMP(24);
  float mean[2], rstd[2];
  uint4 su[2] = {};
  uint32_t xs[7][2];
  {
#pragma unroll
    for (int i = 0; i < 8; i++) {
      const int k = i * 8 + (tid >> 5);
      *reinterpret_cast<uint32_t*>(sg + OFF_WPHI + k * 128 + ((g ^ (k & 7)) << 4) + t * 4) = (i < 7 && lane < 28) ? wv[i % 7] << (k >= 28 ? 16 : 0) : 0u;
    }
    if (tid < 224) reinterpret_cast<uint32_t*>(sg + OFF_B1)[tid] = bv << 16;
    mbar_wait(barX + c * 8, 0);
    STAMP(25);
#pragma unroll
    for (int j = 0; j < 7; j++) {
      const int ci = 7 * r + j;
      const uint32_t a = abuf + (ci >> 3) * 8192 + (w * 16 + g) * 128 + (((ci & 7) ^ g) << 4) + t * 4;
      xs[j][0] = lds32(a); xs[j][1] = lds32(a + 1024);
    }
    __syncwarp();
#pragma unroll 1
    for (int hh = 0; hh < 2; hh++) {
      uint4* p = reinterpret_cast<uint4*>(sg + c * ABYTES + (w * 16 + hh * 8 + g) * 128) + t;
      uint4 v[14];
#pragma unroll
      for (int k = 0; k < 14; k++) v[k] = p[(k >> 1) * 512 + ((k ^ g) & 1) * 4];
      float a8[8] = {};
#pragma unroll
      for (int k = 0; k < 14; k++) {
        const uint32_t e[4] = {v[k].x, v[k].y, v[k].z, v[k].w};
#pragma unroll
        for (int z = 0; z < 4; z++) { a8[2 * z] += lo(e[z]); a8[2 * z + 1] += hi(e[z]); }
      }
      float sm = ((a8[0] + a8[1]) + (a8[2] + a8[3])) + ((a8[4] + a8[5]) + (a8[6] + a8[7]));
      sm += __shfl_xor_sync(~0u, sm, 1); sm += __shfl_xor_sync(~0u, sm, 2);
      sm *= 1.f / DM;
#pragma unroll
      for (int k = 0; k < 14; k++) {
        const uint32_t e[4] = {v[k].x, v[k].y, v[k].z, v[k].w};
#pragma unroll
        for (int z = 0; z < 4; z++) {
          const float a = lo(e[z]) - sm, b = hi(e[z]) - sm;
          a8[2 * z] = fmaf(a, a, k ? a8[2 * z] : 0.f); a8[2 * z + 1] = fmaf(b, b, k ? a8[2 * z + 1] : 0.f);
        }
      }
      float q = ((a8[0] + a8[1]) + (a8[2] + a8[3])) + ((a8[4] + a8[5]) + (a8[6] + a8[7]));
      q += __shfl_xor_sync(~0u, q, 1); q += __shfl_xor_sync(~0u, q, 2);
      q = rsqrtf(q * (1.f / DM) + 1e-5f);
      sm *= -q;
#pragma unroll
      for (int k = 0; k < 14; k++)
        p[(k >> 1) * 512 + ((k ^ g) & 1) * 4] = make_uint4(pack(fmaf(lo(v[k].x), q, sm), fmaf(hi(v[k].x), q, sm)), pack(fmaf(lo(v[k].y), q, sm), fmaf(hi(v[k].y), q, sm)),
                                                           pack(fmaf(lo(v[k].z), q, sm), fmaf(hi(v[k].z), q, sm)), pack(fmaf(lo(v[k].w), q, sm), fmaf(hi(v[k].w), q, sm)));
    }
    fence_async_smem();
    bar_sync<3, 256>();
    epoch = epoch / NCTA + 1;
    mean[0] = mean[1] = 0.f; rstd[0] = rstd[1] = 1.f;
  }
  STAMP(0);
  Ring ring{barFull, barEmpty, sb + OFF_RING, 0, 0};
  int apar = 1;
  const uint32_t stsm_off = (w * 16 + ((lane >> 3) & 1) * 8 + (lane & 7)) * 128;
  const uint32_t stsm_hi = lane >> 4;
  const uint64_t dA = mkdesc(abuf, 1024, 128, 0);

  auto gather = [&](unsigned* fl, const unsigned char* img) {
    __syncwarp();
    if (lane == 0) {
      flag_arrive(fl);
      STAMP(27);
      flag_wait(fl, epoch * 32);
      STAMP(28);
      fence_async();
      mbar_expect(barAc + w * 8, 8192); bulk_ld(abuf + w * 8192, img + w * 8192, 8192, barAc + w * 8);
      if (w < 3) { mbar_expect(barAc + 32 + w * 8, 8192); bulk_ld(abuf + 32768 + w * 8192, img + 32768 + w * 8192, 8192, barAc + 32 + w * 8); }
    }
    __syncwarp();
    apar ^= 1;
  };
  auto slice_off = [&](int j, int hh) -> uint32_t {
    return (7 * r + j) * 1024 + (w * 2 + hh) * 128 + lane * 4;
  };
  auto load_stats = [&](const float2* st) {
    mbar_wait(barAc, apar);
#pragma unroll
    for (int hh = 0; hh < 2; hh++) su[hh] = ldcg4(st + (size_t)(row0 + w * 16 + hh * 8 + g) * 8 + 2 * t);
  };
  auto finish_stats = [&]() {
#pragma unroll
    for (int hh = 0; hh < 2; hh++) {
      const float m0 = __uint_as_float(su[hh].x), m1 = __uint_as_float(su[hh].z);
      float m = m0 + m1;
      m += __shfl_xor_sync(~0u, m, 1); m += __shfl_xor_sync(~0u, m, 2);
      m *= 0.125f;
      float q = __uint_as_float(su[hh].y) + __uint_as_float(su[hh].w) + 56.f * ((m0 - m) * (m0 - m) + (m1 - m) * (m1 - m));
      q += __shfl_xor_sync(~0u, q, 1); q += __shfl_xor_sync(~0u, q, 2);
      mean[hh] = m; rstd[hh] = rsqrtf(q * (1.f / DM) + 1e-5f);
    }
  };

#pragma unroll 1
  for (int layer = 0; layer < 2; layer++) {
    unsigned* const fl = gFlag + (layer * 32 + G * 2 + c) * 7 * 32;
    uint32_t phiq[4][7];
    {
      float acc[92]; reg_def(acc);
      int prev = 0, prev2 = 0;
      const uint64_t dQ = layer ? dA : mkdesc(abuf, 16, 1024, 1);
      const int kstep = layer ? 128 : 2;
      if (layer) load_stats(gStat + 2048 * 8);
#pragma unroll UNR
      for (int st = 0; st < 14; st++) {
        if (!(st & 1) && layer) mbar_wait(barAc + (st >> 1) * 8, apar);
        const uint64_t da = dQ + (st >> 1) * 512 + (st & 1) * 2 * kstep, db = mkdesc(ring.acquire(), 4096, 1024, 1);
        wg_fence();
        mma_ss_184(acc, da, db, 1);
        mma_ss_184(acc, da + kstep, db + 128, 1);
        wg_commit();
        if (st > 1) { wg_wait<2>(); ring.release(prev2, elect); }
        prev2 = prev; prev = ring.advance();
      }
      if (layer) {
        finish_stats();
#pragma unroll
        for (int j = 0; j < 7; j++) { xs[j][0] = lds32(abuf + slice_off(j, 0)); xs[j][1] = lds32(abuf + slice_off(j, 1)); }
      }
      wg_wait<0>(); reg_fence(acc);
      ring.release(prev2, elect); ring.release(prev, elect);
      STAMP(1 + layer * 12);
      uint32_t f[3][14];
      {
        const float2* cs = reinterpret_cast<const float2*>(sg + OFF_CS) + t;
        const float mr0 = -mean[0] * rstd[0], mr1 = -mean[1] * rstd[1];
#pragma unroll
        for (int p = 0; p < 3; p++)
#pragma unroll
          for (int j = 0; j < 7; j++) {
            const float2 s = cs[p * 32 + j * 4];
            const int b = p * 32 + j * 4;
            f[p][2 * j] = pack(fmaf(acc[b], rstd[0], s.x * mr0), fmaf(acc[b + 1], rstd[0], s.y * mr0));
            f[p][2 * j + 1] = pack(fmaf(acc[b + 2], rstd[1], s.x * mr1), fmaf(acc[b + 3], rstd[1], s.y * mr1));
          }
      }
      float pk[28], pq[28]; reg_def(pk); reg_def(pq);
      const uint64_t dW = mkdesc(sb + OFF_WPHI, 4096, 1024, 1);
      wg_fence();
#pragma unroll
      for (int s = 0; s < 4; s++) {
        mma_rs_56(pk, f[1][4 * s], f[1][4 * s + 1], s < 3 ? f[1][(4 * s + 2) % 14] : 0u, s < 3 ? f[1][(4 * s + 3) % 14] : 0u, dW + s * 128, s);
        mma_rs_56(pq, f[0][4 * s], f[0][4 * s + 1], s < 3 ? f[0][(4 * s + 2) % 14] : 0u, s < 3 ? f[0][(4 * s + 3) % 14] : 0u, dW + s * 128, s);
      }
      wg_commit();
      bar_wg(c);
      const uint32_t srow = abuf + stsm_off, ones = t == 0 ? 0x3F803F80u : 0u;
#pragma unroll
      for (int jp = 0; jp < 4; jp++)
        stsm4(srow + 16384 + (((2 * jp + stsm_hi) ^ (lane & 7)) << 4), f[2][4 * jp], f[2][4 * jp + 1],
              jp < 3 ? f[2][(4 * jp + 2) % 14] : ones, jp < 3 ? f[2][(4 * jp + 3) % 14] : ones);
      wg_wait<0>(); reg_fence(pk); reg_fence(pq);
#pragma unroll 1
      for (int pass = 0; pass < 2; pass++) {
        dual_softmax(pk, phiq);
        if (pass) break;
#pragma unroll
        for (int e = 0; e < 2; e++)
#pragma unroll
          for (int jp = 0; jp < 4; jp++)
            stsm4(srow + e * 8192 + (((2 * jp + stsm_hi) ^ (lane & 7)) << 4), phiq[e][2 * jp], phiq[2 + e][2 * jp],
                  jp < 3 ? phiq[e][(2 * jp + 1) % 7] : 0u, jp < 3 ? phiq[2 + e][(2 * jp + 1) % 7] : 0u);
        fence_async_smem();
        bar_sync<3, 256>();
        float kv[32], kw[32]; reg_def(kv); reg_def(kw);
        const uint64_t dP = mkdesc(sb + c * 8192, 4096, 1024, 1), dV = mkdesc(sb + 16384, 4096, 1024, 1);
        wg_fence();
#pragma unroll
        for (int s = 0; s < 4; s++) { mma_ss_64t(kv, dP + s * 128, dV + s * 128, s); mma_ss_64t(kw, dP + ABYTES / 16 + s * 128, dV + ABYTES / 16 + s * 128, s); }
        wg_commit();
        mbar_wait(barCS, 0);
        wg_wait<0>(); reg_fence(kv); reg_fence(kw);
#pragma unroll
        for (int i = 0; i < 32; i++) kv[i] += kw[i];
        float4* kvg = gKV + ((layer * 8 + r) * 2 + c) * 640 + (tid & 127);
#pragma unroll
        for (int i = 0; i < 5; i++) {
          float v0, v1, v2, v3;
          if (i == 4) { v0 = kv[28]; v1 = kv[29]; v2 = kv[30]; v3 = kv[31]; }
          else { v0 = c ? kv[12 + 4 * i] : kv[4 * i]; v1 = c ? kv[13 + 4 * i] : kv[1 + 4 * i]; v2 = c ? kv[14 + 4 * i] : kv[2 + 4 * i]; v3 = c ? kv[15 + 4 * i] : kv[3 + 4 * i]; }
          const bool use = i == 4 ? t == 0 : (i == 0 ? (c == 0 || t >= 2) : (i == 3 ? (c == 1 || t < 2) : true));
          if (use) asm volatile("red.relaxed.gpu.global.add.v4.f32 [%0], {%1,%2,%3,%4};" ::"l"(kvg + i * 128), "f"(v0), "f"(v1), "f"(v2), "f"(v3) : "memory");
        }
        __syncwarp();
        if (lane == 0) flag_arrive(gFlag + (FL_KV + layer * 8 + r) * 32);
        __syncwarp();
        STAMP(2 + layer * 12);
#pragma unroll
        for (int i = 0; i < 28; i++) pk[i] = pq[i];
      }
    }
    {
      if (elect) flag_wait(gFlag + (FL_KV + layer * 8 + r) * 32, epoch * 128);
      bar_wg(c);
      STAMP(3 + layer * 12);
      const float4* kvg = gKV + (layer * 8 + r) * 1280 + (tid & 127);
      uint4 kk[2][5];
#pragma unroll
      for (int e = 0; e < 2; e++)
#pragma unroll
        for (int i = 0; i < 5; i++) kk[e][i] = ldcg4(kvg + e * 640 + i * 128);
      const uint32_t srow = abuf + 24576 + stsm_off;
#pragma unroll
      for (int e = 0; e < 2; e++) {
        uint32_t f[8][2];
#pragma unroll
        for (int j = 0; j < 8; j++) { f[j][0] = 0u; f[j][1] = 0u; }
#pragma unroll
        for (int i = 0; i < 4; i++) {
          f[i + 3 * e][0] = pack(__uint_as_float(kk[e][i].x), __uint_as_float(kk[e][i].y));
          f[i + 3 * e][1] = pack(__uint_as_float(kk[e][i].z), __uint_as_float(kk[e][i].w));
        }
        f[7][0] = e ? pack(0.f, __uint_as_float(kk[e][4].y)) : pack(__uint_as_float(kk[e][4].x), 0.f);
        f[7][1] = e ? pack(0.f, __uint_as_float(kk[e][4].w)) : pack(__uint_as_float(kk[e][4].z), 0.f);
#pragma unroll
        for (int jp = 0; jp < 4; jp++)
          stsm4(srow + e * 8192 + (((2 * jp + stsm_hi) ^ (lane & 7)) << 4), f[2 * jp][0], f[2 * jp][1], f[2 * jp + 1][0], f[2 * jp + 1][1]);
      }
      fence_async_smem();
      bar_wg(c);
      float num[32], nub[32]; reg_def(num); reg_def(nub);
      const uint64_t dK = mkdesc(abuf + 24576, 4096, 1024, 1);
      wg_fence();
#pragma unroll
      for (int s = 0; s < 4; s++) {
        mma_rs_64(num, phiq[0][2 * s], phiq[2][2 * s], s < 3 ? phiq[0][(2 * s + 1) % 7] : 0u, s < 3 ? phiq[2][(2 * s + 1) % 7] : 0u, dK + s * 128, s);
        mma_rs_64(nub, phiq[1][2 * s], phiq[3][2 * s], s < 3 ? phiq[1][(2 * s + 1) % 7] : 0u, s < 3 ? phiq[3][(2 * s + 1) % 7] : 0u, dK + 512 + s * 128, s);
      }
      wg_commit();
      wg_wait<0>(); reg_fence(num); reg_fence(nub);
#pragma unroll
      for (int i = 12; i < 32; i++) num[i] += nub[i];
      float rd[4];
#pragma unroll
      for (int i = 0; i < 4; i++) rd[i] = __fdividef(1.f, __shfl_sync(~0u, num[28 + i], lane & ~3) + 1e-6f);
      unsigned char* img = gImg + (size_t)(G * 2 + c) * ABYTES;
#pragma unroll
      for (int j = 0; j < 7; j++) {
        const bool hb = j > 3 || (j == 3 && t >= 2);
        const float r0 = hb ? rd[1] : rd[0], r1 = hb ? rd[3] : rd[2];
        *reinterpret_cast<uint32_t*>(img + slice_off(j, 0)) = pack(num[4 * j] * r0, num[4 * j + 1] * r0);
        *reinterpret_cast<uint32_t*>(img + slice_off(j, 1)) = pack(num[4 * j + 2] * r1, num[4 * j + 3] * r1);
      }
      STAMP(4 + layer * 12);
      gather(fl, img);
      STAMP(5 + layer * 12);
    }
    {
      float acc[28], acc2[28]; reg_def(acc); reg_def(acc2); reg_fence(acc); reg_fence(acc2);
      int sl[4];
#pragma unroll
      for (int st = 0; st < 4; st++) {
        const uint64_t db = mkdesc(ring.acquire(), 4096, 1024, 1);
        sl[st] = ring.advance();
#pragma unroll
        for (int s = 0; s < 7; s++) {
          const int ks = st * 7 + s;
          if (!(ks & 3)) mbar_wait(barAc + (ks >> 2) * 8, apar);
          if (!(ks & 3) || !s) wg_fence();
          if (ks & 1) mma_ss_56(acc2, dA + ks * 128, db + s * 128, ks > 1); else mma_ss_56(acc, dA + ks * 128, db + s * 128, ks > 1);
        }
        wg_commit();
        if (st > 0) { wg_wait<1>(); ring.release(sl[st - 1], elect); }
      }
      wg_wait<0>(); reg_fence(acc); reg_fence(acc2);
      ring.release(sl[3], elect);
      unsigned char* img = gImg + (size_t)(32 + G * 2 + c) * ABYTES;
#pragma unroll
      for (int hh = 0; hh < 2; hh++) {
        float s = 0.f, q = 0.f;
#pragma unroll
        for (int j = 0; j < 7; j++) {
          xs[j][hh] = pack(lo(xs[j][hh]) + (acc[4 * j + 2 * hh] + acc2[4 * j + 2 * hh]), hi(xs[j][hh]) + (acc[4 * j + 2 * hh + 1] + acc2[4 * j + 2 * hh + 1]));
          *reinterpret_cast<uint32_t*>(img + slice_off(j, hh)) = xs[j][hh];
          s += lo(xs[j][hh]) + hi(xs[j][hh]);
        }
        s += __shfl_xor_sync(~0u, s, 1); s += __shfl_xor_sync(~0u, s, 2);
        s *= 1.f / 56.f;
#pragma unroll
        for (int j = 0; j < 7; j++) { const float a = lo(xs[j][hh]) - s, b = hi(xs[j][hh]) - s; q = fmaf(a, a, q); q = fmaf(b, b, q); }
        q += __shfl_xor_sync(~0u, q, 1); q += __shfl_xor_sync(~0u, q, 2);
        if (t == 0) gStat[(size_t)(row0 + w * 16 + hh * 8 + g) * 8 + r] = make_float2(s, q);
      }
#pragma unroll
      for (int j = 0; j < 7; j++) xs[j][0] = xs[j][1] = 0u;
      STAMP(6 + layer * 12);
      gather(fl + 32, img);
      STAMP(7 + layer * 12);
    }
    {
      uint32_t hf[28][2];
      {
        float acc[112]; reg_def(acc);
        int prev = 0, prev2 = 0;
        load_stats(gStat);
#pragma unroll UNR
        for (int st = 0; st < 14; st++) {
          if (!(st & 1)) mbar_wait(barAc + (st >> 1) * 8, apar);
          const uint64_t da = dA + st * 256, db = mkdesc(ring.acquire(), 2048, 512, 2);
          wg_fence();
          mma_ss_224(acc, da, db, 1);
          mma_ss_224(acc, da + 128, db + 64, 1);
          wg_commit();
          if (st > 1) { wg_wait<2>(); ring.release(prev2, elect); }
          prev2 = prev; prev = ring.advance();
        }
        finish_stats();
        mbar_wait(barCS + 8, 0);
        wg_wait<0>(); reg_fence(acc);
        ring.release(prev2, elect); ring.release(prev, elect);
        STAMP(8 + layer * 12);
        const float2* bs = reinterpret_cast<const float2*>(sg + OFF_B1) + t;
        const float2* cs = reinterpret_cast<const float2*>(sg + OFF_CS + 768) + t;
        const float mr0 = -mean[0] * rstd[0], mr1 = -mean[1] * rstd[1];
#pragma unroll
        for (int j = 0; j < 28; j++) {
          const float2 b = bs[4 * j], s = cs[4 * j];
          hf[j][0] = relu_sq(fmaf(acc[4 * j], rstd[0], fmaf(s.x, mr0, b.x)), fmaf(acc[4 * j + 1], rstd[0], fmaf(s.y, mr0, b.y)));
          hf[j][1] = relu_sq(fmaf(acc[4 * j + 2], rstd[1], fmaf(s.x, mr1, b.x)), fmaf(acc[4 * j + 3], rstd[1], fmaf(s.y, mr1, b.y)));
        }
      }
      unsigned char* pdst = gP + (size_t)(((G * 2 + c) * 8 + 2 * w) * 8 + r) * 7168 + lane * 8;
      uint2 pk[8] = {};
#pragma unroll 1
      for (int ch = 0; ch < 7; ch++) {
        float acc[32], acc2[32]; reg_def(acc); reg_def(acc2);
        const uint64_t db0 = mkdesc(ring.acquire(), 4096, 1024, 1);
        const int sl0 = ring.advance();
        const uint64_t db1 = mkdesc(ring.acquire(), 4096, 1024, 1);
        const int sl1 = ring.advance();
        wg_fence();
#pragma unroll
        for (int s = 0; s < 7; s++) {
          mma_rs_64(acc, hf[2 * s][0], hf[2 * s][1], hf[2 * s + 1][0], hf[2 * s + 1][1], db0 + s * 128, s);
          mma_rs_64(acc2, hf[14 + 2 * s][0], hf[14 + 2 * s][1], hf[15 + 2 * s][0], hf[15 + 2 * s][1], db1 + s * 128, s);
        }
        wg_commit();
        if (ch > 0) {
#pragma unroll
          for (int i = 0; i < 8; i++) *reinterpret_cast<uint2*>(pdst + (i & 1) * (8 * 7168) + (i >> 1) * 256) = pk[i];
          pdst += 1024;
        }
        wg_wait<0>(); reg_fence(acc); reg_fence(acc2); ring.release(sl0, elect); ring.release(sl1, elect);
#pragma unroll
        for (int i = 0; i < 8; i++) {
          const int b = (i >> 1) * 8 + (i & 1) * 2;
          pk[i] = make_uint2((pack(acc[b] + acc2[b], acc[b + 1] + acc2[b + 1]) & ~1u) | (layer ^ 1), pack(acc[b + 4] + acc2[b + 4], acc[b + 5] + acc2[b + 5]));
        }
      }
#pragma unroll
      for (int i = 0; i < 8; i++) *reinterpret_cast<uint2*>(pdst + (i & 1) * (8 * 7168) + (i >> 1) * 256) = pk[i];
      STAMP(9 + layer * 12);
    }
    {
      uint32_t bx[14];
#pragma unroll
      for (int j = 0; j < 14; j++) bx[j] = __ldg(reinterpret_cast<const uint32_t*>(b2 + (j >> 1) * 64 + w * 16 + (j & 1) * 8 + 2 * t));
      const unsigned char* psrc = gP + (size_t)(((G * 2 + c) * 8 + r) * 8) * 7168 + w * 256 + lane * 8;
      unsigned char* img = gImg + (size_t)(64 + G * 2 + c) * ABYTES;
      uint2 pv[8][7] = {};
      uint32_t need = 0x7F;
#pragma unroll 1
      for (int n = 0; need && n < (1 << 16); n++) {
#pragma unroll
        for (int i = 0; i < 7; i++)
          if (need >> i & 1) {
#pragma unroll
            for (int s = 0; s < 8; s++) pv[s][i] = ldcg2(psrc + s * 7168 + i * 1024);
          }
        uint32_t bad = 0;
#pragma unroll
        for (int i = 0; i < 7; i++) {
          const uint32_t all = pv[0][i].x & pv[1][i].x & pv[2][i].x & pv[3][i].x & pv[4][i].x & pv[5][i].x & pv[6][i].x & pv[7][i].x;
          const uint32_t any = pv[0][i].x | pv[1][i].x | pv[2][i].x | pv[3][i].x | pv[4][i].x | pv[5][i].x | pv[6][i].x | pv[7][i].x;
          bad |= ((layer ? any : ~all) & 1u) << i;
        }
        need = __reduce_or_sync(~0u, bad);
      }
      STAMP(10 + layer * 12);
      const uint32_t off = w * 2048 + r * 128 + lane * 4;
      unsigned char* dst = layer ? reinterpret_cast<unsigned char*>(out + (size_t)(row0 + r * 8 + g) * DM + w * 16 + 2 * t) : img + off;
      float sm = 0.f, q = 0.f;
#pragma unroll
      for (int j = 0; j < 14; j++) {
        float y0 = lo(bx[j]), y1 = hi(bx[j]);
        const uint32_t xo = lds32(abuf + off + (j >> 1) * 8192 + (j & 1) * 1024);
        y0 += lo(xo); y1 += hi(xo);
#pragma unroll
        for (int s = 0; s < 8; s++) { const uint32_t u = (j & 1) ? pv[s][j >> 1].y : pv[s][j >> 1].x; y0 += lo(u); y1 += hi(u); }
        bx[j] = pack(y0, y1);
        *reinterpret_cast<uint32_t*>(dst + ((j >> 1) * 8 + (j & 1)) * (layer ? 16 : 1024)) = bx[j];
        sm += lo(bx[j]) + hi(bx[j]);
      }
      if (layer) break;
      sm += __shfl_xor_sync(~0u, sm, 1); sm += __shfl_xor_sync(~0u, sm, 2);
      sm *= 1.f / 112.f;
#pragma unroll
      for (int j = 0; j < 14; j++) { const float a = lo(bx[j]) - sm, b = hi(bx[j]) - sm; q = fmaf(a, a, q); q = fmaf(b, b, q); }
      q += __shfl_xor_sync(~0u, q, 1); q += __shfl_xor_sync(~0u, q, 2);
      if (t < 2) gStat[(size_t)(2048 + row0 + r * 8 + g) * 8 + 2 * w + t] = make_float2(sm, q * 0.5f);
      STAMP(11);
      gather(fl + 64, img);
      STAMP(12);
    }
  }
  STAMP(30);
  if (tid == 0) asm volatile("red.relaxed.gpu.global.add.u32 [%0], 1;" ::"l"(gFlag + FL_DONE * 32) : "memory");
  }
}

typedef CUresult (*EncFn)(CUtensorMap*, CUtensorMapDataType, cuuint32_t, void*, const cuuint64_t*, const cuuint64_t*,
                          const cuuint32_t*, const cuuint32_t*, CUtensorMapInterleave, CUtensorMapSwizzle,
                          CUtensorMapL2promotion, CUtensorMapFloatOOBfill);

void make_map(EncFn enc, CUtensorMap* m, void* p, int rank, uint64_t d0, uint64_t d1, uint64_t d2, uint64_t s1, uint64_t s2,
              uint32_t b0, uint32_t b1, uint32_t b2, CUtensorMapSwizzle sw) {
  cuuint64_t dims[3] = {d0, d1, d2}, strides[2] = {s1, s2};
  cuuint32_t box[3] = {b0, b1, b2}, es[3] = {1, 1, 1};
  enc(m, CU_TENSOR_MAP_DATA_TYPE_BFLOAT16, rank, p, dims, strides, box, es, CU_TENSOR_MAP_INTERLEAVE_NONE, sw,
      CU_TENSOR_MAP_L2_PROMOTION_L2_128B, CU_TENSOR_MAP_FLOAT_OOB_FILL_NONE);
}

}

extern "C" void kernel_launch(void* const* d_in, const int* in_sizes, int n_in, void* d_out, int out_size) {
  static EncFn enc = nullptr;
  if (!enc) {
    cudaDriverEntryPointQueryResult st;
    void* fn = nullptr;
    cudaGetDriverEntryPoint("cuTensorMapEncodeTiled", &fn, cudaEnableDefault, &st);
    enc = (EncFn)fn;
    cudaFuncSetAttribute(fused_kernel, cudaFuncAttributeMaxDynamicSharedMemorySize, SMEM_BYTES);
  }
  CUtensorMap mQKV, mWO, mW1, mW2, mX;
  make_map(enc, &mX, d_in[0], 2, 448, 2048, 1, 896, 0, 64, 64, 1, CU_TENSOR_MAP_SWIZZLE_128B);
  make_map(enc, &mQKV, d_in[1], 3, 448, 448, 3, 2688, 896, 64, 32, 3, CU_TENSOR_MAP_SWIZZLE_128B);
  make_map(enc, &mWO, d_in[3], 2, 448, 448, 1, 896, 0, 64, 112, 1, CU_TENSOR_MAP_SWIZZLE_128B);
  make_map(enc, &mW1, d_in[5], 3, 32, 448, 56, 3584, 64, 32, 32, 7, CU_TENSOR_MAP_SWIZZLE_64B);
  make_map(enc, &mW2, d_in[7], 2, 448, 1792, 1, 896, 0, 64, 112, 1, CU_TENSOR_MAP_SWIZZLE_128B);
  fused_kernel<<<NCTA, 384, SMEM_BYTES, cudaStreamPerThread>>>(
      mQKV, mWO, mW1, mW2, mX, (const __nv_bfloat16*)d_in[2], (const __nv_bfloat16*)d_in[6],
      (const __nv_bfloat16*)d_in[8], (const __nv_bfloat16*)d_in[1], (const __nv_bfloat16*)d_in[3], (const __nv_bfloat16*)d_in[5],
      (const __nv_bfloat16*)d_in[7], (__nv_bfloat16*)d_out);
}
```

```cpp
#include <cuda_runtime.h>
#include <cuda_bf16.h>
#include <cuda.h>
#include <stdint.h>

namespace {

constexpr int DM = 448, NCTA = 128;
constexpr int ABYTES = 57344;
constexpr int SLOT = 14336, NSLOT = 7;
constexpr int OFF_RING = 2 * ABYTES;
constexpr int OFF_WPHI = OFF_RING + NSLOT * SLOT;
constexpr int OFF_B1 = OFF_WPHI + 8192;
constexpr int OFF_CS = OFF_B1 + 896;
constexpr int OFF_BAR = OFF_CS + 1664;
constexpr int SMEM_BYTES = OFF_BAR + 272 + 1024;
constexpr int TILES_PER_LAYER = 46;

__device__ __align__(1024) unsigned char gP[16 * 2 * 8 * 8 * 7168];
__device__ __align__(1024) unsigned char gImg[3 * 32 * ABYTES];
__device__ __align__(1024) float2 gStat[2 * 2048 * 8];
__device__ __align__(1024) float4 gKV[2 * 8 * 2 * 5 * 128];
__device__ __align__(1024) float4 gCS[8 * 16 * 104];
__device__ __align__(128) unsigned gFlag[(2 * 32 * 7 + 32 + 1 + 16) * 32];
#define STAMP(i)

__device__ __forceinline__ uint32_t smem_u32(const void* p) { return (uint32_t)__cvta_generic_to_shared(p); }
__device__ __forceinline__ void mbar_init(uint32_t b, int c) { asm volatile("mbarrier.init.shared::cta.b64 [%0], %1;" ::"r"(b), "r"(c)); }
__device__ __forceinline__ void mbar_expect(uint32_t b, int bytes) { asm volatile("mbarrier.arrive.expect_tx.shared::cta.b64 _, [%0], %1;" ::"r"(b), "r"(bytes) : "memory"); }
__device__ __forceinline__ void mbar_arrive(uint32_t b) { asm volatile("mbarrier.arrive.shared::cta.b64 _, [%0];" ::"r"(b) : "memory"); }
__device__ __forceinline__ void mbar_wait(uint32_t b, int par) {
  uint32_t ok; int n = 0;
#pragma unroll 1
  while (true) {
    asm volatile("{.reg .pred p; mbarrier.try_wait.parity.shared::cta.b64 p, [%1], %2; selp.u32 %0,1,0,p;}" : "=r"(ok) : "r"(b), "r"(par) : "memory");
    if (ok) break;
    if (++n > (1 << 22)) break;
  }
}
__device__ __forceinline__ void flag_wait(const unsigned* f, unsigned target) {
  unsigned v; int n = 0;
#pragma unroll 1
  while (true) {
    asm volatile("ld.acquire.gpu.global.u32 %0, [%1];" : "=r"(v) : "l"(f) : "memory");
    if ((int)(v - target) >= 0) break;
    if (++n > (1 << 21)) break;
  }
}
__device__ __forceinline__ void flag_arrive(unsigned* f) { asm volatile("red.release.gpu.global.add.u32 [%0], 1;" ::"l"(f) : "memory"); }
__device__ __forceinline__ bool elect_one() {
  uint32_t p; asm volatile("{.reg .pred P; elect.sync _|P, 0xffffffff; selp.u32 %0, 1, 0, P;}" : "=r"(p)); return p;
}
__device__ __forceinline__ void fence_async() { asm volatile("fence.proxy.async.global;" ::: "memory"); }
__device__ __forceinline__ void fence_async_smem() { asm volatile("fence.proxy.async.shared::cta;" ::: "memory"); }
template <int ID, int N> __device__ __forceinline__ void bar_sync() { asm volatile("bar.sync %0, %1;" ::"n"(ID), "n"(N) : "memory"); }
__device__ __forceinline__ void bar_wg(int c) { if (c) bar_sync<2, 128>(); else bar_sync<1, 128>(); }
__device__ __forceinline__ void wg_fence() { asm volatile("wgmma.fence.sync.aligned;" ::: "memory"); }
__device__ __forceinline__ void wg_commit() { asm volatile("wgmma.commit_group.sync.aligned;" ::: "memory"); }
template <int N> __device__ __forceinline__ void wg_wait() { asm volatile("wgmma.wait_group.sync.aligned %0;" ::"n"(N) : "memory"); }
template <int N> __device__ __forceinline__ void reg_fence(float (&d)[N]) {
#pragma unroll
  for (int i = 0; i < N; i++) asm volatile("" : "+f"(d[i])::"memory");
}
template <int N> __device__ __forceinline__ void reg_def(float (&d)[N]) {
#pragma unroll
  for (int i = 0; i < N; i++) d[i] = 0.f;
}
__device__ __forceinline__ uint64_t mkdesc(uint32_t addr, uint32_t lbo, uint32_t sbo, uint64_t swz) {
  return (uint64_t)((addr & 0x3FFFF) >> 4) | ((uint64_t)(lbo >> 4) << 16) | ((uint64_t)(sbo >> 4) << 32) | (swz << 62);
}
__device__ __forceinline__ uint32_t pack(float a, float b) {
  uint32_t r; asm("cvt.rn.bf16x2.f32 %0, %1, %2;" : "=r"(r) : "f"(b), "f"(a)); return r;
}
__device__ __forceinline__ uint32_t relu_sq(float a, float b) {
  uint32_t r; asm("{.reg .b32 v; cvt.rn.relu.bf16x2.f32 v, %1, %2; mul.rn.bf16x2 %0, v, v;}" : "=r"(r) : "f"(b), "f"(a)); return r;
}
__device__ __forceinline__ float lo(uint32_t u) { return __uint_as_float(u << 16); }
__device__ __forceinline__ float hi(uint32_t u) { return __uint_as_float(u & 0xFFFF0000u); }
__device__ __forceinline__ float ex2(float x) { float y; asm("ex2.approx.ftz.f32 %0, %1;" : "=f"(y) : "f"(x)); return y; }
__device__ __forceinline__ void stsm4(uint32_t a, uint32_t r0, uint32_t r1, uint32_t r2, uint32_t r3) {
  asm volatile("stmatrix.sync.aligned.m8n8.x4.shared.b16 [%0], {%1,%2,%3,%4};" ::"r"(a), "r"(r0), "r"(r1), "r"(r2), "r"(r3) : "memory");
}
__device__ __forceinline__ void tma3(uint32_t dst, const CUtensorMap* m, int c0, int c1, int c2, uint32_t bar) {
  asm volatile("cp.async.bulk.tensor.3d.shared::cluster.global.mbarrier::complete_tx::bytes [%0], [%1, {%3,%4,%5}], [%2];"
               ::"r"(dst), "l"(m), "r"(bar), "r"(c0), "r"(c1), "r"(c2) : "memory");
}
__device__ __forceinline__ void tma2(uint32_t dst, const CUtensorMap* m, int c0, int c1, uint32_t bar) {
  asm volatile("cp.async.bulk.tensor.2d.shared::cluster.global.mbarrier::complete_tx::bytes [%0], [%1, {%3,%4}], [%2];"
               ::"r"(dst), "l"(m), "r"(bar), "r"(c0), "r"(c1) : "memory");
}
__device__ __forceinline__ uint32_t lds32(uint32_t a) { uint32_t v; asm volatile("ld.shared.u32 %0, [%1];" : "=r"(v) : "r"(a) : "memory"); return v; }
__device__ __forceinline__ void bulk_ld(uint32_t dst, const void* src, int bytes, uint32_t bar) {
  asm volatile("cp.async.bulk.shared::cluster.global.mbarrier::complete_tx::bytes [%0], [%1], %2, [%3];" ::"r"(dst), "l"(src), "r"(bytes), "r"(bar) : "memory");
}
__device__ __forceinline__ uint4 ldcg4(const void* p) {
  uint4 v; asm volatile("ld.global.cg.v4.u32 {%0,%1,%2,%3}, [%4];" : "=r"(v.x), "=r"(v.y), "=r"(v.z), "=r"(v.w) : "l"(p) : "memory"); return v;
}

__device__ __forceinline__ uint2 ldcg2(const void* p) {
  uint2 v; asm volatile("ld.global.cg.v2.u32 {%0,%1}, [%2];" : "=r"(v.x), "=r"(v.y) : "l"(p) : "memory"); return v;
}

__device__ __forceinline__ void mma_ss_184(float (&d)[92], uint64_t da, uint64_t db, int acc) {
  asm volatile("{.reg .pred p; setp.ne.b32 p, %94, 0;\n"
    "wgmma.mma_async.sync.aligned.m64n184k16.f32.bf16.bf16 {%0,%1,%2,%3,%4,%5,%6,%7,%8,%9,%10,%11,%12,%13,%14,%15,%16,%17,%18,%19,%20,%21,%22,%23,%24,%25,%26,%27,%28,%29,%30,%31,%32,%33,%34,%35,%36,%37,%38,%39,%40,%41,%42,%43,%44,%45,%46,%47,%48,%49,%50,%51,%52,%53,%54,%55,%56,%57,%58,%59,%60,%61,%62,%63,%64,%65,%66,%67,%68,%69,%70,%71,%72,%73,%74,%75,%76,%77,%78,%79,%80,%81,%82,%83,%84,%85,%86,%87,%88,%89,%90,%91}, %92, %93, p, 1, 1, 0, 1;}\n"
    : "+f"(d[0]),"+f"(d[1]),"+f"(d[2]),"+f"(d[3]),"+f"(d[4]),"+f"(d[5]),"+f"(d[6]),"+f"(d[7]),"+f"(d[8]),"+f"(d[9]),"+f"(d[10]),"+f"(d[11]),"+f"(d[12]),"+f"(d[13]),"+f"(d[14]),"+f"(d[15]),"+f"(d[16]),"+f"(d[17]),"+f"(d[18]),"+f"(d[19]),"+f"(d[20]),"+f"(d[21]),"+f"(d[22]),"+f"(d[23]),"+f"(d[24]),"+f"(d[25]),"+f"(d[26]),"+f"(d[27]),"+f"(d[28]),"+f"(d[29]),"+f"(d[30]),"+f"(d[31]),"+f"(d[32]),"+f"(d[33]),"+f"(d[34]),"+f"(d[35]),"+f"(d[36]),"+f"(d[37]),"+f"(d[38]),"+f"(d[39]),"+f"(d[40]),"+f"(d[41]),"+f"(d[42]),"+f"(d[43]),"+f"(d[44]),"+f"(d[45]),"+f"(d[46]),"+f"(d[47]),"+f"(d[48]),"+f"(d[49]),"+f"(d[50]),"+f"(d[51]),"+f"(d[52]),"+f"(d[53]),"+f"(d[54]),"+f"(d[55]),"+f"(d[56]),"+f"(d[57]),"+f"(d[58]),"+f"(d[59]),"+f"(d[60]),"+f"(d[61]),"+f"(d[62]),"+f"(d[63]),"+f"(d[64]),"+f"(d[65]),"+f"(d[66]),"+f"(d[67]),"+f"(d[68]),"+f"(d[69]),"+f"(d[70]),"+f"(d[71]),"+f"(d[72]),"+f"(d[73]),"+f"(d[74]),"+f"(d[75]),"+f"(d[76]),"+f"(d[77]),"+f"(d[78]),"+f"(d[79]),"+f"(d[80]),"+f"(d[81]),"+f"(d[82]),"+f"(d[83]),"+f"(d[84]),"+f"(d[85]),"+f"(d[86]),"+f"(d[87]),"+f"(d[88]),"+f"(d[89]),"+f"(d[90]),"+f"(d[91])
    : "l"(da), "l"(db), "r"(acc));
}
__device__ __forceinline__ void mma_ss_224(float (&d)[112], uint64_t da, uint64_t db, int acc) {
  asm volatile("{.reg .pred p; setp.ne.b32 p, %114, 0;\n"
    "wgmma.mma_async.sync.aligned.m64n224k16.f32.bf16.bf16 {%0,%1,%2,%3,%4,%5,%6,%7,%8,%9,%10,%11,%12,%13,%14,%15,%16,%17,%18,%19,%20,%21,%22,%23,%24,%25,%26,%27,%28,%29,%30,%31,%32,%33,%34,%35,%36,%37,%38,%39,%40,%41,%42,%43,%44,%45,%46,%47,%48,%49,%50,%51,%52,%53,%54,%55,%56,%57,%58,%59,%60,%61,%62,%63,%64,%65,%66,%67,%68,%69,%70,%71,%72,%73,%74,%75,%76,%77,%78,%79,%80,%81,%82,%83,%84,%85,%86,%87,%88,%89,%90,%91,%92,%93,%94,%95,%96,%97,%98,%99,%100,%101,%102,%103,%104,%105,%106,%107,%108,%109,%110,%111}, %112, %113, p, 1, 1, 0, 1;}\n"
    : "+f"(d[0]),"+f"(d[1]),"+f"(d[2]),"+f"(d[3]),"+f"(d[4]),"+f"(d[5]),"+f"(d[6]),"+f"(d[7]),"+f"(d[8]),"+f"(d[9]),"+f"(d[10]),"+f"(d[11]),"+f"(d[12]),"+f"(d[13]),"+f"(d[14]),"+f"(d[15]),"+f"(d[16]),"+f"(d[17]),"+f"(d[18]),"+f"(d[19]),"+f"(d[20]),"+f"(d[21]),"+f"(d[22]),"+f"(d[23]),"+f"(d[24]),"+f"(d[25]),"+f"(d[26]),"+f"(d[27]),"+f"(d[28]),"+f"(d[29]),"+f"(d[30]),"+f"(d[31]),"+f"(d[32]),"+f"(d[33]),"+f"(d[34]),"+f"(d[35]),"+f"(d[36]),"+f"(d[37]),"+f"(d[38]),"+f"(d[39]),"+f"(d[40]),"+f"(d[41]),"+f"(d[42]),"+f"(d[43]),"+f"(d[44]),"+f"(d[45]),"+f"(d[46]),"+f"(d[47]),"+f"(d[48]),"+f"(d[49]),"+f"(d[50]),"+f"(d[51]),"+f"(d[52]),"+f"(d[53]),"+f"(d[54]),"+f"(d[55]),"+f"(d[56]),"+f"(d[57]),"+f"(d[58]),"+f"(d[59]),"+f"(d[60]),"+f"(d[61]),"+f"(d[62]),"+f"(d[63]),"+f"(d[64]),"+f"(d[65]),"+f"(d[66]),"+f"(d[67]),"+f"(d[68]),"+f"(d[69]),"+f"(d[70]),"+f"(d[71]),"+f"(d[72]),"+f"(d[73]),"+f"(d[74]),"+f"(d[75]),"+f"(d[76]),"+f"(d[77]),"+f"(d[78]),"+f"(d[79]),"+f"(d[80]),"+f"(d[81]),"+f"(d[82]),"+f"(d[83]),"+f"(d[84]),"+f"(d[85]),"+f"(d[86]),"+f"(d[87]),"+f"(d[88]),"+f"(d[89]),"+f"(d[90]),"+f"(d[91]),"+f"(d[92]),"+f"(d[93]),"+f"(d[94]),"+f"(d[95]),"+f"(d[96]),"+f"(d[97]),"+f"(d[98]),"+f"(d[99]),"+f"(d[100]),"+f"(d[101]),"+f"(d[102]),"+f"(d[103]),"+f"(d[104]),"+f"(d[105]),"+f"(d[106]),"+f"(d[107]),"+f"(d[108]),"+f"(d[109]),"+f"(d[110]),"+f"(d[111])
    : "l"(da), "l"(db), "r"(acc));
}
__device__ __forceinline__ void mma_ss_56(float (&d)[28], uint64_t da, uint64_t db, int acc) {
  asm volatile("{.reg .pred p; setp.ne.b32 p, %30, 0;\n"
    "wgmma.mma_async.sync.aligned.m64n56k16.f32.bf16.bf16 {%0,%1,%2,%3,%4,%5,%6,%7,%8,%9,%10,%11,%12,%13,%14,%15,%16,%17,%18,%19,%20,%21,%22,%23,%24,%25,%26,%27}, %28, %29, p, 1, 1, 0, 1;}\n"
    : "+f"(d[0]),"+f"(d[1]),"+f"(d[2]),"+f"(d[3]),"+f"(d[4]),"+f"(d[5]),"+f"(d[6]),"+f"(d[7]),"+f"(d[8]),"+f"(d[9]),"+f"(d[10]),"+f"(d[11]),"+f"(d[12]),"+f"(d[13]),"+f"(d[14]),"+f"(d[15]),"+f"(d[16]),"+f"(d[17]),"+f"(d[18]),"+f"(d[19]),"+f"(d[20]),"+f"(d[21]),"+f"(d[22]),"+f"(d[23]),"+f"(d[24]),"+f"(d[25]),"+f"(d[26]),"+f"(d[27])
    : "l"(da), "l"(db), "r"(acc));
}
__device__ __forceinline__ void mma_rs_56(float (&d)[28], uint32_t a0, uint32_t a1, uint32_t a2, uint32_t a3, uint64_t db, int acc) {
  asm volatile("{.reg .pred p; setp.ne.b32 p, %33, 0;\n"
    "wgmma.mma_async.sync.aligned.m64n56k16.f32.bf16.bf16 {%0,%1,%2,%3,%4,%5,%6,%7,%8,%9,%10,%11,%12,%13,%14,%15,%16,%17,%18,%19,%20,%21,%22,%23,%24,%25,%26,%27}, {%28,%29,%30,%31}, %32, p, 1, 1, 1;}\n"
    : "+f"(d[0]),"+f"(d[1]),"+f"(d[2]),"+f"(d[3]),"+f"(d[4]),"+f"(d[5]),"+f"(d[6]),"+f"(d[7]),"+f"(d[8]),"+f"(d[9]),"+f"(d[10]),"+f"(d[11]),"+f"(d[12]),"+f"(d[13]),"+f"(d[14]),"+f"(d[15]),"+f"(d[16]),"+f"(d[17]),"+f"(d[18]),"+f"(d[19]),"+f"(d[20]),"+f"(d[21]),"+f"(d[22]),"+f"(d[23]),"+f"(d[24]),"+f"(d[25]),"+f"(d[26]),"+f"(d[27])
    : "r"(a0), "r"(a1), "r"(a2), "r"(a3), "l"(db), "r"(acc));
}
__device__ __forceinline__ void mma_ss_64t(float (&d)[32], uint64_t da, uint64_t db, int acc) {
  asm volatile("{.reg .pred p; setp.ne.b32 p, %34, 0;\n"
    "wgmma.mma_async.sync.aligned.m64n64k16.f32.bf16.bf16 {%0,%1,%2,%3,%4,%5,%6,%7,%8,%9,%10,%11,%12,%13,%14,%15,%16,%17,%18,%19,%20,%21,%22,%23,%24,%25,%26,%27,%28,%29,%30,%31}, %32, %33, p, 1, 1, 1, 1;}\n"
    : "+f"(d[0]),"+f"(d[1]),"+f"(d[2]),"+f"(d[3]),"+f"(d[4]),"+f"(d[5]),"+f"(d[6]),"+f"(d[7]),"+f"(d[8]),"+f"(d[9]),"+f"(d[10]),"+f"(d[11]),"+f"(d[12]),"+f"(d[13]),"+f"(d[14]),"+f"(d[15]),"+f"(d[16]),"+f"(d[17]),"+f"(d[18]),"+f"(d[19]),"+f"(d[20]),"+f"(d[21]),"+f"(d[22]),"+f"(d[23]),"+f"(d[24]),"+f"(d[25]),"+f"(d[26]),"+f"(d[27]),"+f"(d[28]),"+f"(d[29]),"+f"(d[30]),"+f"(d[31])
    : "l"(da), "l"(db), "r"(acc));
}
__device__ __forceinline__ void mma_rs_64(float (&d)[32], uint32_t a0, uint32_t a1, uint32_t a2, uint32_t a3, uint64_t db, int acc) {
  asm volatile("{.reg .pred p; setp.ne.b32 p, %37, 0;\n"
    "wgmma.mma_async.sync.aligned.m64n64k16.f32.bf16.bf16 {%0,%1,%2,%3,%4,%5,%6,%7,%8,%9,%10,%11,%12,%13,%14,%15,%16,%17,%18,%19,%20,%21,%22,%23,%24,%25,%26,%27,%28,%29,%30,%31}, {%32,%33,%34,%35}, %36, p, 1, 1, 1;}\n"
    : "+f"(d[0]),"+f"(d[1]),"+f"(d[2]),"+f"(d[3]),"+f"(d[4]),"+f"(d[5]),"+f"(d[6]),"+f"(d[7]),"+f"(d[8]),"+f"(d[9]),"+f"(d[10]),"+f"(d[11]),"+f"(d[12]),"+f"(d[13]),"+f"(d[14]),"+f"(d[15]),"+f"(d[16]),"+f"(d[17]),"+f"(d[18]),"+f"(d[19]),"+f"(d[20]),"+f"(d[21]),"+f"(d[22]),"+f"(d[23]),"+f"(d[24]),"+f"(d[25]),"+f"(d[26]),"+f"(d[27]),"+f"(d[28]),"+f"(d[29]),"+f"(d[30]),"+f"(d[31])
    : "r"(a0), "r"(a1), "r"(a2), "r"(a3), "l"(db), "r"(acc));
}

__device__ __forceinline__ void dual_softmax(const float (&p)[28], uint32_t (&phi)[4][7]) {
  constexpr float L2E = 1.4426950408889634f;
#pragma unroll
  for (int i = 0; i < 4; i++) {
    float mx = p[i], mn = p[i];
#pragma unroll
    for (int j = 1; j < 7; j++) { mx = fmaxf(mx, p[4 * j + i]); mn = fminf(mn, p[4 * j + i]); }
    mx = fmaxf(mx, __shfl_xor_sync(~0u, mx, 1)); mn = fminf(mn, __shfl_xor_sync(~0u, mn, 1));
    mx = fmaxf(mx, __shfl_xor_sync(~0u, mx, 2)); mn = fminf(mn, __shfl_xor_sync(~0u, mn, 2));
    float a[7], b[7], sa = 0.f, sb = 0.f;
    const float mxl = mx * L2E, mnl = mn * L2E;
#pragma unroll
    for (int j = 0; j < 7; j++) {
      a[j] = ex2(fmaf(p[4 * j + i], L2E, -mxl)); b[j] = ex2(fmaf(p[4 * j + i], -L2E, mnl));
      sa += a[j]; sb += b[j];
    }
    sa += __shfl_xor_sync(~0u, sa, 1); sb += __shfl_xor_sync(~0u, sb, 1);
    sa += __shfl_xor_sync(~0u, sa, 2); sb += __shfl_xor_sync(~0u, sb, 2);
    const float ra = __fdividef(1.f, sa), rb = __fdividef(1.f, sb);
#pragma unroll
    for (int j = 0; j < 7; j++) phi[i][j] = pack(a[j] * ra, b[j] * rb);
  }
}

struct Ring {
  uint32_t full, empty, base; int slot, par;
  __device__ __forceinline__ void uniform() { slot = __shfl_sync(~0u, slot, 0); par = __shfl_sync(~0u, par, 0); }
  __device__ __forceinline__ uint32_t acquire() { mbar_wait(full + slot * 8, par); return base + slot * SLOT; }
  __device__ __forceinline__ int advance() { int s = slot; if (++slot == NSLOT) { slot = 0; par ^= 1; } return s; }
  __device__ __forceinline__ void release(int s, bool elect) { if (elect) mbar_arrive(empty + s * 8); }
};
constexpr int UNR = 14;
constexpr int FL_KV = 448, FL_CS = FL_KV + 16, FL_DONE = FL_KV + 32;

__global__ void __launch_bounds__(384, 1)
fused_kernel(const __grid_constant__ CUtensorMap mQKV, const __grid_constant__ CUtensorMap mWO,
             const __grid_constant__ CUtensorMap mW1, const __grid_constant__ CUtensorMap mW2,
             const __grid_constant__ CUtensorMap mX, const __nv_bfloat16* __restrict__ wphi,
             const __nv_bfloat16* __restrict__ b1, const __nv_bfloat16* __restrict__ b2,
             const __nv_bfloat16* __restrict__ wqkv, const __nv_bfloat16* __restrict__ wo, const __nv_bfloat16* __restrict__ w1,
             const __nv_bfloat16* __restrict__ w2, __nv_bfloat16* __restrict__ out) {
  extern __shared__ unsigned char smem_raw[];
  const uint32_t sb = (smem_u32(smem_raw) + 1023) & ~1023u;
  unsigned char* sg = smem_raw + (sb - smem_u32(smem_raw));
  const int tid = threadIdx.x, lane = tid & 31;
  const int G = blockIdx.x >> 3, r = blockIdx.x & 7;
  const uint32_t barFull = sb + OFF_BAR, barEmpty = barFull + 56, barA = barEmpty + 56, barCS = barA + 112, barX = barCS + 16;
  const int warp = __shfl_sync(~0u, tid >> 5, 0);
  uint32_t wv[7], bv;
#pragma unroll
  for (int i = 0; i < 7; i++)
    wv[i] = __ldg(reinterpret_cast<const unsigned short*>(wphi) + (56 * r + i * 8 + (warp & 7)) * 28 + min(lane, 27));
  bv = __ldg(reinterpret_cast<const unsigned short*>(b1) + 224 * r + min(tid, 223));
  if (lane == 0) {
    if (warp >= 10) {
      const int cc = warp - 10;
      mbar_init(barX + cc * 8, 1);
      fence_async_smem();
      mbar_expect(barX + cc * 8, ABYTES);
#pragma unroll 1
      for (int k = 0; k < 7; k++) tma2(sb + cc * ABYTES + k * 8192, &mX, 64 * k, G * 128 + 64 * cc, barX + cc * 8);
    } else if (warp < 7) { mbar_init(barFull + warp * 8, 1); mbar_init(barEmpty + warp * 8, 2); mbar_init(barA + warp * 8, 1); mbar_init(barA + 56 + warp * 8, 1); }
    else if (warp < 9) mbar_init(barCS + (warp - 7) * 8, 96);
    else
      asm volatile("cp.async.bulk.prefetch.L2.global [%0], %1;" ::"l"((const char*)wqkv + blockIdx.x * 9408), "r"(9408) : "memory");
    asm volatile("fence.mbarrier_init.release.cluster;" ::: "memory");
  }
  if (tid < 192) reinterpret_cast<float*>(sg + OFF_CS)[tid] = 0.f;
  __syncthreads();
  const int wgid = warp >> 2;
  if (wgid == 2) {
    asm volatile("setmaxnreg.dec.sync.aligned.u32 40;");
    if (warp == 8) {
      int slot = 0, par = 1;
#pragma unroll 1
      for (int it = 0; it < 2 * TILES_PER_LAYER; it++) {
        const int i = it >= TILES_PER_LAYER ? it - TILES_PER_LAYER : it;
        mbar_wait(barEmpty + slot * 8, par);
        const uint32_t dst = sb + OFF_RING + slot * SLOT, fb = barFull + slot * 8;
        if (elect_one()) {
          mbar_expect(fb, i < 14 ? 12288 : SLOT);
          if (i < 14) tma3(dst, &mQKV, 56 * r, 32 * i, 0, fb);
          else if (i < 18) tma2(dst, &mWO, 56 * r, 112 * (i - 14), fb);
          else if (i < 32) tma3(dst, &mW1, 0, 32 * (i - 18), 7 * r, fb);
          else tma2(dst, &mW2, 64 * ((i - 32) >> 1), 224 * r + 112 * (i & 1), fb);
        }
        if (++slot == NSLOT) { slot = 0; par ^= 1; }
      }
    } else {
      unsigned ep;
      asm volatile("ld.relaxed.gpu.global.u32 %0, [%1];" : "=r"(ep) : "l"(gFlag + FL_DONE * 32) : "memory");
      const int idx = tid - 288;
      ep = (ep / NCTA + 1) * 3;
      if (G == 0) {
#pragma unroll 1
        for (int i = idx; i < 2 * 1280; i += 96) gKV[((i >= 1280) * 7 + r) * 1280 + i] = make_float4(0.f, 0.f, 0.f, 0.f);
        __syncwarp();
        if (lane == 0) flag_arrive(gFlag + (FL_CS + r) * 32);
      }
      mbar_wait(barFull + 48, 0); mbar_wait(barFull + 48, 1);
      if (idx < 2) {
        const char* pf = idx ? (const char*)w2 + blockIdx.x * 12544 : (const char*)wo + blockIdx.x * 3136;
        asm volatile("cp.async.bulk.prefetch.L2.global [%0], %1;" ::"l"(pf), "r"(idx ? 12544 : 3136) : "memory");
      }
      if (lane == 0) flag_wait(gFlag + (FL_CS + r) * 32, ep);
      __syncwarp();
      mbar_arrive(barCS);
#pragma unroll 1
      for (int ps = 0; ps < 3; ps++) {
        const int nch = ps ? 14 : 21, ch = min(idx >> 2, nch - 1), p = ch / 7, k0 = G * 28 + (idx & 3) * 7;
        const uint4* src = ps ? reinterpret_cast<const uint4*>(w1 + (size_t)k0 * 1792 + 224 * r) + (ps - 1) * 14 + ch
                              : reinterpret_cast<const uint4*>(wqkv + (size_t)k0 * 1344 + p * 448 + 56 * r) + (ch - 7 * p);
        uint4 cu[7];
#pragma unroll
        for (int i = 0; i < 7; i++) cu[i] = __ldg(src + i * (ps ? 224 : 168));
        float s[8] = {};
#pragma unroll
        for (int i = 0; i < 7; i++) { s[0] += lo(cu[i].x); s[1] += hi(cu[i].x); s[2] += lo(cu[i].y); s[3] += hi(cu[i].y); s[4] += lo(cu[i].z); s[5] += hi(cu[i].z); s[6] += lo(cu[i].w); s[7] += hi(cu[i].w); }
#pragma unroll
        for (int i = 0; i < 8; i++) { s[i] += __shfl_xor_sync(~0u, s[i], 1); s[i] += __shfl_xor_sync(~0u, s[i], 2); }
        if ((idx & 3) < 2 && idx < nch * 4) gCS[(r * 16 + G) * 104 + (ps ? 10 + ps * 14 + ch : ch + p) * 2 + (idx & 1)] = (idx & 1) ? make_float4(s[4], s[5], s[6], s[7]) : make_float4(s[0], s[1], s[2], s[3]);
      }
      __syncwarp();
      if (lane == 0) { flag_arrive(gFlag + (FL_CS + 8 + r) * 32); flag_wait(gFlag + (FL_CS + 8 + r) * 32, ep * 16); }
      __syncwarp();
#pragma unroll 1
      for (int j = idx; j < 208; j += 96) {
        float2 a = make_float2(0.f, 0.f);
#pragma unroll 8
        for (int i = 0; i < 16; i++) { const float2 v = __ldcg(reinterpret_cast<const float2*>(gCS + (r * 16 + i) * 104) + j); a.x += v.x; a.y += v.y; }
        reinterpret_cast<float2*>(sg + OFF_CS)[j] = a;
      }
      mbar_arrive(barCS + 8);
    }
  } else {
  asm volatile("setmaxnreg.inc.sync.aligned.u32 232;");
  const int c = wgid, w = warp & 3, g = lane >> 2, t = lane & 3;
  int elect_i = (tid & 127) == 0;
  asm volatile("" : "+r"(elect_i));
  const bool elect = elect_i;
  const uint32_t abuf = sb + c * ABYTES, barAc = barA + c * 56;
  const int row0 = G * 128 + c * 64;
  unsigned epoch;
  asm volatile("ld.relaxed.gpu.global.u32 %0, [%1];" : "=r"(epoch) : "l"(gFlag + FL_DONE * 32) : "memory");
  STAMP(24);
  float mean[2], rstd[2];
  uint4 su[2] = {};
  uint32_t xs[7][2];
  {
#pragma unroll
    for (int i = 0; i < 8; i++) {
      const int k = i * 8 + (tid >> 5);
      *reinterpret_cast<uint32_t*>(sg + OFF_WPHI + k * 128 + ((g ^ (k & 7)) << 4) + t * 4) = (i < 7 && lane < 28) ? wv[i % 7] << (k >= 28 ? 16 : 0) : 0u;
    }
    if (tid < 224) reinterpret_cast<uint32_t*>(sg + OFF_B1)[tid] = bv << 16;
    mbar_wait(barX + c * 8, 0);
    STAMP(25);
#pragma unroll
    for (int j = 0; j < 7; j++) {
      const int ci = 7 * r + j;
      const uint32_t a = abuf + (ci >> 3) * 8192 + (w * 16 + g) * 128 + (((ci & 7) ^ g) << 4) + t * 4;
      xs[j][0] = lds32(a); xs[j][1] = lds32(a + 1024);
    }
    __syncwarp();
#pragma unroll 1
    for (int hh = 0; hh < 2; hh++) {
      uint4* p = reinterpret_cast<uint4*>(sg + c * ABYTES + (w * 16 + hh * 8 + g) * 128) + t;
      uint4 v[14];
#pragma unroll
      for (int k = 0; k < 14; k++) v[k] = p[(k >> 1) * 512 + ((k ^ g) & 1) * 4];
      float a8[8] = {};
#pragma unroll
      for (int k = 0; k < 14; k++) {
        const uint32_t e[4] = {v[k].x, v[k].y, v[k].z, v[k].w};
#pragma unroll
        for (int z = 0; z < 4; z++) { a8[2 * z] += lo(e[z]); a8[2 * z + 1] += hi(e[z]); }
      }
      float sm = ((a8[0] + a8[1]) + (a8[2] + a8[3])) + ((a8[4] + a8[5]) + (a8[6] + a8[7]));
      sm += __shfl_xor_sync(~0u, sm, 1); sm += __shfl_xor_sync(~0u, sm, 2);
      sm *= 1.f / DM;
#pragma unroll
      for (int k = 0; k < 14; k++) {
        const uint32_t e[4] = {v[k].x, v[k].y, v[k].z, v[k].w};
#pragma unroll
        for (int z = 0; z < 4; z++) {
          const float a = lo(e[z]) - sm, b = hi(e[z]) - sm;
          a8[2 * z] = fmaf(a, a, k ? a8[2 * z] : 0.f); a8[2 * z + 1] = fmaf(b, b, k ? a8[2 * z + 1] : 0.f);
        }
      }
      float q = ((a8[0] + a8[1]) + (a8[2] + a8[3])) + ((a8[4] + a8[5]) + (a8[6] + a8[7]));
      q += __shfl_xor_sync(~0u, q, 1); q += __shfl_xor_sync(~0u, q, 2);
      q = rsqrtf(q * (1.f / DM) + 1e-5f);
      sm *= -q;
#pragma unroll
      for (int k = 0; k < 14; k++)
        p[(k >> 1) * 512 + ((k ^ g) & 1) * 4] = make_uint4(pack(fmaf(lo(v[k].x), q, sm), fmaf(hi(v[k].x), q, sm)), pack(fmaf(lo(v[k].y), q, sm), fmaf(hi(v[k].y), q, sm)),
                                                           pack(fmaf(lo(v[k].z), q, sm), fmaf(hi(v[k].z), q, sm)), pack(fmaf(lo(v[k].w), q, sm), fmaf(hi(v[k].w), q, sm)));
    }
    fence_async_smem();
    bar_sync<3, 256>();
    epoch = epoch / NCTA + 1;
    mean[0] = mean[1] = 0.f; rstd[0] = rstd[1] = 1.f;
  }
  STAMP(0);
  Ring ring{barFull, barEmpty, sb + OFF_RING, 0, 0};
  int apar = 1;
  const uint32_t stsm_off = (w * 16 + ((lane >> 3) & 1) * 8 + (lane & 7)) * 128;
  const uint32_t stsm_hi = lane >> 4;
  const uint64_t dA = mkdesc(abuf, 1024, 128, 0);

  auto gather = [&](unsigned* fl, const unsigned char* img) {
    __syncwarp();
    if (lane == 0) {
      flag_arrive(fl);
      STAMP(27);
      flag_wait(fl, epoch * 32);
      STAMP(28);
      fence_async();
      mbar_expect(barAc + w * 8, 8192); bulk_ld(abuf + w * 8192, img + w * 8192, 8192, barAc + w * 8);
      if (w < 3) { mbar_expect(barAc + 32 + w * 8, 8192); bulk_ld(abuf + 32768 + w * 8192, img + 32768 + w * 8192, 8192, barAc + 32 + w * 8); }
    }
    __syncwarp();
    apar ^= 1;
  };
  auto slice_off = [&](int j, int hh) -> uint32_t {
    return (7 * r + j) * 1024 + (w * 2 + hh) * 128 + lane * 4;
  };
  auto load_stats = [&](const float2* st) {
    mbar_wait(barAc, apar);
#pragma unroll
    for (int hh = 0; hh < 2; hh++) su[hh] = ldcg4(st + (size_t)(row0 + w * 16 + hh * 8 + g) * 8 + 2 * t);
  };
  auto finish_stats = [&]() {
#pragma unroll
    for (int hh = 0; hh < 2; hh++) {
      const float m0 = __uint_as_float(su[hh].x), m1 = __uint_as_float(su[hh].z);
      float m = m0 + m1;
      m += __shfl_xor_sync(~0u, m, 1); m += __shfl_xor_sync(~0u, m, 2);
      m *= 0.125f;
      float q = __uint_as_float(su[hh].y) + __uint_as_float(su[hh].w) + 56.f * ((m0 - m) * (m0 - m) + (m1 - m) * (m1 - m));
      q += __shfl_xor_sync(~0u, q, 1); q += __shfl_xor_sync(~0u, q, 2);
      mean[hh] = m; rstd[hh] = rsqrtf(q * (1.f / DM) + 1e-5f);
    }
  };

#pragma unroll 1
  for (int lyr = 0; lyr < 2; lyr++) {
    const int layer = __shfl_sync(~0u, lyr, 0);
    unsigned* const fl = gFlag + (layer * 32 + G * 2 + c) * 7 * 32;
    uint32_t phiq[4][7];
    {
      float acc[92]; reg_def(acc);
      int prev = 0, prev2 = 0;
      ring.uniform();
      const uint64_t dQ = layer ? dA : mkdesc(abuf, 16, 1024, 1);
      const int kstep = layer ? 128 : 2;
      if (layer) load_stats(gStat + 2048 * 8);
#pragma unroll UNR
      for (int st = 0; st < 14; st++) {
        if (!(st & 1) && layer) mbar_wait(barAc + (st >> 1) * 8, apar);
        const uint64_t da = dQ + (st >> 1) * 512 + (st & 1) * 2 * kstep, db = mkdesc(ring.acquire(), 4096, 1024, 1);
        wg_fence();
        mma_ss_184(acc, da, db, 1);
        mma_ss_184(acc, da + kstep, db + 128, 1);
        wg_commit();
        if (st > 1) { wg_wait<2>(); ring.release(prev2, elect); }
        prev2 = prev; prev = ring.advance();
      }
      if (layer) {
        finish_stats();
#pragma unroll
        for (int j = 0; j < 7; j++) { xs[j][0] = lds32(abuf + slice_off(j, 0)); xs[j][1] = lds32(abuf + slice_off(j, 1)); }
      }
      wg_wait<0>(); reg_fence(acc);
      ring.release(prev2, elect); ring.release(prev, elect);
      STAMP(1 + layer * 12);
      uint32_t f[3][14];
      {
        const float2* cs = reinterpret_cast<const float2*>(sg + OFF_CS) + t;
        const float mr0 = -mean[0] * rstd[0], mr1 = -mean[1] * rstd[1];
#pragma unroll
        for (int p = 0; p < 3; p++)
#pragma unroll
          for (int j = 0; j < 7; j++) {
            const float2 s = cs[p * 32 + j * 4];
            const int b = p * 32 + j * 4;
            f[p][2 * j] = pack(fmaf(acc[b], rstd[0], s.x * mr0), fmaf(acc[b + 1], rstd[0], s.y * mr0));
            f[p][2 * j + 1] = pack(fmaf(acc[b + 2], rstd[1], s.x * mr1), fmaf(acc[b + 3], rstd[1], s.y * mr1));
          }
      }
      float pk[28], pq[28]; reg_def(pk); reg_def(pq);
      const uint64_t dW = mkdesc(sb + OFF_WPHI, 4096, 1024, 1);
      wg_fence();
#pragma unroll
      for (int s = 0; s < 4; s++) {
        mma_rs_56(pk, f[1][4 * s], f[1][4 * s + 1], s < 3 ? f[1][(4 * s + 2) % 14] : 0u, s < 3 ? f[1][(4 * s + 3) % 14] : 0u, dW + s * 128, s);
        mma_rs_56(pq, f[0][4 * s], f[0][4 * s + 1], s < 3 ? f[0][(4 * s + 2) % 14] : 0u, s < 3 ? f[0][(4 * s + 3) % 14] : 0u, dW + s * 128, s);
      }
      wg_commit();
      bar_wg(c);
      const uint32_t srow = abuf + stsm_off, ones = t == 0 ? 0x3F803F80u : 0u;
#pragma unroll
      for (int jp = 0; jp < 4; jp++)
        stsm4(srow + 16384 + (((2 * jp + stsm_hi) ^ (lane & 7)) << 4), f[2][4 * jp], f[2][4 * jp + 1],
              jp < 3 ? f[2][(4 * jp + 2) % 14] : ones, jp < 3 ? f[2][(4 * jp + 3) % 14] : ones);
      wg_wait<0>(); reg_fence(pk); reg_fence(pq);
#pragma unroll 1
      for (int pass = 0; pass < 2; pass++) {
        dual_softmax(pk, phiq);
        if (pass) break;
#pragma unroll
        for (int e = 0; e < 2; e++)
#pragma unroll
          for (int jp = 0; jp < 4; jp++)
            stsm4(srow + e * 8192 + (((2 * jp + stsm_hi) ^ (lane & 7)) << 4), phiq[e][2 * jp], phiq[2 + e][2 * jp],
                  jp < 3 ? phiq[e][(2 * jp + 1) % 7] : 0u, jp < 3 ? phiq[2 + e][(2 * jp + 1) % 7] : 0u);
        fence_async_smem();
        bar_sync<3, 256>();
        float kv[32], kw[32]; reg_def(kv); reg_def(kw);
        const uint64_t dP = mkdesc(sb + c * 8192, 4096, 1024, 1), dV = mkdesc(sb + 16384, 4096, 1024, 1);
        wg_fence();
#pragma unroll
        for (int s = 0; s < 4; s++) { mma_ss_64t(kv, dP + s * 128, dV + s * 128, s); mma_ss_64t(kw, dP + ABYTES / 16 + s * 128, dV + ABYTES / 16 + s * 128, s); }
        wg_commit();
        mbar_wait(barCS, 0);
        wg_wait<0>(); reg_fence(kv); reg_fence(kw);
#pragma unroll
        for (int i = 0; i < 32; i++) kv[i] += kw[i];
        float4* kvg = gKV + ((layer * 8 + r) * 2 + c) * 640 + (tid & 127);
#pragma unroll
        for (int i = 0; i < 5; i++) {
          float v0, v1, v2, v3;
          if (i == 4) { v0 = kv[28]; v1 = kv[29]; v2 = kv[30]; v3 = kv[31]; }
          else { v0 = c ? kv[12 + 4 * i] : kv[4 * i]; v1 = c ? kv[13 + 4 * i] : kv[1 + 4 * i]; v2 = c ? kv[14 + 4 * i] : kv[2 + 4 * i]; v3 = c ? kv[15 + 4 * i] : kv[3 + 4 * i]; }
          const bool use = i == 4 ? t == 0 : (i == 0 ? (c == 0 || t >= 2) : (i == 3 ? (c == 1 || t < 2) : true));
          if (use) asm volatile("red.relaxed.gpu.global.add.v4.f32 [%0], {%1,%2,%3,%4};" ::"l"(kvg + i * 128), "f"(v0), "f"(v1), "f"(v2), "f"(v3) : "memory");
        }
        __syncwarp();
        if (lane == 0) flag_arrive(gFlag + (FL_KV + layer * 8 + r) * 32);
        __syncwarp();
        STAMP(2 + layer * 12);
#pragma unroll
        for (int i = 0; i < 28; i++) pk[i] = pq[i];
      }
    }
    {
      if (elect) flag_wait(gFlag + (FL_KV + layer * 8 + r) * 32, epoch * 128);
      bar_wg(c);
      STAMP(3 + layer * 12);
      const float4* kvg = gKV + (layer * 8 + r) * 1280 + (tid & 127);
      uint4 kk[2][5];
#pragma unroll
      for (int e = 0; e < 2; e++)
#pragma unroll
        for (int i = 0; i < 5; i++) kk[e][i] = ldcg4(kvg + e * 640 + i * 128);
      const uint32_t srow = abuf + 24576 + stsm_off;
#pragma unroll
      for (int e = 0; e < 2; e++) {
        uint32_t f[8][2];
#pragma unroll
        for (int j = 0; j < 8; j++) { f[j][0] = 0u; f[j][1] = 0u; }
#pragma unroll
        for (int i = 0; i < 4; i++) {
          f[i + 3 * e][0] = pack(__uint_as_float(kk[e][i].x), __uint_as_float(kk[e][i].y));
          f[i + 3 * e][1] = pack(__uint_as_float(kk[e][i].z), __uint_as_float(kk[e][i].w));
        }
        f[7][0] = e ? pack(0.f, __uint_as_float(kk[e][4].y)) : pack(__uint_as_float(kk[e][4].x), 0.f);
        f[7][1] = e ? pack(0.f, __uint_as_float(kk[e][4].w)) : pack(__uint_as_float(kk[e][4].z), 0.f);
#pragma unroll
        for (int jp = 0; jp < 4; jp++)
          stsm4(srow + e * 8192 + (((2 * jp + stsm_hi) ^ (lane & 7)) << 4), f[2 * jp][0], f[2 * jp][1], f[2 * jp + 1][0], f[2 * jp + 1][1]);
      }
      fence_async_smem();
      bar_wg(c);
      float num[32], nub[32]; reg_def(num); reg_def(nub);
      const uint64_t dK = mkdesc(abuf + 24576, 4096, 1024, 1);
      wg_fence();
#pragma unroll
      for (int s = 0; s < 4; s++) {
        mma_rs_64(num, phiq[0][2 * s], phiq[2][2 * s], s < 3 ? phiq[0][(2 * s + 1) % 7] : 0u, s < 3 ? phiq[2][(2 * s + 1) % 7] : 0u, dK + s * 128, s);
        mma_rs_64(nub, phiq[1][2 * s], phiq[3][2 * s], s < 3 ? phiq[1][(2 * s + 1) % 7] : 0u, s < 3 ? phiq[3][(2 * s + 1) % 7] : 0u, dK + 512 + s * 128, s);
      }
      wg_commit();
      wg_wait<0>(); reg_fence(num); reg_fence(nub);
#pragma unroll
      for (int i = 12; i < 32; i++) num[i] += nub[i];
      float rd[4];
#pragma unroll
      for (int i = 0; i < 4; i++) rd[i] = __fdividef(1.f, __shfl_sync(~0u, num[28 + i], lane & ~3) + 1e-6f);
      unsigned char* img = gImg + (size_t)(G * 2 + c) * ABYTES;
#pragma unroll
      for (int j = 0; j < 7; j++) {
        const bool hb = j > 3 || (j == 3 && t >= 2);
        const float r0 = hb ? rd[1] : rd[0], r1 = hb ? rd[3] : rd[2];
        *reinterpret_cast<uint32_t*>(img + slice_off(j, 0)) = pack(num[4 * j] * r0, num[4 * j + 1] * r0);
        *reinterpret_cast<uint32_t*>(img + slice_off(j, 1)) = pack(num[4 * j + 2] * r1, num[4 * j + 3] * r1);
      }
      STAMP(4 + layer * 12);
      gather(fl, img);
      STAMP(5 + layer * 12);
    }
    {
      float acc[28], acc2[28]; reg_def(acc); reg_def(acc2); reg_fence(acc); reg_fence(acc2);
      int sl[4];
      ring.uniform();
#pragma unroll
      for (int st = 0; st < 4; st++) {
        const uint64_t db = mkdesc(ring.acquire(), 4096, 1024, 1);
        sl[st] = ring.advance();
#pragma unroll
        for (int s = 0; s < 7; s++) {
          const int ks = st * 7 + s;
          if (!(ks & 3)) mbar_wait(barAc + (ks >> 2) * 8, apar);
          if (!(ks & 3) || !s) wg_fence();
          if (ks & 1) mma_ss_56(acc2, dA + ks * 128, db + s * 128, ks > 1); else mma_ss_56(acc, dA + ks * 128, db + s * 128, ks > 1);
        }
        wg_commit();
        if (st > 0) { wg_wait<1>(); ring.release(sl[st - 1], elect); }
      }
      wg_wait<0>(); reg_fence(acc); reg_fence(acc2);
      ring.release(sl[3], elect);
      unsigned char* img = gImg + (size_t)(32 + G * 2 + c) * ABYTES;
#pragma unroll
      for (int hh = 0; hh < 2; hh++) {
        float s = 0.f, q = 0.f;
#pragma unroll
        for (int j = 0; j < 7; j++) {
          xs[j][hh] = pack(lo(xs[j][hh]) + (acc[4 * j + 2 * hh] + acc2[4 * j + 2 * hh]), hi(xs[j][hh]) + (acc[4 * j + 2 * hh + 1] + acc2[4 * j + 2 * hh + 1]));
          *reinterpret_cast<uint32_t*>(img + slice_off(j, hh)) = xs[j][hh];
          s += lo(xs[j][hh]) + hi(xs[j][hh]);
        }
        s += __shfl_xor_sync(~0u, s, 1); s += __shfl_xor_sync(~0u, s, 2);
        s *= 1.f / 56.f;
#pragma unroll
        for (int j = 0; j < 7; j++) { const float a = lo(xs[j][hh]) - s, b = hi(xs[j][hh]) - s; q = fmaf(a, a, q); q = fmaf(b, b, q); }
        q += __shfl_xor_sync(~0u, q, 1); q += __shfl_xor_sync(~0u, q, 2);
        if (t == 0) gStat[(size_t)(row0 + w * 16 + hh * 8 + g) * 8 + r] = make_float2(s, q);
      }
#pragma unroll
      for (int j = 0; j < 7; j++) xs[j][0] = xs[j][1] = 0u;
      STAMP(6 + layer * 12);
      gather(fl + 32, img);
      STAMP(7 + layer * 12);
    }
    {
      uint32_t hf[28][2];
      {
        float acc[112]; reg_def(acc);
        int prev = 0, prev2 = 0;
        load_stats(gStat);
        ring.uniform();
#pragma unroll UNR
        for (int st = 0; st < 14; st++) {
          if (!(st & 1)) mbar_wait(barAc + (st >> 1) * 8, apar);
          const uint64_t da = dA + st * 256, db = mkdesc(ring.acquire(), 2048, 512, 2);
          wg_fence();
          mma_ss_224(acc, da, db, 1);
          mma_ss_224(acc, da + 128, db + 64, 1);
          wg_commit();
          if (st > 1) { wg_wait<2>(); ring.release(prev2, elect); }
          prev2 = prev; prev = ring.advance();
        }
        finish_stats();
        mbar_wait(barCS + 8, 0);
        wg_wait<0>(); reg_fence(acc);
        ring.release(prev2, elect); ring.release(prev, elect);
        STAMP(8 + layer * 12);
        const float2* bs = reinterpret_cast<const float2*>(sg + OFF_B1) + t;
        const float2* cs = reinterpret_cast<const float2*>(sg + OFF_CS + 768) + t;
        const float mr0 = -mean[0] * rstd[0], mr1 = -mean[1] * rstd[1];
#pragma unroll
        for (int j = 0; j < 28; j++) {
          const float2 b = bs[4 * j], s = cs[4 * j];
          hf[j][0] = relu_sq(fmaf(acc[4 * j], rstd[0], fmaf(s.x, mr0, b.x)), fmaf(acc[4 * j + 1], rstd[0], fmaf(s.y, mr0, b.y)));
          hf[j][1] = relu_sq(fmaf(acc[4 * j + 2], rstd[1], fmaf(s.x, mr1, b.x)), fmaf(acc[4 * j + 3], rstd[1], fmaf(s.y, mr1, b.y)));
        }
      }
      unsigned char* pdst = gP + (size_t)(((G * 2 + c) * 8 + 2 * w) * 8 + r) * 7168 + lane * 8;
      uint2 pk[8] = {};
      ring.uniform();
#pragma unroll 1
      for (int ch = 0; ch < 7; ch++) {
        float acc[32], acc2[32]; reg_def(acc); reg_def(acc2);
        const uint64_t db0 = mkdesc(ring.acquire(), 4096, 1024, 1);
        const int sl0 = ring.advance();
        const uint64_t db1 = mkdesc(ring.acquire(), 4096, 1024, 1);
        const int sl1 = ring.advance();
        wg_fence();
#pragma unroll
        for (int s = 0; s < 7; s++) {
          mma_rs_64(acc, hf[2 * s][0], hf[2 * s][1], hf[2 * s + 1][0], hf[2 * s + 1][1], db0 + s * 128, s);
          mma_rs_64(acc2, hf[14 + 2 * s][0], hf[14 + 2 * s][1], hf[15 + 2 * s][0], hf[15 + 2 * s][1], db1 + s * 128, s);
        }
        wg_commit();
        if (ch > 0) {
#pragma unroll
          for (int i = 0; i < 8; i++) *reinterpret_cast<uint2*>(pdst + (i & 1) * (8 * 7168) + (i >> 1) * 256) = pk[i];
          pdst += 1024;
        }
        wg_wait<0>(); reg_fence(acc); reg_fence(acc2); ring.release(sl0, elect); ring.release(sl1, elect);
#pragma unroll
        for (int i = 0; i < 8; i++) {
          const int b = (i >> 1) * 8 + (i & 1) * 2;
          pk[i] = make_uint2((pack(acc[b] + acc2[b], acc[b + 1] + acc2[b + 1]) & ~1u) | (layer ^ 1), pack(acc[b + 4] + acc2[b + 4], acc[b + 5] + acc2[b + 5]));
        }
      }
#pragma unroll
      for (int i = 0; i < 8; i++) *reinterpret_cast<uint2*>(pdst + (i & 1) * (8 * 7168) + (i >> 1) * 256) = pk[i];
      STAMP(9 + layer * 12);
    }
    {
      uint32_t bx[14];
#pragma unroll
      for (int j = 0; j < 14; j++) bx[j] = __ldg(reinterpret_cast<const uint32_t*>(b2 + (j >> 1) * 64 + w * 16 + (j & 1) * 8 + 2 * t));
      const unsigned char* psrc = gP + (size_t)(((G * 2 + c) * 8 + r) * 8) * 7168 + w * 256 + lane * 8;
      unsigned char* img = gImg + (size_t)(64 + G * 2 + c) * ABYTES;
      uint2 pv[8][7] = {};
      uint32_t need = 0x7F;
#pragma unroll 1
      for (int n = 0; need && n < (1 << 16); n++) {
#pragma unroll
        for (int i = 0; i < 7; i++)
          if (need >> i & 1) {
#pragma unroll
            for (int s = 0; s < 8; s++) pv[s][i] = ldcg2(psrc + s * 7168 + i * 1024);
          }
        uint32_t bad = 0;
#pragma unroll
        for (int i = 0; i < 7; i++) {
          const uint32_t all = pv[0][i].x & pv[1][i].x & pv[2][i].x & pv[3][i].x & pv[4][i].x & pv[5][i].x & pv[6][i].x & pv[7][i].x;
          const uint32_t any = pv[0][i].x | pv[1][i].x | pv[2][i].x | pv[3][i].x | pv[4][i].x | pv[5][i].x | pv[6][i].x | pv[7][i].x;
          bad |= ((layer ? any : ~all) & 1u) << i;
        }
        need = __reduce_or_sync(~0u, bad);
      }
      STAMP(10 + layer * 12);
      const uint32_t off = w * 2048 + r * 128 + lane * 4;
      unsigned char* dst = layer ? reinterpret_cast<unsigned char*>(out + (size_t)(row0 + r * 8 + g) * DM + w * 16 + 2 * t) : img + off;
      float sm = 0.f, q = 0.f;
#pragma unroll
      for (int j = 0; j < 14; j++) {
        float y0 = lo(bx[j]), y1 = hi(bx[j]);
        const uint32_t xo = lds32(abuf + off + (j >> 1) * 8192 + (j & 1) * 1024);
        y0 += lo(xo); y1 += hi(xo);
#pragma unroll
        for (int s = 0; s < 8; s++) { const uint32_t u = (j & 1) ? pv[s][j >> 1].y : pv[s][j >> 1].x; y0 += lo(u); y1 += hi(u); }
        bx[j] = pack(y0, y1);
        *reinterpret_cast<uint32_t*>(dst + ((j >> 1) * 8 + (j & 1)) * (layer ? 16 : 1024)) = bx[j];
        sm += lo(bx[j]) + hi(bx[j]);
      }
      if (layer) break;
      sm += __shfl_xor_sync(~0u, sm, 1); sm += __shfl_xor_sync(~0u, sm, 2);
      sm *= 1.f / 112.f;
#pragma unroll
      for (int j = 0; j < 14; j++) { const float a = lo(bx[j]) - sm, b = hi(bx[j]) - sm; q = fmaf(a, a, q); q = fmaf(b, b, q); }
      q += __shfl_xor_sync(~0u, q, 1); q += __shfl_xor_sync(~0u, q, 2);
      if (t < 2) gStat[(size_t)(2048 + row0 + r * 8 + g) * 8 + 2 * w + t] = make_float2(sm, q * 0.5f);
      STAMP(11);
      gather(fl + 64, img);
      STAMP(12);
    }
  }
  STAMP(30);
  if (tid == 0) asm volatile("red.relaxed.gpu.global.add.u32 [%0], 1;" ::"l"(gFlag + FL_DONE * 32) : "memory");
  }
}

typedef CUresult (*EncFn)(CUtensorMap*, CUtensorMapDataType, cuuint32_t, void*, const cuuint64_t*, const cuuint64_t*,
                          const cuuint32_t*, const cuuint32_t*, CUtensorMapInterleave, CUtensorMapSwizzle,
                          CUtensorMapL2promotion, CUtensorMapFloatOOBfill);

void make_map(EncFn enc, CUtensorMap* m, void* p, int rank, uint64_t d0, uint64_t d1, uint64_t d2, uint64_t s1, uint64_t s2,
              uint32_t b0, uint32_t b1, uint32_t b2, CUtensorMapSwizzle sw) {
  cuuint64_t dims[3] = {d0, d1, d2}, strides[2] = {s1, s2};
  cuuint32_t box[3] = {b0, b1, b2}, es[3] = {1, 1, 1};
  enc(m, CU_TENSOR_MAP_DATA_TYPE_BFLOAT16, rank, p, dims, strides, box, es, CU_TENSOR_MAP_INTERLEAVE_NONE, sw,
      CU_TENSOR_MAP_L2_PROMOTION_L2_128B, CU_TENSOR_MAP_FLOAT_OOB_FILL_NONE);
}

}

extern "C" void kernel_launch(void* const* d_in, const int* in_sizes, int n_in, void* d_out, int out_size) {
  static EncFn enc = nullptr;
  if (!enc) {
    cudaDriverEntryPointQueryResult st;
    void* fn = nullptr;
    cudaGetDriverEntryPoint("cuTensorMapEncodeTiled", &fn, cudaEnableDefault, &st);
    enc = (EncFn)fn;
    cudaFuncSetAttribute(fused_kernel, cudaFuncAttributeMaxDynamicSharedMemorySize, SMEM_BYTES);
  }
  CUtensorMap mQKV, mWO, mW1, mW2, mX;
  make_map(enc, &mX, d_in[0], 2, 448, 2048, 1, 896, 0, 64, 64, 1, CU_TENSOR_MAP_SWIZZLE_128B);
  make_map(enc, &mQKV, d_in[1], 3, 448, 448, 3, 2688, 896, 64, 32, 3, CU_TENSOR_MAP_SWIZZLE_128B);
  make_map(enc, &mWO, d_in[3], 2, 448, 448, 1, 896, 0, 64, 112, 1, CU_TENSOR_MAP_SWIZZLE_128B);
  make_map(enc, &mW1, d_in[5], 3, 32, 448, 56, 3584, 64, 32, 32, 7, CU_TENSOR_MAP_SWIZZLE_64B);
  make_map(enc, &mW2, d_in[7], 2, 448, 1792, 1, 896, 0, 64, 112, 1, CU_TENSOR_MAP_SWIZZLE_128B);
  fused_kernel<<<NCTA, 384, SMEM_BYTES, cudaStreamPerThread>>>(
      mQKV, mWO, mW1, mW2, mX, (const __nv_bfloat16*)d_in[2], (const __nv_bfloat16*)d_in[6],
      (const __nv_bfloat16*)d_in[8], (const __nv_bfloat16*)d_in[1], (const __nv_bfloat16*)d_in[3], (const __nv_bfloat16*)d_in[5],
      (const __nv_bfloat16*)d_in[7], (__nv_bfloat16*)d_out);
}
```

```cpp
#include <cuda_runtime.h>
#include <cuda_bf16.h>
#include <cuda.h>
#include <stdint.h>

namespace {

constexpr int DM = 448, NCTA = 128;
constexpr int ABYTES = 57344;
constexpr int SLOT = 14336, NSLOT = 7;
constexpr int OFF_RING = 2 * ABYTES;
constexpr int OFF_WPHI = OFF_RING + NSLOT * SLOT;
constexpr int OFF_B1 = OFF_WPHI + 8192;
constexpr int OFF_CS = OFF_B1 + 896;
constexpr int OFF_BAR = OFF_CS + 1664;
constexpr int SMEM_BYTES = OFF_BAR + 272 + 1024;
constexpr int TILES_PER_LAYER = 46;

__device__ __align__(1024) unsigned char gP[16 * 2 * 8 * 8 * 7168];
__device__ __align__(1024) unsigned char gImg[3 * 32 * ABYTES];
__device__ __align__(1024) float2 gStat[2 * 2048 * 8];
__device__ __align__(1024) float4 gKV[2 * 8 * 2 * 5 * 128];
__device__ __align__(1024) float4 gCS[8 * 16 * 104];
__device__ __align__(128) unsigned gFlag[(2 * 32 * 7 + 32 + 1 + 16) * 32];
#define STAMP(i)

__device__ __forceinline__ uint32_t smem_u32(const void* p) { return (uint32_t)__cvta_generic_to_shared(p); }
__device__ __forceinline__ void mbar_init(uint32_t b, int c) { asm volatile("mbarrier.init.shared::cta.b64 [%0], %1;" ::"r"(b), "r"(c)); }
__device__ __forceinline__ void mbar_expect(uint32_t b, int bytes) { asm volatile("mbarrier.arrive.expect_tx.shared::cta.b64 _, [%0], %1;" ::"r"(b), "r"(bytes) : "memory"); }
__device__ __forceinline__ void mbar_arrive(uint32_t b) { asm volatile("mbarrier.arrive.shared::cta.b64 _, [%0];" ::"r"(b) : "memory"); }
__device__ __forceinline__ void mbar_wait(uint32_t b, int par) {
  uint32_t ok; int n = 0;
#pragma unroll 1
  while (true) {
    asm volatile("{.reg .pred p; mbarrier.try_wait.parity.shared::cta.b64 p, [%1], %2; selp.u32 %0,1,0,p;}" : "=r"(ok) : "r"(b), "r"(par) : "memory");
    if (ok) break;
    if (++n > (1 << 22)) break;
  }
}
__device__ __forceinline__ void flag_wait(const unsigned* f, unsigned target) {
  unsigned v; int n = 0;
#pragma unroll 1
  while (true) {
    asm volatile("ld.acquire.gpu.global.u32 %0, [%1];" : "=r"(v) : "l"(f) : "memory");
    if ((int)(v - target) >= 0) break;
    if (++n > (1 << 21)) break;
  }
}
__device__ __forceinline__ void flag_arrive(unsigned* f) { asm volatile("red.release.gpu.global.add.u32 [%0], 1;" ::"l"(f) : "memory"); }
__device__ __forceinline__ bool elect_one() {
  uint32_t p; asm volatile("{.reg .pred P; elect.sync _|P, 0xffffffff; selp.u32 %0, 1, 0, P;}" : "=r"(p)); return p;
}
__device__ __forceinline__ void fence_async() { asm volatile("fence.proxy.async.global;" ::: "memory"); }
__device__ __forceinline__ void fence_async_smem() { asm volatile("fence.proxy.async.shared::cta;" ::: "memory"); }
template <int ID, int N> __device__ __forceinline__ void bar_sync() { asm volatile("bar.sync %0, %1;" ::"n"(ID), "n"(N) : "memory"); }
__device__ __forceinline__ void bar_wg(int c) { if (c) bar_sync<2, 128>(); else bar_sync<1, 128>(); }
__device__ __forceinline__ void wg_fence() { asm volatile("wgmma.fence.sync.aligned;" ::: "memory"); }
__device__ __forceinline__ void wg_commit() { asm volatile("wgmma.commit_group.sync.aligned;" ::: "memory"); }
template <int N> __device__ __forceinline__ void wg_wait() { asm volatile("wgmma.wait_group.sync.aligned %0;" ::"n"(N) : "memory"); }
template <int N> __device__ __forceinline__ void reg_fence(float (&d)[N]) {
#pragma unroll
  for (int i = 0; i < N; i++) asm volatile("" : "+f"(d[i])::"memory");
}
template <int N> __device__ __forceinline__ void reg_def(float (&d)[N]) {
#pragma unroll
  for (int i = 0; i < N; i++) d[i] = 0.f;
}
__device__ __forceinline__ uint64_t mkdesc(uint32_t addr, uint32_t lbo, uint32_t sbo, uint64_t swz) {
  return (uint64_t)((addr & 0x3FFFF) >> 4) | ((uint64_t)(lbo >> 4) << 16) | ((uint64_t)(sbo >> 4) << 32) | (swz << 62);
}
__device__ __forceinline__ uint32_t pack(float a, float b) {
  uint32_t r; asm("cvt.rn.bf16x2.f32 %0, %1, %2;" : "=r"(r) : "f"(b), "f"(a)); return r;
}
__device__ __forceinline__ uint32_t relu_sq(float a, float b) {
  uint32_t r; asm("{.reg .b32 v; cvt.rn.relu.bf16x2.f32 v, %1, %2; mul.rn.bf16x2 %0, v, v;}" : "=r"(r) : "f"(b), "f"(a)); return r;
}
__device__ __forceinline__ float lo(uint32_t u) { return __uint_as_float(u << 16); }
__device__ __forceinline__ float hi(uint32_t u) { return __uint_as_float(u & 0xFFFF0000u); }
__device__ __forceinline__ float ex2(float x) { float y; asm("ex2.approx.ftz.f32 %0, %1;" : "=f"(y) : "f"(x)); return y; }
__device__ __forceinline__ void stsm4(uint32_t a, uint32_t r0, uint32_t r1, uint32_t r2, uint32_t r3) {
  asm volatile("stmatrix.sync.aligned.m8n8.x4.shared.b16 [%0], {%1,%2,%3,%4};" ::"r"(a), "r"(r0), "r"(r1), "r"(r2), "r"(r3) : "memory");
}
__device__ __forceinline__ void tma3(uint32_t dst, const CUtensorMap* m, int c0, int c1, int c2, uint32_t bar) {
  asm volatile("cp.async.bulk.tensor.3d.shared::cluster.global.mbarrier::complete_tx::bytes [%0], [%1, {%3,%4,%5}], [%2];"
               ::"r"(dst), "l"(m), "r"(bar), "r"(c0), "r"(c1), "r"(c2) : "memory");
}
__device__ __forceinline__ void tma2(uint32_t dst, const CUtensorMap* m, int c0, int c1, uint32_t bar) {
  asm volatile("cp.async.bulk.tensor.2d.shared::cluster.global.mbarrier::complete_tx::bytes [%0], [%1, {%3,%4}], [%2];"
               ::"r"(dst), "l"(m), "r"(bar), "r"(c0), "r"(c1) : "memory");
}
__device__ __forceinline__ uint32_t lds32(uint32_t a) { uint32_t v; asm volatile("ld.shared.u32 %0, [%1];" : "=r"(v) : "r"(a) : "memory"); return v; }
__device__ __forceinline__ void bulk_ld(uint32_t dst, const void* src, int bytes, uint32_t bar) {
  asm volatile("cp.async.bulk.shared::cluster.global.mbarrier::complete_tx::bytes [%0], [%1], %2, [%3];" ::"r"(dst), "l"(src), "r"(bytes), "r"(bar) : "memory");
}
__device__ __forceinline__ uint4 ldcg4(const void* p) {
  uint4 v; asm volatile("ld.global.cg.v4.u32 {%0,%1,%2,%3}, [%4];" : "=r"(v.x), "=r"(v.y), "=r"(v.z), "=r"(v.w) : "l"(p) : "memory"); return v;
}

__device__ __forceinline__ uint2 ldcg2(const void* p) {
  uint2 v; asm volatile("ld.global.cg.v2.u32 {%0,%1}, [%2];" : "=r"(v.x), "=r"(v.y) : "l"(p) : "memory"); return v;
}

__device__ __forceinline__ void mma_ss_184(float (&d)[92], uint64_t da, uint64_t db, int acc) {
  asm volatile("{.reg .pred p; setp.ne.b32 p, %94, 0;\n"
    "wgmma.mma_async.sync.aligned.m64n184k16.f32.bf16.bf16 {%0,%1,%2,%3,%4,%5,%6,%7,%8,%9,%10,%11,%12,%13,%14,%15,%16,%17,%18,%19,%20,%21,%22,%23,%24,%25,%26,%27,%28,%29,%30,%31,%32,%33,%34,%35,%36,%37,%38,%39,%40,%41,%42,%43,%44,%45,%46,%47,%48,%49,%50,%51,%52,%53,%54,%55,%56,%57,%58,%59,%60,%61,%62,%63,%64,%65,%66,%67,%68,%69,%70,%71,%72,%73,%74,%75,%76,%77,%78,%79,%80,%81,%82,%83,%84,%85,%86,%87,%88,%89,%90,%91}, %92, %93, p, 1, 1, 0, 1;}\n"
    : "+f"(d[0]),"+f"(d[1]),"+f"(d[2]),"+f"(d[3]),"+f"(d[4]),"+f"(d[5]),"+f"(d[6]),"+f"(d[7]),"+f"(d[8]),"+f"(d[9]),"+f"(d[10]),"+f"(d[11]),"+f"(d[12]),"+f"(d[13]),"+f"(d[14]),"+f"(d[15]),"+f"(d[16]),"+f"(d[17]),"+f"(d[18]),"+f"(d[19]),"+f"(d[20]),"+f"(d[21]),"+f"(d[22]),"+f"(d[23]),"+f"(d[24]),"+f"(d[25]),"+f"(d[26]),"+f"(d[27]),"+f"(d[28]),"+f"(d[29]),"+f"(d[30]),"+f"(d[31]),"+f"(d[32]),"+f"(d[33]),"+f"(d[34]),"+f"(d[35]),"+f"(d[36]),"+f"(d[37]),"+f"(d[38]),"+f"(d[39]),"+f"(d[40]),"+f"(d[41]),"+f"(d[42]),"+f"(d[43]),"+f"(d[44]),"+f"(d[45]),"+f"(d[46]),"+f"(d[47]),"+f"(d[48]),"+f"(d[49]),"+f"(d[50]),"+f"(d[51]),"+f"(d[52]),"+f"(d[53]),"+f"(d[54]),"+f"(d[55]),"+f"(d[56]),"+f"(d[57]),"+f"(d[58]),"+f"(d[59]),"+f"(d[60]),"+f"(d[61]),"+f"(d[62]),"+f"(d[63]),"+f"(d[64]),"+f"(d[65]),"+f"(d[66]),"+f"(d[67]),"+f"(d[68]),"+f"(d[69]),"+f"(d[70]),"+f"(d[71]),"+f"(d[72]),"+f"(d[73]),"+f"(d[74]),"+f"(d[75]),"+f"(d[76]),"+f"(d[77]),"+f"(d[78]),"+f"(d[79]),"+f"(d[80]),"+f"(d[81]),"+f"(d[82]),"+f"(d[83]),"+f"(d[84]),"+f"(d[85]),"+f"(d[86]),"+f"(d[87]),"+f"(d[88]),"+f"(d[89]),"+f"(d[90]),"+f"(d[91])
    : "l"(da), "l"(db), "r"(acc));
}
__device__ __forceinline__ void mma_ss_224(float (&d)[112], uint64_t da, uint64_t db, int acc) {
  asm volatile("{.reg .pred p; setp.ne.b32 p, %114, 0;\n"
    "wgmma.mma_async.sync.aligned.m64n224k16.f32.bf16.bf16 {%0,%1,%2,%3,%4,%5,%6,%7,%8,%9,%10,%11,%12,%13,%14,%15,%16,%17,%18,%19,%20,%21,%22,%23,%24,%25,%26,%27,%28,%29,%30,%31,%32,%33,%34,%35,%36,%37,%38,%39,%40,%41,%42,%43,%44,%45,%46,%47,%48,%49,%50,%51,%52,%53,%54,%55,%56,%57,%58,%59,%60,%61,%62,%63,%64,%65,%66,%67,%68,%69,%70,%71,%72,%73,%74,%75,%76,%77,%78,%79,%80,%81,%82,%83,%84,%85,%86,%87,%88,%89,%90,%91,%92,%93,%94,%95,%96,%97,%98,%99,%100,%101,%102,%103,%104,%105,%106,%107,%108,%109,%110,%111}, %112, %113, p, 1, 1, 0, 1;}\n"
    : "+f"(d[0]),"+f"(d[1]),"+f"(d[2]),"+f"(d[3]),"+f"(d[4]),"+f"(d[5]),"+f"(d[6]),"+f"(d[7]),"+f"(d[8]),"+f"(d[9]),"+f"(d[10]),"+f"(d[11]),"+f"(d[12]),"+f"(d[13]),"+f"(d[14]),"+f"(d[15]),"+f"(d[16]),"+f"(d[17]),"+f"(d[18]),"+f"(d[19]),"+f"(d[20]),"+f"(d[21]),"+f"(d[22]),"+f"(d[23]),"+f"(d[24]),"+f"(d[25]),"+f"(d[26]),"+f"(d[27]),"+f"(d[28]),"+f"(d[29]),"+f"(d[30]),"+f"(d[31]),"+f"(d[32]),"+f"(d[33]),"+f"(d[34]),"+f"(d[35]),"+f"(d[36]),"+f"(d[37]),"+f"(d[38]),"+f"(d[39]),"+f"(d[40]),"+f"(d[41]),"+f"(d[42]),"+f"(d[43]),"+f"(d[44]),"+f"(d[45]),"+f"(d[46]),"+f"(d[47]),"+f"(d[48]),"+f"(d[49]),"+f"(d[50]),"+f"(d[51]),"+f"(d[52]),"+f"(d[53]),"+f"(d[54]),"+f"(d[55]),"+f"(d[56]),"+f"(d[57]),"+f"(d[58]),"+f"(d[59]),"+f"(d[60]),"+f"(d[61]),"+f"(d[62]),"+f"(d[63]),"+f"(d[64]),"+f"(d[65]),"+f"(d[66]),"+f"(d[67]),"+f"(d[68]),"+f"(d[69]),"+f"(d[70]),"+f"(d[71]),"+f"(d[72]),"+f"(d[73]),"+f"(d[74]),"+f"(d[75]),"+f"(d[76]),"+f"(d[77]),"+f"(d[78]),"+f"(d[79]),"+f"(d[80]),"+f"(d[81]),"+f"(d[82]),"+f"(d[83]),"+f"(d[84]),"+f"(d[85]),"+f"(d[86]),"+f"(d[87]),"+f"(d[88]),"+f"(d[89]),"+f"(d[90]),"+f"(d[91]),"+f"(d[92]),"+f"(d[93]),"+f"(d[94]),"+f"(d[95]),"+f"(d[96]),"+f"(d[97]),"+f"(d[98]),"+f"(d[99]),"+f"(d[100]),"+f"(d[101]),"+f"(d[102]),"+f"(d[103]),"+f"(d[104]),"+f"(d[105]),"+f"(d[106]),"+f"(d[107]),"+f"(d[108]),"+f"(d[109]),"+f"(d[110]),"+f"(d[111])
    : "l"(da), "l"(db), "r"(acc));
}
__device__ __forceinline__ void mma_ss_56(float (&d)[28], uint64_t da, uint64_t db, int acc) {
  asm volatile("{.reg .pred p; setp.ne.b32 p, %30, 0;\n"
    "wgmma.mma_async.sync.aligned.m64n56k16.f32.bf16.bf16 {%0,%1,%2,%3,%4,%5,%6,%7,%8,%9,%10,%11,%12,%13,%14,%15,%16,%17,%18,%19,%20,%21,%22,%23,%24,%25,%26,%27}, %28, %29, p, 1, 1, 0, 1;}\n"
    : "+f"(d[0]),"+f"(d[1]),"+f"(d[2]),"+f"(d[3]),"+f"(d[4]),"+f"(d[5]),"+f"(d[6]),"+f"(d[7]),"+f"(d[8]),"+f"(d[9]),"+f"(d[10]),"+f"(d[11]),"+f"(d[12]),"+f"(d[13]),"+f"(d[14]),"+f"(d[15]),"+f"(d[16]),"+f"(d[17]),"+f"(d[18]),"+f"(d[19]),"+f"(d[20]),"+f"(d[21]),"+f"(d[22]),"+f"(d[23]),"+f"(d[24]),"+f"(d[25]),"+f"(d[26]),"+f"(d[27])
    : "l"(da), "l"(db), "r"(acc));
}
__device__ __forceinline__ void mma_rs_56(float (&d)[28], uint32_t a0, uint32_t a1, uint32_t a2, uint32_t a3, uint64_t db, int acc) {
  asm volatile("{.reg .pred p; setp.ne.b32 p, %33, 0;\n"
    "wgmma.mma_async.sync.aligned.m64n56k16.f32.bf16.bf16 {%0,%1,%2,%3,%4,%5,%6,%7,%8,%9,%10,%11,%12,%13,%14,%15,%16,%17,%18,%19,%20,%21,%22,%23,%24,%25,%26,%27}, {%28,%29,%30,%31}, %32, p, 1, 1, 1;}\n"
    : "+f"(d[0]),"+f"(d[1]),"+f"(d[2]),"+f"(d[3]),"+f"(d[4]),"+f"(d[5]),"+f"(d[6]),"+f"(d[7]),"+f"(d[8]),"+f"(d[9]),"+f"(d[10]),"+f"(d[11]),"+f"(d[12]),"+f"(d[13]),"+f"(d[14]),"+f"(d[15]),"+f"(d[16]),"+f"(d[17]),"+f"(d[18]),"+f"(d[19]),"+f"(d[20]),"+f"(d[21]),"+f"(d[22]),"+f"(d[23]),"+f"(d[24]),"+f"(d[25]),"+f"(d[26]),"+f"(d[27])
    : "r"(a0), "r"(a1), "r"(a2), "r"(a3), "l"(db), "r"(acc));
}
__device__ __forceinline__ void mma_ss_64t(float (&d)[32], uint64_t da, uint64_t db, int acc) {
  asm volatile("{.reg .pred p; setp.ne.b32 p, %34, 0;\n"
    "wgmma.mma_async.sync.aligned.m64n64k16.f32.bf16.bf16 {%0,%1,%2,%3,%4,%5,%6,%7,%8,%9,%10,%11,%12,%13,%14,%15,%16,%17,%18,%19,%20,%21,%22,%23,%24,%25,%26,%27,%28,%29,%30,%31}, %32, %33, p, 1, 1, 1, 1;}\n"
    : "+f"(d[0]),"+f"(d[1]),"+f"(d[2]),"+f"(d[3]),"+f"(d[4]),"+f"(d[5]),"+f"(d[6]),"+f"(d[7]),"+f"(d[8]),"+f"(d[9]),"+f"(d[10]),"+f"(d[11]),"+f"(d[12]),"+f"(d[13]),"+f"(d[14]),"+f"(d[15]),"+f"(d[16]),"+f"(d[17]),"+f"(d[18]),"+f"(d[19]),"+f"(d[20]),"+f"(d[21]),"+f"(d[22]),"+f"(d[23]),"+f"(d[24]),"+f"(d[25]),"+f"(d[26]),"+f"(d[27]),"+f"(d[28]),"+f"(d[29]),"+f"(d[30]),"+f"(d[31])
    : "l"(da), "l"(db), "r"(acc));
}
__device__ __forceinline__ void mma_rs_64(float (&d)[32], uint32_t a0, uint32_t a1, uint32_t a2, uint32_t a3, uint64_t db, int acc) {
  asm volatile("{.reg .pred p; setp.ne.b32 p, %37, 0;\n"
    "wgmma.mma_async.sync.aligned.m64n64k16.f32.bf16.bf16 {%0,%1,%2,%3,%4,%5,%6,%7,%8,%9,%10,%11,%12,%13,%14,%15,%16,%17,%18,%19,%20,%21,%22,%23,%24,%25,%26,%27,%28,%29,%30,%31}, {%32,%33,%34,%35}, %36, p, 1, 1, 1;}\n"
    : "+f"(d[0]),"+f"(d[1]),"+f"(d[2]),"+f"(d[3]),"+f"(d[4]),"+f"(d[5]),"+f"(d[6]),"+f"(d[7]),"+f"(d[8]),"+f"(d[9]),"+f"(d[10]),"+f"(d[11]),"+f"(d[12]),"+f"(d[13]),"+f"(d[14]),"+f"(d[15]),"+f"(d[16]),"+f"(d[17]),"+f"(d[18]),"+f"(d[19]),"+f"(d[20]),"+f"(d[21]),"+f"(d[22]),"+f"(d[23]),"+f"(d[24]),"+f"(d[25]),"+f"(d[26]),"+f"(d[27]),"+f"(d[28]),"+f"(d[29]),"+f"(d[30]),"+f"(d[31])
    : "r"(a0), "r"(a1), "r"(a2), "r"(a3), "l"(db), "r"(acc));
}

__device__ __forceinline__ void dual_softmax(const float (&p)[28], uint32_t (&phi)[4][7]) {
  constexpr float L2E = 1.4426950408889634f;
#pragma unroll
  for (int i = 0; i < 4; i++) {
    float mx = p[i], mn = p[i];
#pragma unroll
    for (int j = 1; j < 7; j++) { mx = fmaxf(mx, p[4 * j + i]); mn = fminf(mn, p[4 * j + i]); }
    mx = fmaxf(mx, __shfl_xor_sync(~0u, mx, 1)); mn = fminf(mn, __shfl_xor_sync(~0u, mn, 1));
    mx = fmaxf(mx, __shfl_xor_sync(~0u, mx, 2)); mn = fminf(mn, __shfl_xor_sync(~0u, mn, 2));
    float a[7], b[7], sa = 0.f, sb = 0.f;
    const float mxl = mx * L2E, mnl = mn * L2E;
#pragma unroll
    for (int j = 0; j < 7; j++) {
      a[j] = ex2(fmaf(p[4 * j + i], L2E, -mxl)); b[j] = ex2(fmaf(p[4 * j + i], -L2E, mnl));
      sa += a[j]; sb += b[j];
    }
    sa += __shfl_xor_sync(~0u, sa, 1); sb += __shfl_xor_sync(~0u, sb, 1);
    sa += __shfl_xor_sync(~0u, sa, 2); sb += __shfl_xor_sync(~0u, sb, 2);
    const float ra = __fdividef(1.f, sa), rb = __fdividef(1.f, sb);
#pragma unroll
    for (int j = 0; j < 7; j++) phi[i][j] = pack(a[j] * ra, b[j] * rb);
  }
}

struct Ring {
  uint32_t full, empty, base; int slot, par;
  __device__ __forceinline__ void uniform() { slot = __shfl_sync(~0u, slot, 0); par = __shfl_sync(~0u, par, 0); }
  __device__ __forceinline__ uint32_t acquire() { mbar_wait(full + slot * 8, par); return base + slot * SLOT; }
  __device__ __forceinline__ int advance() { int s = slot; if (++slot == NSLOT) { slot = 0; par ^= 1; } return s; }
  __device__ __forceinline__ void release(int s, bool elect) { if (elect) mbar_arrive(empty + s * 8); }
};
constexpr int UNR = 14;
constexpr int FL_KV = 448, FL_CS = FL_KV + 16, FL_DONE = FL_KV + 32;

__global__ void __launch_bounds__(384, 1)
fused_kernel(const __grid_constant__ CUtensorMap mQKV, const __grid_constant__ CUtensorMap mWO,
             const __grid_constant__ CUtensorMap mW1, const __grid_constant__ CUtensorMap mW2,
             const __grid_constant__ CUtensorMap mX, const __nv_bfloat16* __restrict__ wphi,
             const __nv_bfloat16* __restrict__ b1, const __nv_bfloat16* __restrict__ b2,
             const __nv_bfloat16* __restrict__ wqkv, const __nv_bfloat16* __restrict__ wo, const __nv_bfloat16* __restrict__ w1,
             const __nv_bfloat16* __restrict__ w2, __nv_bfloat16* __restrict__ out) {
  extern __shared__ unsigned char smem_raw[];
  const uint32_t sb = (smem_u32(smem_raw) + 1023) & ~1023u;
  unsigned char* sg = smem_raw + (sb - smem_u32(smem_raw));
  const int tid = threadIdx.x, lane = tid & 31;
  const int G = blockIdx.x >> 3, r = blockIdx.x & 7;
  const uint32_t barFull = sb + OFF_BAR, barEmpty = barFull + 56, barA = barEmpty + 56, barCS = barA + 112, barX = barCS + 16;
  const int warp = __shfl_sync(~0u, tid >> 5, 0);
  uint32_t wv[7], bv;
#pragma unroll
  for (int i = 0; i < 7; i++)
    wv[i] = __ldg(reinterpret_cast<const unsigned short*>(wphi) + (56 * r + i * 8 + (warp & 7)) * 28 + min(lane, 27));
  bv = __ldg(reinterpret_cast<const unsigned short*>(b1) + 224 * r + min(tid, 223));
  if (lane == 0) {
    if (warp >= 10) {
      const int cc = warp - 10;
      mbar_init(barX + cc * 8, 1);
      fence_async_smem();
      mbar_expect(barX + cc * 8, ABYTES);
#pragma unroll 1
      for (int k = 0; k < 7; k++) tma2(sb + cc * ABYTES + k * 8192, &mX, 64 * k, G * 128 + 64 * cc, barX + cc * 8);
    } else if (warp < 7) { mbar_init(barFull + warp * 8, 1); mbar_init(barEmpty + warp * 8, 2); mbar_init(barA + warp * 8, 1); mbar_init(barA + 56 + warp * 8, 1); }
    else if (warp < 9) mbar_init(barCS + (warp - 7) * 8, 96);
    else
      asm volatile("cp.async.bulk.prefetch.L2.global [%0], %1;" ::"l"((const char*)wqkv + blockIdx.x * 9408), "r"(9408) : "memory");
    asm volatile("fence.mbarrier_init.release.cluster;" ::: "memory");
  }
  if (tid < 192) reinterpret_cast<float*>(sg + OFF_CS)[tid] = 0.f;
  __syncthreads();
  const int wgid = warp >> 2;
  if (wgid == 2) {
    asm volatile("setmaxnreg.dec.sync.aligned.u32 40;");
    if (warp == 8) {
      int slot = 0, par = 1;
#pragma unroll 1
      for (int it = 0; it < 2 * TILES_PER_LAYER; it++) {
        const int i = it >= TILES_PER_LAYER ? it - TILES_PER_LAYER : it;
        mbar_wait(barEmpty + slot * 8, par);
        const uint32_t dst = sb + OFF_RING + slot * SLOT, fb = barFull + slot * 8;
        if (elect_one()) {
          mbar_expect(fb, i < 14 ? 12288 : SLOT);
          if (i < 14) tma3(dst, &mQKV, 56 * r, 32 * i, 0, fb);
          else if (i < 18) tma2(dst, &mWO, 56 * r, 112 * (i - 14), fb);
          else if (i < 32) tma3(dst, &mW1, 0, 32 * (i - 18), 7 * r, fb);
          else tma2(dst, &mW2, 64 * ((i - 32) >> 1), 224 * r + 112 * (i & 1), fb);
        }
        if (++slot == NSLOT) { slot = 0; par ^= 1; }
      }
    } else {
      unsigned ep;
      asm volatile("ld.relaxed.gpu.global.u32 %0, [%1];" : "=r"(ep) : "l"(gFlag + FL_DONE * 32) : "memory");
      const int idx = tid - 288;
      ep = (ep / NCTA + 1) * 3;
      if (G == 0) {
#pragma unroll 1
        for (int i = idx; i < 2 * 1280; i += 96) gKV[((i >= 1280) * 7 + r) * 1280 + i] = make_float4(0.f, 0.f, 0.f, 0.f);
        __syncwarp();
        if (lane == 0) flag_arrive(gFlag + (FL_CS + r) * 32);
      }
      mbar_wait(barFull + 48, 0); mbar_wait(barFull + 48, 1);
      if (idx < 2) {
        const char* pf = idx ? (const char*)w2 + blockIdx.x * 12544 : (const char*)wo + blockIdx.x * 3136;
        asm volatile("cp.async.bulk.prefetch.L2.global [%0], %1;" ::"l"(pf), "r"(idx ? 12544 : 3136) : "memory");
      }
      if (lane == 0) flag_wait(gFlag + (FL_CS + r) * 32, ep);
      __syncwarp();
      mbar_arrive(barCS);
#pragma unroll 1
      for (int ps = 0; ps < 3; ps++) {
        const int nch = ps ? 14 : 21, ch = min(idx >> 2, nch - 1), p = ch / 7, k0 = G * 28 + (idx & 3) * 7;
        const uint4* src = ps ? reinterpret_cast<const uint4*>(w1 + (size_t)k0 * 1792 + 224 * r) + (ps - 1) * 14 + ch
                              : reinterpret_cast<const uint4*>(wqkv + (size_t)k0 * 1344 + p * 448 + 56 * r) + (ch - 7 * p);
        uint4 cu[7];
#pragma unroll
        for (int i = 0; i < 7; i++) cu[i] = __ldg(src + i * (ps ? 224 : 168));
        float s[8] = {};
#pragma unroll
        for (int i = 0; i < 7; i++) { s[0] += lo(cu[i].x); s[1] += hi(cu[i].x); s[2] += lo(cu[i].y); s[3] += hi(cu[i].y); s[4] += lo(cu[i].z); s[5] += hi(cu[i].z); s[6] += lo(cu[i].w); s[7] += hi(cu[i].w); }
#pragma unroll
        for (int i = 0; i < 8; i++) { s[i] += __shfl_xor_sync(~0u, s[i], 1); s[i] += __shfl_xor_sync(~0u, s[i], 2); }
        if ((idx & 3) < 2 && idx < nch * 4) gCS[(r * 16 + G) * 104 + (ps ? 10 + ps * 14 + ch : ch + p) * 2 + (idx & 1)] = (idx & 1) ? make_float4(s[4], s[5], s[6], s[7]) : make_float4(s[0], s[1], s[2], s[3]);
      }
      __syncwarp();
      if (lane == 0) { flag_arrive(gFlag + (FL_CS + 8 + r) * 32); flag_wait(gFlag + (FL_CS + 8 + r) * 32, ep * 16); }
      __syncwarp();
#pragma unroll 1
      for (int j = idx; j < 208; j += 96) {
        float2 a = make_float2(0.f, 0.f);
#pragma unroll 8
        for (int i = 0; i < 16; i++) { const float2 v = __ldcg(reinterpret_cast<const float2*>(gCS + (r * 16 + i) * 104) + j); a.x += v.x; a.y += v.y; }
        reinterpret_cast<float2*>(sg + OFF_CS)[j] = a;
      }
      mbar_arrive(barCS + 8);
    }
  } else {
  asm volatile("setmaxnreg.inc.sync.aligned.u32 232;");
  const int c = wgid, w = warp & 3, g = lane >> 2, t = lane & 3;
  int elect_i = (tid & 127) == 0;
  asm volatile("" : "+r"(elect_i));
  const bool elect = elect_i;
  const uint32_t abuf = sb + c * ABYTES, barAc = barA + c * 56;
  const int row0 = G * 128 + c * 64;
  unsigned epoch;
  asm volatile("ld.relaxed.gpu.global.u32 %0, [%1];" : "=r"(epoch) : "l"(gFlag + FL_DONE * 32) : "memory");
  STAMP(24);
  float mean[2], rstd[2] = {0.f, 0.f};
  uint4 su[2] = {};
  uint32_t xs[7][2];
  {
#pragma unroll
    for (int i = 0; i < 8; i++) {
      const int k = i * 8 + (tid >> 5);
      *reinterpret_cast<uint32_t*>(sg + OFF_WPHI + k * 128 + ((g ^ (k & 7)) << 4) + t * 4) = (i < 7 && lane < 28) ? wv[i % 7] << (k >= 28 ? 16 : 0) : 0u;
    }
    if (tid < 224) reinterpret_cast<uint32_t*>(sg + OFF_B1)[tid] = bv << 16;
    mbar_wait(barX + c * 8, 0);
    STAMP(25);
#pragma unroll
    for (int j = 0; j < 7; j++) {
      const int ci = 7 * r + j;
      const uint32_t a = abuf + (ci >> 3) * 8192 + (w * 16 + g) * 128 + (((ci & 7) ^ g) << 4) + t * 4;
      xs[j][0] = lds32(a); xs[j][1] = lds32(a + 1024);
    }
    __syncwarp();
#pragma unroll 1
    for (int hh = 0; hh < 2; hh++) {
      uint4* p = reinterpret_cast<uint4*>(sg + c * ABYTES + (w * 16 + hh * 8 + g) * 128) + t;
      uint4 v[14];
#pragma unroll
      for (int k = 0; k < 14; k++) v[k] = p[(k >> 1) * 512 + ((k ^ g) & 1) * 4];
      float a8[8] = {};
#pragma unroll
      for (int k = 0; k < 14; k++) {
        const uint32_t e[4] = {v[k].x, v[k].y, v[k].z, v[k].w};
#pragma unroll
        for (int z = 0; z < 4; z++) { a8[2 * z] += lo(e[z]); a8[2 * z + 1] += hi(e[z]); }
      }
      float sm = ((a8[0] + a8[1]) + (a8[2] + a8[3])) + ((a8[4] + a8[5]) + (a8[6] + a8[7]));
      sm += __shfl_xor_sync(~0u, sm, 1); sm += __shfl_xor_sync(~0u, sm, 2);
      sm *= 1.f / DM;
#pragma unroll
      for (int k = 0; k < 14; k++) {
        uint32_t e[4] = {v[k].x, v[k].y, v[k].z, v[k].w};
#pragma unroll
        for (int z = 0; z < 4; z++) {
          const float a = lo(e[z]) - sm, b = hi(e[z]) - sm;
          a8[2 * z] = fmaf(a, a, k ? a8[2 * z] : 0.f); a8[2 * z + 1] = fmaf(b, b, k ? a8[2 * z + 1] : 0.f);
          e[z] = pack(a, b);
        }
        p[(k >> 1) * 512 + ((k ^ g) & 1) * 4] = make_uint4(e[0], e[1], e[2], e[3]);
      }
      float q = ((a8[0] + a8[1]) + (a8[2] + a8[3])) + ((a8[4] + a8[5]) + (a8[6] + a8[7]));
      q += __shfl_xor_sync(~0u, q, 1); q += __shfl_xor_sync(~0u, q, 2);
      rstd[1] = rsqrtf(q * (1.f / DM) + 1e-5f);
      if (hh == 0) rstd[0] = rstd[1];
    }
    fence_async_smem();
    bar_sync<3, 256>();
    epoch = epoch / NCTA + 1;
    mean[0] = mean[1] = 0.f;
  }
  STAMP(0);
  Ring ring{barFull, barEmpty, sb + OFF_RING, 0, 0};
  int apar = 1;
  const uint32_t stsm_off = (w * 16 + ((lane >> 3) & 1) * 8 + (lane & 7)) * 128;
  const uint32_t stsm_hi = lane >> 4;
  const uint64_t dA = mkdesc(abuf, 1024, 128, 0);

  auto gather = [&](unsigned* fl, const unsigned char* img) {
    __syncwarp();
    if (lane == 0) {
      flag_arrive(fl);
      STAMP(27);
      flag_wait(fl, epoch * 32);
      STAMP(28);
      fence_async();
      mbar_expect(barAc + w * 8, 8192); bulk_ld(abuf + w * 8192, img + w * 8192, 8192, barAc + w * 8);
      if (w < 3) { mbar_expect(barAc + 32 + w * 8, 8192); bulk_ld(abuf + 32768 + w * 8192, img + 32768 + w * 8192, 8192, barAc + 32 + w * 8); }
    }
    __syncwarp();
    apar ^= 1;
  };
  auto slice_off = [&](int j, int hh) -> uint32_t {
    return (7 * r + j) * 1024 + (w * 2 + hh) * 128 + lane * 4;
  };
  auto load_stats = [&](const float2* st) {
    mbar_wait(barAc, apar);
#pragma unroll
    for (int hh = 0; hh < 2; hh++) su[hh] = ldcg4(st + (size_t)(row0 + w * 16 + hh * 8 + g) * 8 + 2 * t);
  };
  auto finish_stats = [&]() {
#pragma unroll
    for (int hh = 0; hh < 2; hh++) {
      const float m0 = __uint_as_float(su[hh].x), m1 = __uint_as_float(su[hh].z);
      float m = m0 + m1;
      m += __shfl_xor_sync(~0u, m, 1); m += __shfl_xor_sync(~0u, m, 2);
      m *= 0.125f;
      float q = __uint_as_float(su[hh].y) + __uint_as_float(su[hh].w) + 56.f * ((m0 - m) * (m0 - m) + (m1 - m) * (m1 - m));
      q += __shfl_xor_sync(~0u, q, 1); q += __shfl_xor_sync(~0u, q, 2);
      mean[hh] = m; rstd[hh] = rsqrtf(q * (1.f / DM) + 1e-5f);
    }
  };

#pragma unroll 1
  for (int lyr = 0; lyr < 2; lyr++) {
    const int layer = __shfl_sync(~0u, lyr, 0);
    unsigned* const fl = gFlag + (layer * 32 + G * 2 + c) * 7 * 32;
    uint32_t phiq[4][7];
    {
      float acc[92]; reg_def(acc);
      int prev = 0, prev2 = 0;
      ring.uniform();
      const uint64_t dQ = layer ? dA : mkdesc(abuf, 16, 1024, 1);
      const int kstep = layer ? 128 : 2;
      if (layer) load_stats(gStat + 2048 * 8);
#pragma unroll UNR
      for (int st = 0; st < 14; st++) {
        if (!(st & 1) && layer) mbar_wait(barAc + (st >> 1) * 8, apar);
        const uint64_t da = dQ + (st >> 1) * 512 + (st & 1) * 2 * kstep, db = mkdesc(ring.acquire(), 4096, 1024, 1);
        wg_fence();
        mma_ss_184(acc, da, db, 1);
        mma_ss_184(acc, da + kstep, db + 128, 1);
        wg_commit();
        if (st > 1) { wg_wait<2>(); ring.release(prev2, elect); }
        prev2 = prev; prev = ring.advance();
      }
      if (layer) {
        finish_stats();
#pragma unroll
        for (int j = 0; j < 7; j++) { xs[j][0] = lds32(abuf + slice_off(j, 0)); xs[j][1] = lds32(abuf + slice_off(j, 1)); }
      }
      wg_wait<0>(); reg_fence(acc);
      ring.release(prev2, elect); ring.release(prev, elect);
      STAMP(1 + layer * 12);
      uint32_t f[3][14];
      {
        const float2* cs = reinterpret_cast<const float2*>(sg + OFF_CS) + t;
        const float mr0 = -mean[0] * rstd[0], mr1 = -mean[1] * rstd[1];
#pragma unroll
        for (int p = 0; p < 3; p++)
#pragma unroll
          for (int j = 0; j < 7; j++) {
            const float2 s = cs[p * 32 + j * 4];
            const int b = p * 32 + j * 4;
            f[p][2 * j] = pack(fmaf(acc[b], rstd[0], s.x * mr0), fmaf(acc[b + 1], rstd[0], s.y * mr0));
            f[p][2 * j + 1] = pack(fmaf(acc[b + 2], rstd[1], s.x * mr1), fmaf(acc[b + 3], rstd[1], s.y * mr1));
          }
      }
      float pk[28], pq[28]; reg_def(pk); reg_def(pq);
      const uint64_t dW = mkdesc(sb + OFF_WPHI, 4096, 1024, 1);
      wg_fence();
#pragma unroll
      for (int s = 0; s < 4; s++) {
        mma_rs_56(pk, f[1][4 * s], f[1][4 * s + 1], s < 3 ? f[1][(4 * s + 2) % 14] : 0u, s < 3 ? f[1][(4 * s + 3) % 14] : 0u, dW + s * 128, s);
        mma_rs_56(pq, f[0][4 * s], f[0][4 * s + 1], s < 3 ? f[0][(4 * s + 2) % 14] : 0u, s < 3 ? f[0][(4 * s + 3) % 14] : 0u, dW + s * 128, s);
      }
      wg_commit();
      bar_wg(c);
      const uint32_t srow = abuf + stsm_off, ones = t == 0 ? 0x3F803F80u : 0u;
#pragma unroll
      for (int jp = 0; jp < 4; jp++)
        stsm4(srow + 16384 + (((2 * jp + stsm_hi) ^ (lane & 7)) << 4), f[2][4 * jp], f[2][4 * jp + 1],
              jp < 3 ? f[2][(4 * jp + 2) % 14] : ones, jp < 3 ? f[2][(4 * jp + 3) % 14] : ones);
      wg_wait<0>(); reg_fence(pk); reg_fence(pq);
#pragma unroll 1
      for (int pass = 0; pass < 2; pass++) {
        dual_softmax(pk, phiq);
        if (pass) break;
#pragma unroll
        for (int e = 0; e < 2; e++)
#pragma unroll
          for (int jp = 0; jp < 4; jp++)
            stsm4(srow + e * 8192 + (((2 * jp + stsm_hi) ^ (lane & 7)) << 4), phiq[e][2 * jp], phiq[2 + e][2 * jp],
                  jp < 3 ? phiq[e][(2 * jp + 1) % 7] : 0u, jp < 3 ? phiq[2 + e][(2 * jp + 1) % 7] : 0u);
        fence_async_smem();
        bar_sync<3, 256>();
        float kv[32], kw[32]; reg_def(kv); reg_def(kw);
        const uint64_t dP = mkdesc(sb + c * 8192, 4096, 1024, 1), dV = mkdesc(sb + 16384, 4096, 1024, 1);
        wg_fence();
#pragma unroll
        for (int s = 0; s < 4; s++) { mma_ss_64t(kv, dP + s * 128, dV + s * 128, s); mma_ss_64t(kw, dP + ABYTES / 16 + s * 128, dV + ABYTES / 16 + s * 128, s); }
        wg_commit();
        mbar_wait(barCS, 0);
        wg_wait<0>(); reg_fence(kv); reg_fence(kw);
#pragma unroll
        for (int i = 0; i < 32; i++) kv[i] += kw[i];
        float4* kvg = gKV + ((layer * 8 + r) * 2 + c) * 640 + (tid & 127);
#pragma unroll
        for (int i = 0; i < 5; i++) {
          float v0, v1, v2, v3;
          if (i == 4) { v0 = kv[28]; v1 = kv[29]; v2 = kv[30]; v3 = kv[31]; }
          else { v0 = c ? kv[12 + 4 * i] : kv[4 * i]; v1 = c ? kv[13 + 4 * i] : kv[1 + 4 * i]; v2 = c ? kv[14 + 4 * i] : kv[2 + 4 * i]; v3 = c ? kv[15 + 4 * i] : kv[3 + 4 * i]; }
          const bool use = i == 4 ? t == 0 : (i == 0 ? (c == 0 || t >= 2) : (i == 3 ? (c == 1 || t < 2) : true));
          if (use) asm volatile("red.relaxed.gpu.global.add.v4.f32 [%0], {%1,%2,%3,%4};" ::"l"(kvg + i * 128), "f"(v0), "f"(v1), "f"(v2), "f"(v3) : "memory");
        }
        __syncwarp();
        if (lane == 0) flag_arrive(gFlag + (FL_KV + layer * 8 + r) * 32);
        __syncwarp();
        STAMP(2 + layer * 12);
#pragma unroll
        for (int i = 0; i < 28; i++) pk[i] = pq[i];
      }
    }
    {
      if (elect) flag_wait(gFlag + (FL_KV + layer * 8 + r) * 32, epoch * 128);
      bar_wg(c);
      STAMP(3 + layer * 12);
      const float4* kvg = gKV + (layer * 8 + r) * 1280 + (tid & 127);
      uint4 kk[2][5];
#pragma unroll
      for (int e = 0; e < 2; e++)
#pragma unroll
        for (int i = 0; i < 5; i++) kk[e][i] = ldcg4(kvg + e * 640 + i * 128);
      const uint32_t srow = abuf + 24576 + stsm_off;
#pragma unroll
      for (int e = 0; e < 2; e++) {
        uint32_t f[8][2];
#pragma unroll
        for (int j = 0; j < 8; j++) { f[j][0] = 0u; f[j][1] = 0u; }
#pragma unroll
        for (int i = 0; i < 4; i++) {
          f[i + 3 * e][0] = pack(__uint_as_float(kk[e][i].x), __uint_as_float(kk[e][i].y));
          f[i + 3 * e][1] = pack(__uint_as_float(kk[e][i].z), __uint_as_float(kk[e][i].w));
        }
        f[7][0] = e ? pack(0.f, __uint_as_float(kk[e][4].y)) : pack(__uint_as_float(kk[e][4].x), 0.f);
        f[7][1] = e ? pack(0.f, __uint_as_float(kk[e][4].w)) : pack(__uint_as_float(kk[e][4].z), 0.f);
#pragma unroll
        for (int jp = 0; jp < 4; jp++)
          stsm4(srow + e * 8192 + (((2 * jp + stsm_hi) ^ (lane & 7)) << 4), f[2 * jp][0], f[2 * jp][1], f[2 * jp + 1][0], f[2 * jp + 1][1]);
      }
      fence_async_smem();
      bar_wg(c);
      float num[32], nub[32]; reg_def(num); reg_def(nub);
      const uint64_t dK = mkdesc(abuf + 24576, 4096, 1024, 1);
      wg_fence();
#pragma unroll
      for (int s = 0; s < 4; s++) {
        mma_rs_64(num, phiq[0][2 * s], phiq[2][2 * s], s < 3 ? phiq[0][(2 * s + 1) % 7] : 0u, s < 3 ? phiq[2][(2 * s + 1) % 7] : 0u, dK + s * 128, s);
        mma_rs_64(nub, phiq[1][2 * s], phiq[3][2 * s], s < 3 ? phiq[1][(2 * s + 1) % 7] : 0u, s < 3 ? phiq[3][(2 * s + 1) % 7] : 0u, dK + 512 + s * 128, s);
      }
      wg_commit();
      wg_wait<0>(); reg_fence(num); reg_fence(nub);
#pragma unroll
      for (int i = 12; i < 32; i++) num[i] += nub[i];
      float rd[4];
#pragma unroll
      for (int i = 0; i < 4; i++) rd[i] = __fdividef(1.f, __shfl_sync(~0u, num[28 + i], lane & ~3) + 1e-6f);
      unsigned char* img = gImg + (size_t)(G * 2 + c) * ABYTES;
#pragma unroll
      for (int j = 0; j < 7; j++) {
        const bool hb = j > 3 || (j == 3 && t >= 2);
        const float r0 = hb ? rd[1] : rd[0], r1 = hb ? rd[3] : rd[2];
        *reinterpret_cast<uint32_t*>(img + slice_off(j, 0)) = pack(num[4 * j] * r0, num[4 * j + 1] * r0);
        *reinterpret_cast<uint32_t*>(img + slice_off(j, 1)) = pack(num[4 * j + 2] * r1, num[4 * j + 3] * r1);
      }
      STAMP(4 + layer * 12);
      gather(fl, img);
      STAMP(5 + layer * 12);
    }
    {
      float acc[28], acc2[28]; reg_def(acc); reg_def(acc2); reg_fence(acc); reg_fence(acc2);
      int sl[4];
      ring.uniform();
#pragma unroll
      for (int st = 0; st < 4; st++) {
        const uint64_t db = mkdesc(ring.acquire(), 4096, 1024, 1);
        sl[st] = ring.advance();
#pragma unroll
        for (int s = 0; s < 7; s++) {
          const int ks = st * 7 + s;
          if (!(ks & 3)) mbar_wait(barAc + (ks >> 2) * 8, apar);
          if (!(ks & 3) || !s) wg_fence();
          if (ks & 1) mma_ss_56(acc2, dA + ks * 128, db + s * 128, ks > 1); else mma_ss_56(acc, dA + ks * 128, db + s * 128, ks > 1);
        }
        wg_commit();
      }
      wg_wait<0>(); reg_fence(acc); reg_fence(acc2);
      unsigned char* img = gImg + (size_t)(32 + G * 2 + c) * ABYTES;
#pragma unroll
      for (int hh = 0; hh < 2; hh++) {
        float s = 0.f, q = 0.f;
#pragma unroll
        for (int j = 0; j < 7; j++) {
          xs[j][hh] = pack(lo(xs[j][hh]) + (acc[4 * j + 2 * hh] + acc2[4 * j + 2 * hh]), hi(xs[j][hh]) + (acc[4 * j + 2 * hh + 1] + acc2[4 * j + 2 * hh + 1]));
          *reinterpret_cast<uint32_t*>(img + slice_off(j, hh)) = xs[j][hh];
          s += lo(xs[j][hh]) + hi(xs[j][hh]);
        }
        s += __shfl_xor_sync(~0u, s, 1); s += __shfl_xor_sync(~0u, s, 2);
        s *= 1.f / 56.f;
#pragma unroll
        for (int j = 0; j < 7; j++) { const float a = lo(xs[j][hh]) - s, b = hi(xs[j][hh]) - s; q = fmaf(a, a, q); q = fmaf(b, b, q); }
        q += __shfl_xor_sync(~0u, q, 1); q += __shfl_xor_sync(~0u, q, 2);
        if (t == 0) gStat[(size_t)(row0 + w * 16 + hh * 8 + g) * 8 + r] = make_float2(s, q);
      }
#pragma unroll
      for (int j = 0; j < 7; j++) xs[j][0] = xs[j][1] = 0u;
      STAMP(6 + layer * 12);
      gather(fl + 32, img);
#pragma unroll
      for (int st = 0; st < 4; st++) ring.release(sl[st], elect);
      STAMP(7 + layer * 12);
    }
    {
      uint32_t hf[28][2];
      {
        float acc[112]; reg_def(acc);
        int prev = 0, prev2 = 0;
        load_stats(gStat);
        ring.uniform();
#pragma unroll UNR
        for (int st = 0; st < 14; st++) {
          if (!(st & 1)) mbar_wait(barAc + (st >> 1) * 8, apar);
          const uint64_t da = dA + st * 256, db = mkdesc(ring.acquire(), 2048, 512, 2);
          wg_fence();
          mma_ss_224(acc, da, db, 1);
          mma_ss_224(acc, da + 128, db + 64, 1);
          wg_commit();
          if (st > 1) { wg_wait<2>(); ring.release(prev2, elect); }
          prev2 = prev; prev = ring.advance();
        }
        finish_stats();
        mbar_wait(barCS + 8, 0);
        wg_wait<0>(); reg_fence(acc);
        ring.release(prev2, elect); ring.release(prev, elect);
        STAMP(8 + layer * 12);
        const float2* bs = reinterpret_cast<const float2*>(sg + OFF_B1) + t;
        const float2* cs = reinterpret_cast<const float2*>(sg + OFF_CS + 768) + t;
        const float mr0 = -mean[0] * rstd[0], mr1 = -mean[1] * rstd[1];
#pragma unroll
        for (int j = 0; j < 28; j++) {
          const float2 b = bs[4 * j], s = cs[4 * j];
          hf[j][0] = relu_sq(fmaf(acc[4 * j], rstd[0], fmaf(s.x, mr0, b.x)), fmaf(acc[4 * j + 1], rstd[0], fmaf(s.y, mr0, b.y)));
          hf[j][1] = relu_sq(fmaf(acc[4 * j + 2], rstd[1], fmaf(s.x, mr1, b.x)), fmaf(acc[4 * j + 3], rstd[1], fmaf(s.y, mr1, b.y)));
        }
      }
      unsigned char* pdst = gP + (size_t)(((G * 2 + c) * 8 + 2 * w) * 8 + r) * 7168 + lane * 8;
      ring.uniform();
      float accA[32], accB[32]; reg_def(accA); reg_def(accB);
      int rel = ring.slot;
      auto issue = [&](float (&acc)[32]) {
        const uint64_t db0 = mkdesc(ring.acquire(), 4096, 1024, 1);
        ring.advance();
        const uint64_t db1 = mkdesc(ring.acquire(), 4096, 1024, 1);
        ring.advance();
        wg_fence();
#pragma unroll
        for (int ks = 0; ks < 14; ks++) mma_rs_64(acc, hf[2 * ks][0], hf[2 * ks][1], hf[2 * ks + 1][0], hf[2 * ks + 1][1], ks < 7 ? db0 + ks * 128 : db1 + (ks - 7) * 128, ks);
        wg_commit();
      };
      auto drain = [&](float (&acc)[32]) {
        reg_fence(acc);
        ring.release(rel, elect); if (++rel == NSLOT) rel = 0;
        ring.release(rel, elect); if (++rel == NSLOT) rel = 0;
#pragma unroll
        for (int i = 0; i < 8; i++) {
          const int b = (i >> 1) * 8 + (i & 1) * 2;
          *reinterpret_cast<uint2*>(pdst + (i & 1) * (8 * 7168) + (i >> 1) * 256) = make_uint2((pack(acc[b], acc[b + 1]) & ~1u) | (layer ^ 1), pack(acc[b + 4], acc[b + 5]));
        }
        pdst += 1024;
      };
      issue(accA);
#pragma unroll
      for (int ch = 0; ch < 3; ch++) {
        issue(accB); wg_wait<1>(); drain(accA);
        issue(accA); wg_wait<1>(); drain(accB);
      }
      wg_wait<0>(); drain(accA);
      STAMP(9 + layer * 12);
    }
    {
      uint32_t bx[14];
#pragma unroll
      for (int j = 0; j < 14; j++) bx[j] = __ldg(reinterpret_cast<const uint32_t*>(b2 + (j >> 1) * 64 + w * 16 + (j & 1) * 8 + 2 * t));
      const unsigned char* psrc = gP + (size_t)(((G * 2 + c) * 8 + r) * 8) * 7168 + w * 256 + lane * 8;
      unsigned char* img = gImg + (size_t)(64 + G * 2 + c) * ABYTES;
      uint2 pv[8][7] = {};
      uint32_t need = 0x7F;
#pragma unroll 1
      for (int n = 0; need && n < (1 << 16); n++) {
#pragma unroll
        for (int i = 0; i < 7; i++)
          if (need >> i & 1) {
#pragma unroll
            for (int s = 0; s < 8; s++) pv[s][i] = ldcg2(psrc + s * 7168 + i * 1024);
          }
        uint32_t bad = 0;
#pragma unroll
        for (int i = 0; i < 7; i++) {
          const uint32_t all = pv[0][i].x & pv[1][i].x & pv[2][i].x & pv[3][i].x & pv[4][i].x & pv[5][i].x & pv[6][i].x & pv[7][i].x;
          const uint32_t any = pv[0][i].x | pv[1][i].x | pv[2][i].x | pv[3][i].x | pv[4][i].x | pv[5][i].x | pv[6][i].x | pv[7][i].x;
          bad |= ((layer ? any : ~all) & 1u) << i;
        }
        need = __reduce_or_sync(~0u, bad);
      }
      STAMP(10 + layer * 12);
      const uint32_t off = w * 2048 + r * 128 + lane * 4;
      unsigned char* dst = layer ? reinterpret_cast<unsigned char*>(out + (size_t)(row0 + r * 8 + g) * DM + w * 16 + 2 * t) : img + off;
      float sm = 0.f, q = 0.f;
#pragma unroll
      for (int j = 0; j < 14; j++) {
        float y0 = lo(bx[j]), y1 = hi(bx[j]);
        const uint32_t xo = lds32(abuf + off + (j >> 1) * 8192 + (j & 1) * 1024);
        y0 += lo(xo); y1 += hi(xo);
#pragma unroll
        for (int s = 0; s < 8; s++) { const uint32_t u = (j & 1) ? pv[s][j >> 1].y : pv[s][j >> 1].x; y0 += lo(u); y1 += hi(u); }
        bx[j] = pack(y0, y1);
        *reinterpret_cast<uint32_t*>(dst + ((j >> 1) * 8 + (j & 1)) * (layer ? 16 : 1024)) = bx[j];
        sm += lo(bx[j]) + hi(bx[j]);
      }
      if (layer) break;
      sm += __shfl_xor_sync(~0u, sm, 1); sm += __shfl_xor_sync(~0u, sm, 2);
      sm *= 1.f / 112.f;
#pragma unroll
      for (int j = 0; j < 14; j++) { const float a = lo(bx[j]) - sm, b = hi(bx[j]) - sm; q = fmaf(a, a, q); q = fmaf(b, b, q); }
      q += __shfl_xor_sync(~0u, q, 1); q += __shfl_xor_sync(~0u, q, 2);
      if (t < 2) gStat[(size_t)(2048 + row0 + r * 8 + g) * 8 + 2 * w + t] = make_float2(sm, q * 0.5f);
      STAMP(11);
      gather(fl + 64, img);
      STAMP(12);
    }
  }
  STAMP(30);
  if (tid == 0) asm volatile("red.relaxed.gpu.global.add.u32 [%0], 1;" ::"l"(gFlag + FL_DONE * 32) : "memory");
  }
}

typedef CUresult (*EncFn)(CUtensorMap*, CUtensorMapDataType, cuuint32_t, void*, const cuuint64_t*, const cuuint64_t*,
                          const cuuint32_t*, const cuuint32_t*, CUtensorMapInterleave, CUtensorMapSwizzle,
                          CUtensorMapL2promotion, CUtensorMapFloatOOBfill);

void make_map(EncFn enc, CUtensorMap* m, void* p, int rank, uint64_t d0, uint64_t d1, uint64_t d2, uint64_t s1, uint64_t s2,
              uint32_t b0, uint32_t b1, uint32_t b2, CUtensorMapSwizzle sw) {
  cuuint64_t dims[3] = {d0, d1, d2}, strides[2] = {s1, s2};
  cuuint32_t box[3] = {b0, b1, b2}, es[3] = {1, 1, 1};
  enc(m, CU_TENSOR_MAP_DATA_TYPE_BFLOAT16, rank, p, dims, strides, box, es, CU_TENSOR_MAP_INTERLEAVE_NONE, sw,
      CU_TENSOR_MAP_L2_PROMOTION_L2_128B, CU_TENSOR_MAP_FLOAT_OOB_FILL_NONE);
}

}

extern "C" void kernel_launch(void* const* d_in, const int* in_sizes, int n_in, void* d_out, int out_size) {
  static EncFn enc = nullptr;
  if (!enc) {
    cudaDriverEntryPointQueryResult st;
    void* fn = nullptr;
    cudaGetDriverEntryPoint("cuTensorMapEncodeTiled", &fn, cudaEnableDefault, &st);
    enc = (EncFn)fn;
    cudaFuncSetAttribute(fused_kernel, cudaFuncAttributeMaxDynamicSharedMemorySize, SMEM_BYTES);
  }
  CUtensorMap mQKV, mWO, mW1, mW2, mX;
  make_map(enc, &mX, d_in[0], 2, 448, 2048, 1, 896, 0, 64, 64, 1, CU_TENSOR_MAP_SWIZZLE_128B);
  make_map(enc, &mQKV, d_in[1], 3, 448, 448, 3, 2688, 896, 64, 32, 3, CU_TENSOR_MAP_SWIZZLE_128B);
  make_map(enc, &mWO, d_in[3], 2, 448, 448, 1, 896, 0, 64, 112, 1, CU_TENSOR_MAP_SWIZZLE_128B);
  make_map(enc, &mW1, d_in[5], 3, 32, 448, 56, 3584, 64, 32, 32, 7, CU_TENSOR_MAP_SWIZZLE_64B);
  make_map(enc, &mW2, d_in[7], 2, 448, 1792, 1, 896, 0, 64, 112, 1, CU_TENSOR_MAP_SWIZZLE_128B);
  fused_kernel<<<NCTA, 384, SMEM_BYTES, cudaStreamPerThread>>>(
      mQKV, mWO, mW1, mW2, mX, (const __nv_bfloat16*)d_in[2], (const __nv_bfloat16*)d_in[6],
      (const __nv_bfloat16*)d_in[8], (const __nv_bfloat16*)d_in[1], (const __nv_bfloat16*)d_in[3], (const __nv_bfloat16*)d_in[5],
      (const __nv_bfloat16*)d_in[7], (__nv_bfloat16*)d_out);
}
```

```cpp
#include <cuda_runtime.h>
#include <cuda_bf16.h>
#include <cuda.h>
#include <stdint.h>

namespace {

constexpr int DM = 448, NCTA = 128;
constexpr int ABYTES = 57344;
constexpr int SLOT = 14336, NSLOT = 7;
constexpr int OFF_RING = 2 * ABYTES;
constexpr int OFF_WPHI = OFF_RING + NSLOT * SLOT;
constexpr int OFF_B1 = OFF_WPHI + 8192;
constexpr int OFF_CS = OFF_B1 + 896;
constexpr int OFF_BAR = OFF_CS + 1664;
constexpr int SMEM_BYTES = OFF_BAR + 272 + 1024;
constexpr int TILES_PER_LAYER = 46;

__device__ __align__(1024) unsigned char gP[16 * 2 * 8 * 8 * 7168];
__device__ __align__(1024) unsigned char gImg[3 * 32 * ABYTES];
__device__ __align__(1024) float2 gStat[2 * 2048 * 8];
__device__ __align__(1024) float4 gKV[2 * 8 * 2 * 5 * 128];
__device__ __align__(1024) float4 gCS[8 * 16 * 104];
__device__ __align__(128) unsigned gFlag[(2 * 32 * 7 + 32 + 1 + 16) * 32];
#define STAMP(i)

__device__ __forceinline__ uint32_t smem_u32(const void* p) { return (uint32_t)__cvta_generic_to_shared(p); }
__device__ __forceinline__ void mbar_init(uint32_t b, int c) { asm volatile("mbarrier.init.shared::cta.b64 [%0], %1;" ::"r"(b), "r"(c)); }
__device__ __forceinline__ void mbar_expect(uint32_t b, int bytes) { asm volatile("mbarrier.arrive.expect_tx.shared::cta.b64 _, [%0], %1;" ::"r"(b), "r"(bytes) : "memory"); }
__device__ __forceinline__ void mbar_arrive(uint32_t b) { asm volatile("mbarrier.arrive.shared::cta.b64 _, [%0];" ::"r"(b) : "memory"); }
__device__ __forceinline__ void mbar_wait(uint32_t b, int par) {
  uint32_t ok; int n = 0;
#pragma unroll 1
  while (true) {
    asm volatile("{.reg .pred p; mbarrier.try_wait.parity.shared::cta.b64 p, [%1], %2; selp.u32 %0,1,0,p;}" : "=r"(ok) : "r"(b), "r"(par) : "memory");
    if (ok) break;
    if (++n > (1 << 22)) break;
  }
}
__device__ __forceinline__ void flag_wait(const unsigned* f, unsigned target) {
  unsigned v; int n = 0;
#pragma unroll 1
  while (true) {
    asm volatile("ld.acquire.gpu.global.u32 %0, [%1];" : "=r"(v) : "l"(f) : "memory");
    if ((int)(v - target) >= 0) break;
    if (++n > (1 << 21)) break;
  }
}
__device__ __forceinline__ void flag_arrive(unsigned* f) { asm volatile("red.release.gpu.global.add.u32 [%0], 1;" ::"l"(f) : "memory"); }
__device__ __forceinline__ bool elect_one() {
  uint32_t p; asm volatile("{.reg .pred P; elect.sync _|P, 0xffffffff; selp.u32 %0, 1, 0, P;}" : "=r"(p)); return p;
}
__device__ __forceinline__ void fence_async() { asm volatile("fence.proxy.async.global;" ::: "memory"); }
__device__ __forceinline__ void fence_async_smem() { asm volatile("fence.proxy.async.shared::cta;" ::: "memory"); }
template <int ID, int N> __device__ __forceinline__ void bar_sync() { asm volatile("bar.sync %0, %1;" ::"n"(ID), "n"(N) : "memory"); }
__device__ __forceinline__ void bar_wg(int c) { if (c) bar_sync<2, 128>(); else bar_sync<1, 128>(); }
__device__ __forceinline__ void wg_fence() { asm volatile("wgmma.fence.sync.aligned;" ::: "memory"); }
__device__ __forceinline__ void wg_commit() { asm volatile("wgmma.commit_group.sync.aligned;" ::: "memory"); }
template <int N> __device__ __forceinline__ void wg_wait() { asm volatile("wgmma.wait_group.sync.aligned %0;" ::"n"(N) : "memory"); }
template <int N> __device__ __forceinline__ void reg_fence(float (&d)[N]) {
#pragma unroll
  for (int i = 0; i < N; i++) asm volatile("" : "+f"(d[i])::"memory");
}
template <int N> __device__ __forceinline__ void reg_def(float (&d)[N]) {
#pragma unroll
  for (int i = 0; i < N; i++) d[i] = 0.f;
}
__device__ __forceinline__ uint64_t mkdesc(uint32_t addr, uint32_t lbo, uint32_t sbo, uint64_t swz) {
  return (uint64_t)((addr & 0x3FFFF) >> 4) | ((uint64_t)(lbo >> 4) << 16) | ((uint64_t)(sbo >> 4) << 32) | (swz << 62);
}
__device__ __forceinline__ uint32_t pack(float a, float b) {
  uint32_t r; asm("cvt.rn.bf16x2.f32 %0, %1, %2;" : "=r"(r) : "f"(b), "f"(a)); return r;
}
__device__ __forceinline__ uint32_t relu_sq(float a, float b) {
  uint32_t r; asm("{.reg .b32 v; cvt.rn.relu.bf16x2.f32 v, %1, %2; mul.rn.bf16x2 %0, v, v;}" : "=r"(r) : "f"(b), "f"(a)); return r;
}
__device__ __forceinline__ float lo(uint32_t u) { return __uint_as_float(u << 16); }
__device__ __forceinline__ float hi(uint32_t u) { return __uint_as_float(u & 0xFFFF0000u); }
__device__ __forceinline__ float ex2(float x) { float y; asm("ex2.approx.ftz.f32 %0, %1;" : "=f"(y) : "f"(x)); return y; }
__device__ __forceinline__ void stsm4(uint32_t a, uint32_t r0, uint32_t r1, uint32_t r2, uint32_t r3) {
  asm volatile("stmatrix.sync.aligned.m8n8.x4.shared.b16 [%0], {%1,%2,%3,%4};" ::"r"(a), "r"(r0), "r"(r1), "r"(r2), "r"(r3) : "memory");
}
__device__ __forceinline__ void tma3(uint32_t dst, const CUtensorMap* m, int c0, int c1, int c2, uint32_t bar) {
  asm volatile("cp.async.bulk.tensor.3d.shared::cluster.global.mbarrier::complete_tx::bytes [%0], [%1, {%3,%4,%5}], [%2];"
               ::"r"(dst), "l"(m), "r"(bar), "r"(c0), "r"(c1), "r"(c2) : "memory");
}
__device__ __forceinline__ void tma2(uint32_t dst, const CUtensorMap* m, int c0, int c1, uint32_t bar) {
  asm volatile("cp.async.bulk.tensor.2d.shared::cluster.global.mbarrier::complete_tx::bytes [%0], [%1, {%3,%4}], [%2];"
               ::"r"(dst), "l"(m), "r"(bar), "r"(c0), "r"(c1) : "memory");
}
__device__ __forceinline__ uint32_t lds32(uint32_t a) { uint32_t v; asm volatile("ld.shared.u32 %0, [%1];" : "=r"(v) : "r"(a) : "memory"); return v; }
__device__ __forceinline__ void bulk_ld(uint32_t dst, const void* src, int bytes, uint32_t bar) {
  asm volatile("cp.async.bulk.shared::cluster.global.mbarrier::complete_tx::bytes [%0], [%1], %2, [%3];" ::"r"(dst), "l"(src), "r"(bytes), "r"(bar) : "memory");
}
__device__ __forceinline__ uint4 ldcg4(const void* p) {
  uint4 v; asm volatile("ld.global.cg.v4.u32 {%0,%1,%2,%3}, [%4];" : "=r"(v.x), "=r"(v.y), "=r"(v.z), "=r"(v.w) : "l"(p) : "memory"); return v;
}

__device__ __forceinline__ uint2 ldcg2(const void* p) {
  uint2 v; asm volatile("ld.global.cg.v2.u32 {%0,%1}, [%2];" : "=r"(v.x), "=r"(v.y) : "l"(p) : "memory"); return v;
}

__device__ __forceinline__ void mma_ss_184(float (&d)[92], uint64_t da, uint64_t db, int acc) {
  asm volatile("{.reg .pred p; setp.ne.b32 p, %94, 0;\n"
    "wgmma.mma_async.sync.aligned.m64n184k16.f32.bf16.bf16 {%0,%1,%2,%3,%4,%5,%6,%7,%8,%9,%10,%11,%12,%13,%14,%15,%16,%17,%18,%19,%20,%21,%22,%23,%24,%25,%26,%27,%28,%29,%30,%31,%32,%33,%34,%35,%36,%37,%38,%39,%40,%41,%42,%43,%44,%45,%46,%47,%48,%49,%50,%51,%52,%53,%54,%55,%56,%57,%58,%59,%60,%61,%62,%63,%64,%65,%66,%67,%68,%69,%70,%71,%72,%73,%74,%75,%76,%77,%78,%79,%80,%81,%82,%83,%84,%85,%86,%87,%88,%89,%90,%91}, %92, %93, p, 1, 1, 0, 1;}\n"
    : "+f"(d[0]),"+f"(d[1]),"+f"(d[2]),"+f"(d[3]),"+f"(d[4]),"+f"(d[5]),"+f"(d[6]),"+f"(d[7]),"+f"(d[8]),"+f"(d[9]),"+f"(d[10]),"+f"(d[11]),"+f"(d[12]),"+f"(d[13]),"+f"(d[14]),"+f"(d[15]),"+f"(d[16]),"+f"(d[17]),"+f"(d[18]),"+f"(d[19]),"+f"(d[20]),"+f"(d[21]),"+f"(d[22]),"+f"(d[23]),"+f"(d[24]),"+f"(d[25]),"+f"(d[26]),"+f"(d[27]),"+f"(d[28]),"+f"(d[29]),"+f"(d[30]),"+f"(d[31]),"+f"(d[32]),"+f"(d[33]),"+f"(d[34]),"+f"(d[35]),"+f"(d[36]),"+f"(d[37]),"+f"(d[38]),"+f"(d[39]),"+f"(d[40]),"+f"(d[41]),"+f"(d[42]),"+f"(d[43]),"+f"(d[44]),"+f"(d[45]),"+f"(d[46]),"+f"(d[47]),"+f"(d[48]),"+f"(d[49]),"+f"(d[50]),"+f"(d[51]),"+f"(d[52]),"+f"(d[53]),"+f"(d[54]),"+f"(d[55]),"+f"(d[56]),"+f"(d[57]),"+f"(d[58]),"+f"(d[59]),"+f"(d[60]),"+f"(d[61]),"+f"(d[62]),"+f"(d[63]),"+f"(d[64]),"+f"(d[65]),"+f"(d[66]),"+f"(d[67]),"+f"(d[68]),"+f"(d[69]),"+f"(d[70]),"+f"(d[71]),"+f"(d[72]),"+f"(d[73]),"+f"(d[74]),"+f"(d[75]),"+f"(d[76]),"+f"(d[77]),"+f"(d[78]),"+f"(d[79]),"+f"(d[80]),"+f"(d[81]),"+f"(d[82]),"+f"(d[83]),"+f"(d[84]),"+f"(d[85]),"+f"(d[86]),"+f"(d[87]),"+f"(d[88]),"+f"(d[89]),"+f"(d[90]),"+f"(d[91])
    : "l"(da), "l"(db), "r"(acc));
}
__device__ __forceinline__ void mma_ss_224(float (&d)[112], uint64_t da, uint64_t db, int acc) {
  asm volatile("{.reg .pred p; setp.ne.b32 p, %114, 0;\n"
    "wgmma.mma_async.sync.aligned.m64n224k16.f32.bf16.bf16 {%0,%1,%2,%3,%4,%5,%6,%7,%8,%9,%10,%11,%12,%13,%14,%15,%16,%17,%18,%19,%20,%21,%22,%23,%24,%25,%26,%27,%28,%29,%30,%31,%32,%33,%34,%35,%36,%37,%38,%39,%40,%41,%42,%43,%44,%45,%46,%47,%48,%49,%50,%51,%52,%53,%54,%55,%56,%57,%58,%59,%60,%61,%62,%63,%64,%65,%66,%67,%68,%69,%70,%71,%72,%73,%74,%75,%76,%77,%78,%79,%80,%81,%82,%83,%84,%85,%86,%87,%88,%89,%90,%91,%92,%93,%94,%95,%96,%97,%98,%99,%100,%101,%102,%103,%104,%105,%106,%107,%108,%109,%110,%111}, %112, %113, p, 1, 1, 0, 1;}\n"
    : "+f"(d[0]),"+f"(d[1]),"+f"(d[2]),"+f"(d[3]),"+f"(d[4]),"+f"(d[5]),"+f"(d[6]),"+f"(d[7]),"+f"(d[8]),"+f"(d[9]),"+f"(d[10]),"+f"(d[11]),"+f"(d[12]),"+f"(d[13]),"+f"(d[14]),"+f"(d[15]),"+f"(d[16]),"+f"(d[17]),"+f"(d[18]),"+f"(d[19]),"+f"(d[20]),"+f"(d[21]),"+f"(d[22]),"+f"(d[23]),"+f"(d[24]),"+f"(d[25]),"+f"(d[26]),"+f"(d[27]),"+f"(d[28]),"+f"(d[29]),"+f"(d[30]),"+f"(d[31]),"+f"(d[32]),"+f"(d[33]),"+f"(d[34]),"+f"(d[35]),"+f"(d[36]),"+f"(d[37]),"+f"(d[38]),"+f"(d[39]),"+f"(d[40]),"+f"(d[41]),"+f"(d[42]),"+f"(d[43]),"+f"(d[44]),"+f"(d[45]),"+f"(d[46]),"+f"(d[47]),"+f"(d[48]),"+f"(d[49]),"+f"(d[50]),"+f"(d[51]),"+f"(d[52]),"+f"(d[53]),"+f"(d[54]),"+f"(d[55]),"+f"(d[56]),"+f"(d[57]),"+f"(d[58]),"+f"(d[59]),"+f"(d[60]),"+f"(d[61]),"+f"(d[62]),"+f"(d[63]),"+f"(d[64]),"+f"(d[65]),"+f"(d[66]),"+f"(d[67]),"+f"(d[68]),"+f"(d[69]),"+f"(d[70]),"+f"(d[71]),"+f"(d[72]),"+f"(d[73]),"+f"(d[74]),"+f"(d[75]),"+f"(d[76]),"+f"(d[77]),"+f"(d[78]),"+f"(d[79]),"+f"(d[80]),"+f"(d[81]),"+f"(d[82]),"+f"(d[83]),"+f"(d[84]),"+f"(d[85]),"+f"(d[86]),"+f"(d[87]),"+f"(d[88]),"+f"(d[89]),"+f"(d[90]),"+f"(d[91]),"+f"(d[92]),"+f"(d[93]),"+f"(d[94]),"+f"(d[95]),"+f"(d[96]),"+f"(d[97]),"+f"(d[98]),"+f"(d[99]),"+f"(d[100]),"+f"(d[101]),"+f"(d[102]),"+f"(d[103]),"+f"(d[104]),"+f"(d[105]),"+f"(d[106]),"+f"(d[107]),"+f"(d[108]),"+f"(d[109]),"+f"(d[110]),"+f"(d[111])
    : "l"(da), "l"(db), "r"(acc));
}
__device__ __forceinline__ void mma_ss_56(float (&d)[28], uint64_t da, uint64_t db, int acc) {
  asm volatile("{.reg .pred p; setp.ne.b32 p, %30, 0;\n"
    "wgmma.mma_async.sync.aligned.m64n56k16.f32.bf16.bf16 {%0,%1,%2,%3,%4,%5,%6,%7,%8,%9,%10,%11,%12,%13,%14,%15,%16,%17,%18,%19,%20,%21,%22,%23,%24,%25,%26,%27}, %28, %29, p, 1, 1, 0, 1;}\n"
    : "+f"(d[0]),"+f"(d[1]),"+f"(d[2]),"+f"(d[3]),"+f"(d[4]),"+f"(d[5]),"+f"(d[6]),"+f"(d[7]),"+f"(d[8]),"+f"(d[9]),"+f"(d[10]),"+f"(d[11]),"+f"(d[12]),"+f"(d[13]),"+f"(d[14]),"+f"(d[15]),"+f"(d[16]),"+f"(d[17]),"+f"(d[18]),"+f"(d[19]),"+f"(d[20]),"+f"(d[21]),"+f"(d[22]),"+f"(d[23]),"+f"(d[24]),"+f"(d[25]),"+f"(d[26]),"+f"(d[27])
    : "l"(da), "l"(db), "r"(acc));
}
__device__ __forceinline__ void mma_rs_56(float (&d)[28], uint32_t a0, uint32_t a1, uint32_t a2, uint32_t a3, uint64_t db, int acc) {
  asm volatile("{.reg .pred p; setp.ne.b32 p, %33, 0;\n"
    "wgmma.mma_async.sync.aligned.m64n56k16.f32.bf16.bf16 {%0,%1,%2,%3,%4,%5,%6,%7,%8,%9,%10,%11,%12,%13,%14,%15,%16,%17,%18,%19,%20,%21,%22,%23,%24,%25,%26,%27}, {%28,%29,%30,%31}, %32, p, 1, 1, 1;}\n"
    : "+f"(d[0]),"+f"(d[1]),"+f"(d[2]),"+f"(d[3]),"+f"(d[4]),"+f"(d[5]),"+f"(d[6]),"+f"(d[7]),"+f"(d[8]),"+f"(d[9]),"+f"(d[10]),"+f"(d[11]),"+f"(d[12]),"+f"(d[13]),"+f"(d[14]),"+f"(d[15]),"+f"(d[16]),"+f"(d[17]),"+f"(d[18]),"+f"(d[19]),"+f"(d[20]),"+f"(d[21]),"+f"(d[22]),"+f"(d[23]),"+f"(d[24]),"+f"(d[25]),"+f"(d[26]),"+f"(d[27])
    : "r"(a0), "r"(a1), "r"(a2), "r"(a3), "l"(db), "r"(acc));
}
__device__ __forceinline__ void mma_ss_64t(float (&d)[32], uint64_t da, uint64_t db, int acc) {
  asm volatile("{.reg .pred p; setp.ne.b32 p, %34, 0;\n"
    "wgmma.mma_async.sync.aligned.m64n64k16.f32.bf16.bf16 {%0,%1,%2,%3,%4,%5,%6,%7,%8,%9,%10,%11,%12,%13,%14,%15,%16,%17,%18,%19,%20,%21,%22,%23,%24,%25,%26,%27,%28,%29,%30,%31}, %32, %33, p, 1, 1, 1, 1;}\n"
    : "+f"(d[0]),"+f"(d[1]),"+f"(d[2]),"+f"(d[3]),"+f"(d[4]),"+f"(d[5]),"+f"(d[6]),"+f"(d[7]),"+f"(d[8]),"+f"(d[9]),"+f"(d[10]),"+f"(d[11]),"+f"(d[12]),"+f"(d[13]),"+f"(d[14]),"+f"(d[15]),"+f"(d[16]),"+f"(d[17]),"+f"(d[18]),"+f"(d[19]),"+f"(d[20]),"+f"(d[21]),"+f"(d[22]),"+f"(d[23]),"+f"(d[24]),"+f"(d[25]),"+f"(d[26]),"+f"(d[27]),"+f"(d[28]),"+f"(d[29]),"+f"(d[30]),"+f"(d[31])
    : "l"(da), "l"(db), "r"(acc));
}
__device__ __forceinline__ void mma_rs_64(float (&d)[32], uint32_t a0, uint32_t a1, uint32_t a2, uint32_t a3, uint64_t db, int acc) {
  asm volatile("{.reg .pred p; setp.ne.b32 p, %37, 0;\n"
    "wgmma.mma_async.sync.aligned.m64n64k16.f32.bf16.bf16 {%0,%1,%2,%3,%4,%5,%6,%7,%8,%9,%10,%11,%12,%13,%14,%15,%16,%17,%18,%19,%20,%21,%22,%23,%24,%25,%26,%27,%28,%29,%30,%31}, {%32,%33,%34,%35}, %36, p, 1, 1, 1;}\n"
    : "+f"(d[0]),"+f"(d[1]),"+f"(d[2]),"+f"(d[3]),"+f"(d[4]),"+f"(d[5]),"+f"(d[6]),"+f"(d[7]),"+f"(d[8]),"+f"(d[9]),"+f"(d[10]),"+f"(d[11]),"+f"(d[12]),"+f"(d[13]),"+f"(d[14]),"+f"(d[15]),"+f"(d[16]),"+f"(d[17]),"+f"(d[18]),"+f"(d[19]),"+f"(d[20]),"+f"(d[21]),"+f"(d[22]),"+f"(d[23]),"+f"(d[24]),"+f"(d[25]),"+f"(d[26]),"+f"(d[27]),"+f"(d[28]),"+f"(d[29]),"+f"(d[30]),"+f"(d[31])
    : "r"(a0), "r"(a1), "r"(a2), "r"(a3), "l"(db), "r"(acc));
}

__device__ __forceinline__ void dual_softmax(const float (&p)[28], uint32_t (&phi)[4][7]) {
  constexpr float L2E = 1.4426950408889634f;
#pragma unroll
  for (int i = 0; i < 4; i++) {
    float mx = p[i], mn = p[i];
#pragma unroll
    for (int j = 1; j < 7; j++) { mx = fmaxf(mx, p[4 * j + i]); mn = fminf(mn, p[4 * j + i]); }
    mx = fmaxf(mx, __shfl_xor_sync(~0u, mx, 1)); mn = fminf(mn, __shfl_xor_sync(~0u, mn, 1));
    mx = fmaxf(mx, __shfl_xor_sync(~0u, mx, 2)); mn = fminf(mn, __shfl_xor_sync(~0u, mn, 2));
    float a[7], b[7], sa = 0.f, sb = 0.f;
    const float mxl = mx * L2E, mnl = mn * L2E;
#pragma unroll
    for (int j = 0; j < 7; j++) {
      a[j] = ex2(fmaf(p[4 * j + i], L2E, -mxl)); b[j] = ex2(fmaf(p[4 * j + i], -L2E, mnl));
      sa += a[j]; sb += b[j];
    }
    sa += __shfl_xor_sync(~0u, sa, 1); sb += __shfl_xor_sync(~0u, sb, 1);
    sa += __shfl_xor_sync(~0u, sa, 2); sb += __shfl_xor_sync(~0u, sb, 2);
    const float ra = __fdividef(1.f, sa), rb = __fdividef(1.f, sb);
#pragma unroll
    for (int j = 0; j < 7; j++) phi[i][j] = pack(a[j] * ra, b[j] * rb);
  }
}

struct Ring {
  uint32_t full, empty, base; int slot, par;
  __device__ __forceinline__ void uniform() { slot = __shfl_sync(~0u, slot, 0); par = __shfl_sync(~0u, par, 0); }
  __device__ __forceinline__ uint32_t acquire() { mbar_wait(full + slot * 8, par); return base + slot * SLOT; }
  __device__ __forceinline__ int advance() { int s = slot; if (++slot == NSLOT) { slot = 0; par ^= 1; } return s; }
  __device__ __forceinline__ void release(int s, bool elect) { if (elect) mbar_arrive(empty + s * 8); }
};
constexpr int UNR = 14;
constexpr int FL_KV = 448, FL_CS = FL_KV + 16, FL_DONE = FL_KV + 32;

__global__ void __launch_bounds__(384, 1)
fused_kernel(const __grid_constant__ CUtensorMap mQKV, const __grid_constant__ CUtensorMap mWO,
             const __grid_constant__ CUtensorMap mW1, const __grid_constant__ CUtensorMap mW2,
             const __grid_constant__ CUtensorMap mX, const __nv_bfloat16* __restrict__ wphi,
             const __nv_bfloat16* __restrict__ b1, const __nv_bfloat16* __restrict__ b2,
             const __nv_bfloat16* __restrict__ wqkv, const __nv_bfloat16* __restrict__ wo, const __nv_bfloat16* __restrict__ w1,
             const __nv_bfloat16* __restrict__ w2, __nv_bfloat16* __restrict__ out) {
  extern __shared__ unsigned char smem_raw[];
  const uint32_t sb = (smem_u32(smem_raw) + 1023) & ~1023u;
  unsigned char* sg = smem_raw + (sb - smem_u32(smem_raw));
  const int tid = threadIdx.x, lane = tid & 31;
  const int G = blockIdx.x >> 3, r = blockIdx.x & 7;
  const uint32_t barFull = sb + OFF_BAR, barEmpty = barFull + 56, barA = barEmpty + 56, barCS = barA + 112, barX = barCS + 16;
  const int warp = __shfl_sync(~0u, tid >> 5, 0);
  uint32_t wv[7], bv;
#pragma unroll
  for (int i = 0; i < 7; i++)
    wv[i] = __ldg(reinterpret_cast<const unsigned short*>(wphi) + (56 * r + i * 8 + (warp & 7)) * 28 + min(lane, 27));
  bv = __ldg(reinterpret_cast<const unsigned short*>(b1) + 224 * r + min(tid, 223));
  if (lane == 0) {
    if (warp >= 10) {
      const int cc = warp - 10;
      mbar_init(barX + cc * 8, 1);
      fence_async_smem();
      mbar_expect(barX + cc * 8, ABYTES);
#pragma unroll 1
      for (int k = 0; k < 7; k++) tma2(sb + cc * ABYTES + k * 8192, &mX, 64 * k, G * 128 + 64 * cc, barX + cc * 8);
    } else if (warp < 7) { mbar_init(barFull + warp * 8, 1); mbar_init(barEmpty + warp * 8, 2); mbar_init(barA + warp * 8, 1); mbar_init(barA + 56 + warp * 8, 1); }
    else if (warp < 9) mbar_init(barCS + (warp - 7) * 8, 96);
    else
      asm volatile("cp.async.bulk.prefetch.L2.global [%0], %1;" ::"l"((const char*)wqkv + blockIdx.x * 9408), "r"(9408) : "memory");
    asm volatile("fence.mbarrier_init.release.cluster;" ::: "memory");
  }
  if (tid < 192) reinterpret_cast<float*>(sg + OFF_CS)[tid] = 0.f;
  __syncthreads();
  const int wgid = warp >> 2;
  if (wgid == 2) {
    asm volatile("setmaxnreg.dec.sync.aligned.u32 40;");
    if (warp == 8) {
      int slot = 0, par = 1;
#pragma unroll 1
      for (int it = 0; it < 2 * TILES_PER_LAYER; it++) {
        const int i = it >= TILES_PER_LAYER ? it - TILES_PER_LAYER : it;
        mbar_wait(barEmpty + slot * 8, par);
        const uint32_t dst = sb + OFF_RING + slot * SLOT, fb = barFull + slot * 8;
        if (elect_one()) {
          mbar_expect(fb, i < 14 ? 12288 : SLOT);
          if (i < 14) tma3(dst, &mQKV, 56 * r, 32 * i, 0, fb);
          else if (i < 18) tma2(dst, &mWO, 56 * r, 112 * (i - 14), fb);
          else if (i < 32) tma3(dst, &mW1, 0, 32 * (i - 18), 7 * r, fb);
          else tma2(dst, &mW2, 64 * ((i - 32) >> 1), 224 * r + 112 * (i & 1), fb);
        }
        if (++slot == NSLOT) { slot = 0; par ^= 1; }
      }
    } else {
      unsigned ep;
      asm volatile("ld.relaxed.gpu.global.u32 %0, [%1];" : "=r"(ep) : "l"(gFlag + FL_DONE * 32) : "memory");
      const int idx = tid - 288;
      ep = (ep / NCTA + 1) * 3;
      if (G == 0) {
#pragma unroll 1
        for (int i = idx; i < 2 * 1280; i += 96) gKV[((i >= 1280) * 7 + r) * 1280 + i] = make_float4(0.f, 0.f, 0.f, 0.f);
        __syncwarp();
        if (lane == 0) flag_arrive(gFlag + (FL_CS + r) * 32);
      }
      mbar_wait(barFull + 48, 0); mbar_wait(barFull + 48, 1);
      if (idx < 2) {
        const char* pf = idx ? (const char*)w2 + blockIdx.x * 12544 : (const char*)wo + blockIdx.x * 3136;
        asm volatile("cp.async.bulk.prefetch.L2.global [%0], %1;" ::"l"(pf), "r"(idx ? 12544 : 3136) : "memory");
      }
      if (lane == 0) flag_wait(gFlag + (FL_CS + r) * 32, ep);
      __syncwarp();
      mbar_arrive(barCS);
#pragma unroll 1
      for (int ps = 0; ps < 3; ps++) {
        const int nch = ps ? 14 : 21, ch = min(idx >> 2, nch - 1), p = ch / 7, k0 = G * 28 + (idx & 3) * 7;
        const uint4* src = ps ? reinterpret_cast<const uint4*>(w1 + (size_t)k0 * 1792 + 224 * r) + (ps - 1) * 14 + ch
                              : reinterpret_cast<const uint4*>(wqkv + (size_t)k0 * 1344 + p * 448 + 56 * r) + (ch - 7 * p);
        uint4 cu[7];
#pragma unroll
        for (int i = 0; i < 7; i++) cu[i] = __ldg(src + i * (ps ? 224 : 168));
        float s[8] = {};
#pragma unroll
        for (int i = 0; i < 7; i++) { s[0] += lo(cu[i].x); s[1] += hi(cu[i].x); s[2] += lo(cu[i].y); s[3] += hi(cu[i].y); s[4] += lo(cu[i].z); s[5] += hi(cu[i].z); s[6] += lo(cu[i].w); s[7] += hi(cu[i].w); }
#pragma unroll
        for (int i = 0; i < 8; i++) { s[i] += __shfl_xor_sync(~0u, s[i], 1); s[i] += __shfl_xor_sync(~0u, s[i], 2); }
        if ((idx & 3) < 2 && idx < nch * 4) gCS[(r * 16 + G) * 104 + (ps ? 10 + ps * 14 + ch : ch + p) * 2 + (idx & 1)] = (idx & 1) ? make_float4(s[4], s[5], s[6], s[7]) : make_float4(s[0], s[1], s[2], s[3]);
      }
      __syncwarp();
      if (lane == 0) { flag_arrive(gFlag + (FL_CS + 8 + r) * 32); flag_wait(gFlag + (FL_CS + 8 + r) * 32, ep * 16); }
      __syncwarp();
#pragma unroll 1
      for (int j = idx; j < 208; j += 96) {
        float2 a = make_float2(0.f, 0.f);
#pragma unroll 8
        for (int i = 0; i < 16; i++) { const float2 v = __ldcg(reinterpret_cast<const float2*>(gCS + (r * 16 + i) * 104) + j); a.x += v.x; a.y += v.y; }
        reinterpret_cast<float2*>(sg + OFF_CS)[j] = a;
      }
      mbar_arrive(barCS + 8);
    }
  } else {
  asm volatile("setmaxnreg.inc.sync.aligned.u32 232;");
  const int c = wgid, w = warp & 3, g = lane >> 2, t = lane & 3;
  int elect_i = (tid & 127) == 0;
  asm volatile("" : "+r"(elect_i));
  const bool elect = elect_i;
  const uint32_t abuf = sb + c * ABYTES, barAc = barA + c * 56;
  const int row0 = G * 128 + c * 64;
  unsigned epoch;
  asm volatile("ld.relaxed.gpu.global.u32 %0, [%1];" : "=r"(epoch) : "l"(gFlag + FL_DONE * 32) : "memory");
  STAMP(24);
  float mean[2], rstd[2] = {0.f, 0.f};
  uint4 su[2] = {};
  uint32_t xs[7][2];
  {
#pragma unroll
    for (int i = 0; i < 8; i++) {
      const int k = i * 8 + (tid >> 5);
      *reinterpret_cast<uint32_t*>(sg + OFF_WPHI + k * 128 + ((g ^ (k & 7)) << 4) + t * 4) = (i < 7 && lane < 28) ? wv[i % 7] << (k >= 28 ? 16 : 0) : 0u;
    }
    if (tid < 224) reinterpret_cast<uint32_t*>(sg + OFF_B1)[tid] = bv << 16;
    mbar_wait(barX + c * 8, 0);
    STAMP(25);
#pragma unroll
    for (int j = 0; j < 7; j++) {
      const int ci = 7 * r + j;
      const uint32_t a = abuf + (ci >> 3) * 8192 + (w * 16 + g) * 128 + (((ci & 7) ^ g) << 4) + t * 4;
      xs[j][0] = lds32(a); xs[j][1] = lds32(a + 1024);
    }
    __syncwarp();
#pragma unroll 1
    for (int hh = 0; hh < 2; hh++) {
      uint4* p = reinterpret_cast<uint4*>(sg + c * ABYTES + (w * 16 + hh * 8 + g) * 128) + t;
      uint4 v[14];
#pragma unroll
      for (int k = 0; k < 14; k++) v[k] = p[(k >> 1) * 512 + ((k ^ g) & 1) * 4];
      float a8[8] = {};
#pragma unroll
      for (int k = 0; k < 14; k++) {
        const uint32_t e[4] = {v[k].x, v[k].y, v[k].z, v[k].w};
#pragma unroll
        for (int z = 0; z < 4; z++) { a8[2 * z] += lo(e[z]); a8[2 * z + 1] += hi(e[z]); }
      }
      float sm = ((a8[0] + a8[1]) + (a8[2] + a8[3])) + ((a8[4] + a8[5]) + (a8[6] + a8[7]));
      sm += __shfl_xor_sync(~0u, sm, 1); sm += __shfl_xor_sync(~0u, sm, 2);
      sm *= 1.f / DM;
#pragma unroll
      for (int k = 0; k < 14; k++) {
        uint32_t e[4] = {v[k].x, v[k].y, v[k].z, v[k].w};
#pragma unroll
        for (int z = 0; z < 4; z++) {
          const float a = lo(e[z]) - sm, b = hi(e[z]) - sm;
          a8[2 * z] = fmaf(a, a, k ? a8[2 * z] : 0.f); a8[2 * z + 1] = fmaf(b, b, k ? a8[2 * z + 1] : 0.f);
          e[z] = pack(a, b);
        }
        p[(k >> 1) * 512 + ((k ^ g) & 1) * 4] = make_uint4(e[0], e[1], e[2], e[3]);
      }
      float q = ((a8[0] + a8[1]) + (a8[2] + a8[3])) + ((a8[4] + a8[5]) + (a8[6] + a8[7]));
      q += __shfl_xor_sync(~0u, q, 1); q += __shfl_xor_sync(~0u, q, 2);
      rstd[1] = rsqrtf(q * (1.f / DM) + 1e-5f);
      if (hh == 0) rstd[0] = rstd[1];
    }
    fence_async_smem();
    bar_sync<3, 256>();
    epoch = epoch / NCTA + 1;
    mean[0] = mean[1] = 0.f;
  }
  STAMP(0);
  Ring ring{barFull, barEmpty, sb + OFF_RING, 0, 0};
  int apar = 1;
  const uint32_t stsm_off = (w * 16 + ((lane >> 3) & 1) * 8 + (lane & 7)) * 128;
  const uint32_t stsm_hi = lane >> 4;
  const uint64_t dA = mkdesc(abuf, 1024, 128, 0);

  auto gather = [&](unsigned* fl, const unsigned char* img) {
    __syncwarp();
    if (lane == 0) {
      flag_arrive(fl);
      STAMP(27);
      flag_wait(fl, epoch * 32);
      STAMP(28);
      fence_async();
      mbar_expect(barAc + w * 8, 8192); bulk_ld(abuf + w * 8192, img + w * 8192, 8192, barAc + w * 8);
      if (w < 3) { mbar_expect(barAc + 32 + w * 8, 8192); bulk_ld(abuf + 32768 + w * 8192, img + 32768 + w * 8192, 8192, barAc + 32 + w * 8); }
    }
    __syncwarp();
    apar ^= 1;
  };
  auto slice_off = [&](int j, int hh) -> uint32_t {
    return (7 * r + j) * 1024 + (w * 2 + hh) * 128 + lane * 4;
  };
  auto load_stats = [&](const float2* st) {
    mbar_wait(barAc, apar);
#pragma unroll
    for (int hh = 0; hh < 2; hh++) su[hh] = ldcg4(st + (size_t)(row0 + w * 16 + hh * 8 + g) * 8 + 2 * t);
  };
  auto finish_stats = [&]() {
#pragma unroll
    for (int hh = 0; hh < 2; hh++) {
      const float m0 = __uint_as_float(su[hh].x), m1 = __uint_as_float(su[hh].z);
      float m = m0 + m1;
      m += __shfl_xor_sync(~0u, m, 1); m += __shfl_xor_sync(~0u, m, 2);
      m *= 0.125f;
      float q = __uint_as_float(su[hh].y) + __uint_as_float(su[hh].w) + 56.f * ((m0 - m) * (m0 - m) + (m1 - m) * (m1 - m));
      q += __shfl_xor_sync(~0u, q, 1); q += __shfl_xor_sync(~0u, q, 2);
      mean[hh] = m; rstd[hh] = rsqrtf(q * (1.f / DM) + 1e-5f);
    }
  };

#pragma unroll 1
  for (int lyr = 0; lyr < 2; lyr++) {
    const int layer = __shfl_sync(~0u, lyr, 0);
    unsigned* const fl = gFlag + (layer * 32 + G * 2 + c) * 7 * 32;
    uint32_t phiq[4][7];
    {
      float acc[92]; reg_def(acc);
      int prev = 0, prev2 = 0;
      ring.uniform();
      const uint64_t dQ = layer ? dA : mkdesc(abuf, 16, 1024, 1);
      const int kstep = layer ? 128 : 2;
      if (layer) load_stats(gStat + 2048 * 8);
#pragma unroll UNR
      for (int st = 0; st < 14; st++) {
        if (!(st & 1) && layer) mbar_wait(barAc + (st >> 1) * 8, apar);
        const uint64_t da = dQ + (st >> 1) * 512 + (st & 1) * 2 * kstep, db = mkdesc(ring.acquire(), 4096, 1024, 1);
        wg_fence();
        mma_ss_184(acc, da, db, 1);
        mma_ss_184(acc, da + kstep, db + 128, 1);
        wg_commit();
        if (st > 1) { wg_wait<2>(); ring.release(prev2, elect); }
        prev2 = prev; prev = ring.advance();
      }
      if (layer) {
        finish_stats();
#pragma unroll
        for (int j = 0; j < 7; j++) { xs[j][0] = lds32(abuf + slice_off(j, 0)); xs[j][1] = lds32(abuf + slice_off(j, 1)); }
      }
      wg_wait<0>(); reg_fence(acc);
      ring.release(prev2, elect); ring.release(prev, elect);
      STAMP(1 + layer * 12);
      uint32_t f[3][14];
      {
        const float2* cs = reinterpret_cast<const float2*>(sg + OFF_CS) + t;
        const float mr0 = -mean[0] * rstd[0], mr1 = -mean[1] * rstd[1];
#pragma unroll
        for (int p = 0; p < 3; p++)
#pragma unroll
          for (int j = 0; j < 7; j++) {
            const float2 s = cs[p * 32 + j * 4];
            const int b = p * 32 + j * 4;
            f[p][2 * j] = pack(fmaf(acc[b], rstd[0], s.x * mr0), fmaf(acc[b + 1], rstd[0], s.y * mr0));
            f[p][2 * j + 1] = pack(fmaf(acc[b + 2], rstd[1], s.x * mr1), fmaf(acc[b + 3], rstd[1], s.y * mr1));
          }
      }
      float pk[28], pq[28]; reg_def(pk); reg_def(pq);
      const uint64_t dW = mkdesc(sb + OFF_WPHI, 4096, 1024, 1);
      wg_fence();
#pragma unroll
      for (int s = 0; s < 4; s++) {
        mma_rs_56(pk, f[1][4 * s], f[1][4 * s + 1], s < 3 ? f[1][(4 * s + 2) % 14] : 0u, s < 3 ? f[1][(4 * s + 3) % 14] : 0u, dW + s * 128, s);
        mma_rs_56(pq, f[0][4 * s], f[0][4 * s + 1], s < 3 ? f[0][(4 * s + 2) % 14] : 0u, s < 3 ? f[0][(4 * s + 3) % 14] : 0u, dW + s * 128, s);
      }
      wg_commit();
      bar_wg(c);
      const uint32_t srow = abuf + stsm_off, ones = t == 0 ? 0x3F803F80u : 0u;
#pragma unroll
      for (int jp = 0; jp < 4; jp++)
        stsm4(srow + 16384 + (((2 * jp + stsm_hi) ^ (lane & 7)) << 4), f[2][4 * jp], f[2][4 * jp + 1],
              jp < 3 ? f[2][(4 * jp + 2) % 14] : ones, jp < 3 ? f[2][(4 * jp + 3) % 14] : ones);
      wg_wait<0>(); reg_fence(pk); reg_fence(pq);
#pragma unroll 1
      for (int pass = 0; pass < 2; pass++) {
        dual_softmax(pk, phiq);
        if (pass) break;
#pragma unroll
        for (int e = 0; e < 2; e++)
#pragma unroll
          for (int jp = 0; jp < 4; jp++)
            stsm4(srow + e * 8192 + (((2 * jp + stsm_hi) ^ (lane & 7)) << 4), phiq[e][2 * jp], phiq[2 + e][2 * jp],
                  jp < 3 ? phiq[e][(2 * jp + 1) % 7] : 0u, jp < 3 ? phiq[2 + e][(2 * jp + 1) % 7] : 0u);
        fence_async_smem();
        bar_sync<3, 256>();
        float kv[32], kw[32]; reg_def(kv); reg_def(kw);
        const uint64_t dP = mkdesc(sb + c * 8192, 4096, 1024, 1), dV = mkdesc(sb + 16384, 4096, 1024, 1);
        wg_fence();
#pragma unroll
        for (int s = 0; s < 4; s++) { mma_ss_64t(kv, dP + s * 128, dV + s * 128, s); mma_ss_64t(kw, dP + ABYTES / 16 + s * 128, dV + ABYTES / 16 + s * 128, s); }
        wg_commit();
        mbar_wait(barCS, 0);
        wg_wait<0>(); reg_fence(kv); reg_fence(kw);
#pragma unroll
        for (int i = 0; i < 32; i++) kv[i] += kw[i];
        float4* kvg = gKV + ((layer * 8 + r) * 2 + c) * 640 + (tid & 127);
#pragma unroll
        for (int i = 0; i < 5; i++) {
          float v0, v1, v2, v3;
          if (i == 4) { v0 = kv[28]; v1 = kv[29]; v2 = kv[30]; v3 = kv[31]; }
          else { v0 = c ? kv[12 + 4 * i] : kv[4 * i]; v1 = c ? kv[13 + 4 * i] : kv[1 + 4 * i]; v2 = c ? kv[14 + 4 * i] : kv[2 + 4 * i]; v3 = c ? kv[15 + 4 * i] : kv[3 + 4 * i]; }
          const bool use = i == 4 ? t == 0 : (i == 0 ? (c == 0 || t >= 2) : (i == 3 ? (c == 1 || t < 2) : true));
          if (use) asm volatile("red.relaxed.gpu.global.add.v4.f32 [%0], {%1,%2,%3,%4};" ::"l"(kvg + i * 128), "f"(v0), "f"(v1), "f"(v2), "f"(v3) : "memory");
        }
        __syncwarp();
        if (lane == 0) flag_arrive(gFlag + (FL_KV + layer * 8 + r) * 32);
        __syncwarp();
        STAMP(2 + layer * 12);
#pragma unroll
        for (int i = 0; i < 28; i++) pk[i] = pq[i];
      }
    }
    {
      if (elect) flag_wait(gFlag + (FL_KV + layer * 8 + r) * 32, epoch * 128);
      bar_wg(c);
      STAMP(3 + layer * 12);
      const float4* kvg = gKV + (layer * 8 + r) * 1280 + (tid & 127);
      uint4 kk[2][5];
#pragma unroll
      for (int e = 0; e < 2; e++)
#pragma unroll
        for (int i = 0; i < 5; i++) kk[e][i] = ldcg4(kvg + e * 640 + i * 128);
      const uint32_t srow = abuf + 24576 + stsm_off;
#pragma unroll
      for (int e = 0; e < 2; e++) {
        uint32_t f[8][2];
#pragma unroll
        for (int j = 0; j < 8; j++) { f[j][0] = 0u; f[j][1] = 0u; }
#pragma unroll
        for (int i = 0; i < 4; i++) {
          f[i + 3 * e][0] = pack(__uint_as_float(kk[e][i].x), __uint_as_float(kk[e][i].y));
          f[i + 3 * e][1] = pack(__uint_as_float(kk[e][i].z), __uint_as_float(kk[e][i].w));
        }
        f[7][0] = e ? pack(0.f, __uint_as_float(kk[e][4].y)) : pack(__uint_as_float(kk[e][4].x), 0.f);
        f[7][1] = e ? pack(0.f, __uint_as_float(kk[e][4].w)) : pack(__uint_as_float(kk[e][4].z), 0.f);
#pragma unroll
        for (int jp = 0; jp < 4; jp++)
          stsm4(srow + e * 8192 + (((2 * jp + stsm_hi) ^ (lane & 7)) << 4), f[2 * jp][0], f[2 * jp][1], f[2 * jp + 1][0], f[2 * jp + 1][1]);
      }
      fence_async_smem();
      bar_wg(c);
      float num[32], nub[32]; reg_def(num); reg_def(nub);
      const uint64_t dK = mkdesc(abuf + 24576, 4096, 1024, 1);
      wg_fence();
#pragma unroll
      for (int s = 0; s < 4; s++) {
        mma_rs_64(num, phiq[0][2 * s], phiq[2][2 * s], s < 3 ? phiq[0][(2 * s + 1) % 7] : 0u, s < 3 ? phiq[2][(2 * s + 1) % 7] : 0u, dK + s * 128, s);
        mma_rs_64(nub, phiq[1][2 * s], phiq[3][2 * s], s < 3 ? phiq[1][(2 * s + 1) % 7] : 0u, s < 3 ? phiq[3][(2 * s + 1) % 7] : 0u, dK + 512 + s * 128, s);
      }
      wg_commit();
      wg_wait<0>(); reg_fence(num); reg_fence(nub);
#pragma unroll
      for (int i = 12; i < 32; i++) num[i] += nub[i];
      float rd[4];
#pragma unroll
      for (int i = 0; i < 4; i++) rd[i] = __fdividef(1.f, __shfl_sync(~0u, num[28 + i], lane & ~3) + 1e-6f);
      unsigned char* img = gImg + (size_t)(G * 2 + c) * ABYTES;
#pragma unroll
      for (int j = 0; j < 7; j++) {
        const bool hb = j > 3 || (j == 3 && t >= 2);
        const float r0 = hb ? rd[1] : rd[0], r1 = hb ? rd[3] : rd[2];
        *reinterpret_cast<uint32_t*>(img + slice_off(j, 0)) = pack(num[4 * j] * r0, num[4 * j + 1] * r0);
        *reinterpret_cast<uint32_t*>(img + slice_off(j, 1)) = pack(num[4 * j + 2] * r1, num[4 * j + 3] * r1);
      }
      STAMP(4 + layer * 12);
      gather(fl, img);
      STAMP(5 + layer * 12);
    }
    {
      float acc[28], acc2[28]; reg_def(acc); reg_def(acc2); reg_fence(acc); reg_fence(acc2);
      int sl[4];
      ring.uniform();
#pragma unroll
      for (int st = 0; st < 4; st++) {
        const uint64_t db = mkdesc(ring.acquire(), 4096, 1024, 1);
        sl[st] = ring.advance();
#pragma unroll
        for (int s = 0; s < 7; s++) {
          const int ks = st * 7 + s;
          if (!(ks & 3)) mbar_wait(barAc + (ks >> 2) * 8, apar);
          if (!(ks & 3) || !s) wg_fence();
          if (ks & 1) mma_ss_56(acc2, dA + ks * 128, db + s * 128, ks > 1); else mma_ss_56(acc, dA + ks * 128, db + s * 128, ks > 1);
        }
        wg_commit();
      }
      wg_wait<0>(); reg_fence(acc); reg_fence(acc2);
      unsigned char* img = gImg + (size_t)(32 + G * 2 + c) * ABYTES;
#pragma unroll
      for (int hh = 0; hh < 2; hh++) {
        float s = 0.f, q = 0.f;
#pragma unroll
        for (int j = 0; j < 7; j++) {
          xs[j][hh] = pack(lo(xs[j][hh]) + (acc[4 * j + 2 * hh] + acc2[4 * j + 2 * hh]), hi(xs[j][hh]) + (acc[4 * j + 2 * hh + 1] + acc2[4 * j + 2 * hh + 1]));
          *reinterpret_cast<uint32_t*>(img + slice_off(j, hh)) = xs[j][hh];
          s += lo(xs[j][hh]) + hi(xs[j][hh]);
        }
        s += __shfl_xor_sync(~0u, s, 1); s += __shfl_xor_sync(~0u, s, 2);
        s *= 1.f / 56.f;
#pragma unroll
        for (int j = 0; j < 7; j++) { const float a = lo(xs[j][hh]) - s, b = hi(xs[j][hh]) - s; q = fmaf(a, a, q); q = fmaf(b, b, q); }
        q += __shfl_xor_sync(~0u, q, 1); q += __shfl_xor_sync(~0u, q, 2);
        if (t == 0) gStat[(size_t)(row0 + w * 16 + hh * 8 + g) * 8 + r] = make_float2(s, q);
      }
#pragma unroll
      for (int j = 0; j < 7; j++) xs[j][0] = xs[j][1] = 0u;
      STAMP(6 + layer * 12);
      gather(fl + 32, img);
#pragma unroll
      for (int st = 0; st < 4; st++) ring.release(sl[st], elect);
      STAMP(7 + layer * 12);
    }
    {
      uint32_t hf[28][2];
      {
        float acc[112]; reg_def(acc);
        int prev = 0, prev2 = 0;
        load_stats(gStat);
        ring.uniform();
#pragma unroll UNR
        for (int st = 0; st < 14; st++) {
          if (!(st & 1)) mbar_wait(barAc + (st >> 1) * 8, apar);
          const uint64_t da = dA + st * 256, db = mkdesc(ring.acquire(), 2048, 512, 2);
          wg_fence();
          mma_ss_224(acc, da, db, 1);
          mma_ss_224(acc, da + 128, db + 64, 1);
          wg_commit();
          if (st > 1) { wg_wait<2>(); ring.release(prev2, elect); }
          prev2 = prev; prev = ring.advance();
        }
        finish_stats();
        mbar_wait(barCS + 8, 0);
        wg_wait<0>(); reg_fence(acc);
        ring.release(prev2, elect); ring.release(prev, elect);
        STAMP(8 + layer * 12);
        const float2* bs = reinterpret_cast<const float2*>(sg + OFF_B1) + t;
        const float2* cs = reinterpret_cast<const float2*>(sg + OFF_CS + 768) + t;
        const float mr0 = -mean[0] * rstd[0], mr1 = -mean[1] * rstd[1];
#pragma unroll
        for (int j = 0; j < 28; j++) {
          const float2 b = bs[4 * j], s = cs[4 * j];
          hf[j][0] = relu_sq(fmaf(acc[4 * j], rstd[0], fmaf(s.x, mr0, b.x)), fmaf(acc[4 * j + 1], rstd[0], fmaf(s.y, mr0, b.y)));
          hf[j][1] = relu_sq(fmaf(acc[4 * j + 2], rstd[1], fmaf(s.x, mr1, b.x)), fmaf(acc[4 * j + 3], rstd[1], fmaf(s.y, mr1, b.y)));
        }
      }
      unsigned char* pd[2]; int pstr[2];
#pragma unroll
      for (int hh = 0; hh < 2; hh++) {
        const bool own = 2 * w + hh == r;
        pd[hh] = own ? sg + c * ABYTES + (lane >> 4) * 1024 + (r ^ 1) * 128 + (lane & 15) * 8
                     : gP + (size_t)(((G * 2 + c) * 8 + 2 * w + hh) * 8 + r) * 7168 + lane * 8;
        pstr[hh] = own ? 2048 : 256;
      }
      uint2 pk[8] = {};
      ring.uniform();
#pragma unroll 1
      for (int ch = 0; ch < 7; ch++) {
        float acc[32], acc2[32]; reg_def(acc); reg_def(acc2);
        const uint64_t db0 = mkdesc(ring.acquire(), 4096, 1024, 1);
        const int sl0 = ring.advance();
        const uint64_t db1 = mkdesc(ring.acquire(), 4096, 1024, 1);
        const int sl1 = ring.advance();
        wg_fence();
#pragma unroll
        for (int s = 0; s < 7; s++) {
          mma_rs_64(acc, hf[2 * s][0], hf[2 * s][1], hf[2 * s + 1][0], hf[2 * s + 1][1], db0 + s * 128, s);
          mma_rs_64(acc2, hf[14 + 2 * s][0], hf[14 + 2 * s][1], hf[15 + 2 * s][0], hf[15 + 2 * s][1], db1 + s * 128, s);
        }
        wg_commit();
        if (ch > 0) {
#pragma unroll
          for (int i = 0; i < 8; i++) { *reinterpret_cast<uint2*>(pd[i & 1]) = pk[i]; pd[i & 1] += pstr[i & 1]; }
        }
        wg_wait<0>(); reg_fence(acc); reg_fence(acc2); ring.release(sl0, elect); ring.release(sl1, elect);
#pragma unroll
        for (int i = 0; i < 8; i++) {
          const int b = (i >> 1) * 8 + (i & 1) * 2;
          pk[i] = make_uint2((pack(acc[b] + acc2[b], acc[b + 1] + acc2[b + 1]) & ~1u) | (layer ^ 1), pack(acc[b + 4] + acc2[b + 4], acc[b + 5] + acc2[b + 5]));
        }
      }
#pragma unroll
      for (int i = 0; i < 8; i++) { *reinterpret_cast<uint2*>(pd[i & 1]) = pk[i]; pd[i & 1] += pstr[i & 1]; }
      STAMP(9 + layer * 12);
    }
    {
      uint32_t bx[14];
#pragma unroll
      for (int j = 0; j < 14; j++) bx[j] = __ldg(reinterpret_cast<const uint32_t*>(b2 + (j >> 1) * 64 + w * 16 + (j & 1) * 8 + 2 * t));
      const unsigned char* psrc = gP + (size_t)(((G * 2 + c) * 8 + r) * 8) * 7168 + w * 256 + lane * 8;
      unsigned char* img = gImg + (size_t)(64 + G * 2 + c) * ABYTES;
      uint2 pv[7][7];
      const unsigned char* ps[7];
#pragma unroll
      for (int s = 0; s < 7; s++) ps[s] = psrc + ((r + 1 + s) & 7) * 7168;
#pragma unroll
      for (int i = 0; i < 7; i++)
#pragma unroll
        for (int s = 0; s < 7; s++) pv[s][i] = ldcg2(ps[s] + i * 1024);
      bar_wg(c);
      const uint32_t off = w * 2048 + r * 128 + lane * 4;
      unsigned char* dst = layer ? reinterpret_cast<unsigned char*>(out + (size_t)(row0 + r * 8 + g) * DM + w * 16 + 2 * t) : img + off;
      float sm = 0.f, q = 0.f;
#pragma unroll
      for (int i = 0; i < 7; i++) {
        const uint2 own = *reinterpret_cast<const uint2*>(sg + c * ABYTES + i * 8192 + w * 2048 + (lane >> 4) * 1024 + (r ^ 1) * 128 + (lane & 15) * 8);
#pragma unroll 1
        for (int n = 0; n < (1 << 16); n++) {
          const uint32_t all = pv[0][i].x & pv[1][i].x & pv[2][i].x & pv[3][i].x & pv[4][i].x & pv[5][i].x & pv[6][i].x;
          const uint32_t any = pv[0][i].x | pv[1][i].x | pv[2][i].x | pv[3][i].x | pv[4][i].x | pv[5][i].x | pv[6][i].x;
          if (!__any_sync(~0u, (layer ? any : ~all) & 1u)) break;
#pragma unroll
          for (int s = 0; s < 7; s++) pv[s][i] = ldcg2(ps[s] + i * 1024);
        }
#pragma unroll
        for (int jj = 0; jj < 2; jj++) {
          const int j = 2 * i + jj;
          const uint32_t xo = lds32(abuf + off + i * 8192 + jj * 1024), uo = jj ? own.y : own.x;
          float y0 = lo(bx[j]) + lo(xo) + lo(uo), y1 = hi(bx[j]) + hi(xo) + hi(uo);
#pragma unroll
          for (int s = 0; s < 7; s++) { const uint32_t u = jj ? pv[s][i].y : pv[s][i].x; y0 += lo(u); y1 += hi(u); }
          bx[j] = pack(y0, y1);
          *reinterpret_cast<uint32_t*>(dst + (i * 8 + jj) * (layer ? 16 : 1024)) = bx[j];
          sm += lo(bx[j]) + hi(bx[j]);
        }
      }
      if (layer) break;
      sm += __shfl_xor_sync(~0u, sm, 1); sm += __shfl_xor_sync(~0u, sm, 2);
      sm *= 1.f / 112.f;
#pragma unroll
      for (int j = 0; j < 14; j++) { const float a = lo(bx[j]) - sm, b = hi(bx[j]) - sm; q = fmaf(a, a, q); q = fmaf(b, b, q); }
      q += __shfl_xor_sync(~0u, q, 1); q += __shfl_xor_sync(~0u, q, 2);
      if (t < 2) gStat[(size_t)(2048 + row0 + r * 8 + g) * 8 + 2 * w + t] = make_float2(sm, q * 0.5f);
      STAMP(11);
      gather(fl + 64, img);
      STAMP(12);
    }
  }
  STAMP(30);
  if (tid == 0) asm volatile("red.relaxed.gpu.global.add.u32 [%0], 1;" ::"l"(gFlag + FL_DONE * 32) : "memory");
  }
}

typedef CUresult (*EncFn)(CUtensorMap*, CUtensorMapDataType, cuuint32_t, void*, const cuuint64_t*, const cuuint64_t*,
                          const cuuint32_t*, const cuuint32_t*, CUtensorMapInterleave, CUtensorMapSwizzle,
                          CUtensorMapL2promotion, CUtensorMapFloatOOBfill);

void make_map(EncFn enc, CUtensorMap* m, void* p, int rank, uint64_t d0, uint64_t d1, uint64_t d2, uint64_t s1, uint64_t s2,
              uint32_t b0, uint32_t b1, uint32_t b2, CUtensorMapSwizzle sw) {
  cuuint64_t dims[3] = {d0, d1, d2}, strides[2] = {s1, s2};
  cuuint32_t box[3] = {b0, b1, b2}, es[3] = {1, 1, 1};
  enc(m, CU_TENSOR_MAP_DATA_TYPE_BFLOAT16, rank, p, dims, strides, box, es, CU_TENSOR_MAP_INTERLEAVE_NONE, sw,
      CU_TENSOR_MAP_L2_PROMOTION_L2_128B, CU_TENSOR_MAP_FLOAT_OOB_FILL_NONE);
}

}

extern "C" void kernel_launch(void* const* d_in, const int* in_sizes, int n_in, void* d_out, int out_size) {
  static EncFn enc = nullptr;
  if (!enc) {
    cudaDriverEntryPointQueryResult st;
    void* fn = nullptr;
    cudaGetDriverEntryPoint("cuTensorMapEncodeTiled", &fn, cudaEnableDefault, &st);
    enc = (EncFn)fn;
    cudaFuncSetAttribute(fused_kernel, cudaFuncAttributeMaxDynamicSharedMemorySize, SMEM_BYTES);
  }
  CUtensorMap mQKV, mWO, mW1, mW2, mX;
  make_map(enc, &mX, d_in[0], 2, 448, 2048, 1, 896, 0, 64, 64, 1, CU_TENSOR_MAP_SWIZZLE_128B);
  make_map(enc, &mQKV, d_in[1], 3, 448, 448, 3, 2688, 896, 64, 32, 3, CU_TENSOR_MAP_SWIZZLE_128B);
  make_map(enc, &mWO, d_in[3], 2, 448, 448, 1, 896, 0, 64, 112, 1, CU_TENSOR_MAP_SWIZZLE_128B);
  make_map(enc, &mW1, d_in[5], 3, 32, 448, 56, 3584, 64, 32, 32, 7, CU_TENSOR_MAP_SWIZZLE_64B);
  make_map(enc, &mW2, d_in[7], 2, 448, 1792, 1, 896, 0, 64, 112, 1, CU_TENSOR_MAP_SWIZZLE_128B);
  fused_kernel<<<NCTA, 384, SMEM_BYTES, cudaStreamPerThread>>>(
      mQKV, mWO, mW1, mW2, mX, (const __nv_bfloat16*)d_in[2], (const __nv_bfloat16*)d_in[6],
      (const __nv_bfloat16*)d_in[8], (const __nv_bfloat16*)d_in[1], (const __nv_bfloat16*)d_in[3], (const __nv_bfloat16*)d_in[5],
      (const __nv_bfloat16*)d_in[7], (__nv_bfloat16*)d_out);
}
```

```cpp
#include <cuda_runtime.h>
#include <cuda_bf16.h>
#include <cuda.h>
#include <stdint.h>

namespace {

constexpr int DM = 448, NCTA = 128;
constexpr int ABYTES = 57344;
constexpr int SLOT = 14336, NSLOT = 7;
constexpr int OFF_RING = 2 * ABYTES;
constexpr int OFF_WPHI = OFF_RING + NSLOT * SLOT;
constexpr int OFF_B1 = OFF_WPHI + 8192;
constexpr int OFF_CS = OFF_B1 + 896;
constexpr int OFF_BAR = OFF_CS + 1664;
constexpr int SMEM_BYTES = OFF_BAR + 272 + 1024;
constexpr int TILES_PER_LAYER = 46;

__device__ __align__(1024) unsigned char gP[16 * 2 * 8 * 8 * 7168];
__device__ __align__(1024) unsigned char gImg[3 * 32 * ABYTES];
__device__ __align__(1024) float2 gStat[2 * 2048 * 8];
__device__ __align__(1024) float4 gKV[2 * 8 * 2 * 5 * 128];
__device__ __align__(1024) float4 gCS[8 * 16 * 104];
__device__ __align__(128) unsigned gFlag[(2 * 32 * 7 + 32 + 1 + 16) * 32];
#define STAMP(i)

__device__ __forceinline__ uint32_t smem_u32(const void* p) { return (uint32_t)__cvta_generic_to_shared(p); }
__device__ __forceinline__ void mbar_init(uint32_t b, int c) { asm volatile("mbarrier.init.shared::cta.b64 [%0], %1;" ::"r"(b), "r"(c)); }
__device__ __forceinline__ void mbar_expect(uint32_t b, int bytes) { asm volatile("mbarrier.arrive.expect_tx.shared::cta.b64 _, [%0], %1;" ::"r"(b), "r"(bytes) : "memory"); }
__device__ __forceinline__ void mbar_arrive(uint32_t b) { asm volatile("mbarrier.arrive.shared::cta.b64 _, [%0];" ::"r"(b) : "memory"); }
__device__ __forceinline__ void mbar_wait(uint32_t b, int par) {
  uint32_t ok; int n = 0;
#pragma unroll 1
  while (true) {
    asm volatile("{.reg .pred p; mbarrier.try_wait.parity.shared::cta.b64 p, [%1], %2; selp.u32 %0,1,0,p;}" : "=r"(ok) : "r"(b), "r"(par) : "memory");
    if (ok) break;
    if (++n > (1 << 22)) break;
  }
}
__device__ __forceinline__ void flag_wait(const unsigned* f, unsigned target) {
  unsigned v; int n = 0;
#pragma unroll 1
  while (true) {
    asm volatile("ld.acquire.gpu.global.u32 %0, [%1];" : "=r"(v) : "l"(f) : "memory");
    if ((int)(v - target) >= 0) break;
    if (++n > (1 << 21)) break;
  }
}
__device__ __forceinline__ void flag_arrive(unsigned* f) { asm volatile("red.release.gpu.global.add.u32 [%0], 1;" ::"l"(f) : "memory"); }
__device__ __forceinline__ bool elect_one() {
  uint32_t p; asm volatile("{.reg .pred P; elect.sync _|P, 0xffffffff; selp.u32 %0, 1, 0, P;}" : "=r"(p)); return p;
}
__device__ __forceinline__ void fence_async() { asm volatile("fence.proxy.async.global;" ::: "memory"); }
__device__ __forceinline__ void fence_async_smem() { asm volatile("fence.proxy.async.shared::cta;" ::: "memory"); }
template <int ID, int N> __device__ __forceinline__ void bar_sync() { asm volatile("bar.sync %0, %1;" ::"n"(ID), "n"(N) : "memory"); }
__device__ __forceinline__ void bar_wg(int c) { if (c) bar_sync<2, 128>(); else bar_sync<1, 128>(); }
__device__ __forceinline__ void wg_fence() { asm volatile("wgmma.fence.sync.aligned;" ::: "memory"); }
__device__ __forceinline__ void wg_commit() { asm volatile("wgmma.commit_group.sync.aligned;" ::: "memory"); }
template <int N> __device__ __forceinline__ void wg_wait() { asm volatile("wgmma.wait_group.sync.aligned %0;" ::"n"(N) : "memory"); }
template <int N> __device__ __forceinline__ void reg_fence(float (&d)[N]) {
#pragma unroll
  for (int i = 0; i < N; i++) asm volatile("" : "+f"(d[i])::"memory");
}
template <int N> __device__ __forceinline__ void reg_def(float (&d)[N]) {
#pragma unroll
  for (int i = 0; i < N; i++) d[i] = 0.f;
}
__device__ __forceinline__ uint64_t mkdesc(uint32_t addr, uint32_t lbo, uint32_t sbo, uint64_t swz) {
  return (uint64_t)((addr & 0x3FFFF) >> 4) | ((uint64_t)(lbo >> 4) << 16) | ((uint64_t)(sbo >> 4) << 32) | (swz << 62);
}
__device__ __forceinline__ uint32_t pack(float a, float b) {
  uint32_t r; asm("cvt.rn.bf16x2.f32 %0, %1, %2;" : "=r"(r) : "f"(b), "f"(a)); return r;
}
__device__ __forceinline__ uint32_t relu_sq(float a, float b) {
  uint32_t r; asm("{.reg .b32 v; cvt.rn.relu.bf16x2.f32 v, %1, %2; mul.rn.bf16x2 %0, v, v;}" : "=r"(r) : "f"(b), "f"(a)); return r;
}
__device__ __forceinline__ float lo(uint32_t u) { return __uint_as_float(u << 16); }
__device__ __forceinline__ float hi(uint32_t u) { return __uint_as_float(u & 0xFFFF0000u); }
__device__ __forceinline__ float ex2(float x) { float y; asm("ex2.approx.ftz.f32 %0, %1;" : "=f"(y) : "f"(x)); return y; }
__device__ __forceinline__ void stsm4(uint32_t a, uint32_t r0, uint32_t r1, uint32_t r2, uint32_t r3) {
  asm volatile("stmatrix.sync.aligned.m8n8.x4.shared.b16 [%0], {%1,%2,%3,%4};" ::"r"(a), "r"(r0), "r"(r1), "r"(r2), "r"(r3) : "memory");
}
__device__ __forceinline__ void tma3(uint32_t dst, const CUtensorMap* m, int c0, int c1, int c2, uint32_t bar) {
  asm volatile("cp.async.bulk.tensor.3d.shared::cluster.global.mbarrier::complete_tx::bytes [%0], [%1, {%3,%4,%5}], [%2];"
               ::"r"(dst), "l"(m), "r"(bar), "r"(c0), "r"(c1), "r"(c2) : "memory");
}
__device__ __forceinline__ void tma2(uint32_t dst, const CUtensorMap* m, int c0, int c1, uint32_t bar) {
  asm volatile("cp.async.bulk.tensor.2d.shared::cluster.global.mbarrier::complete_tx::bytes [%0], [%1, {%3,%4}], [%2];"
               ::"r"(dst), "l"(m), "r"(bar), "r"(c0), "r"(c1) : "memory");
}
__device__ __forceinline__ uint32_t lds32(uint32_t a) { uint32_t v; asm volatile("ld.shared.u32 %0, [%1];" : "=r"(v) : "r"(a) : "memory"); return v; }
__device__ __forceinline__ void bulk_ld(uint32_t dst, const void* src, int bytes, uint32_t bar) {
  asm volatile("cp.async.bulk.shared::cluster.global.mbarrier::complete_tx::bytes [%0], [%1], %2, [%3];" ::"r"(dst), "l"(src), "r"(bytes), "r"(bar) : "memory");
}
__device__ __forceinline__ uint4 ldcg4(const void* p) {
  uint4 v; asm volatile("ld.global.cg.v4.u32 {%0,%1,%2,%3}, [%4];" : "=r"(v.x), "=r"(v.y), "=r"(v.z), "=r"(v.w) : "l"(p) : "memory"); return v;
}

__device__ __forceinline__ uint2 ldcg2(const void* p) {
  uint2 v; asm volatile("ld.global.cg.v2.u32 {%0,%1}, [%2];" : "=r"(v.x), "=r"(v.y) : "l"(p) : "memory"); return v;
}

__device__ __forceinline__ void mma_ss_184(float (&d)[92], uint64_t da, uint64_t db, int acc) {
  asm volatile("{.reg .pred p; setp.ne.b32 p, %94, 0;\n"
    "wgmma.mma_async.sync.aligned.m64n184k16.f32.bf16.bf16 {%0,%1,%2,%3,%4,%5,%6,%7,%8,%9,%10,%11,%12,%13,%14,%15,%16,%17,%18,%19,%20,%21,%22,%23,%24,%25,%26,%27,%28,%29,%30,%31,%32,%33,%34,%35,%36,%37,%38,%39,%40,%41,%42,%43,%44,%45,%46,%47,%48,%49,%50,%51,%52,%53,%54,%55,%56,%57,%58,%59,%60,%61,%62,%63,%64,%65,%66,%67,%68,%69,%70,%71,%72,%73,%74,%75,%76,%77,%78,%79,%80,%81,%82,%83,%84,%85,%86,%87,%88,%89,%90,%91}, %92, %93, p, 1, 1, 0, 1;}\n"
    : "+f"(d[0]),"+f"(d[1]),"+f"(d[2]),"+f"(d[3]),"+f"(d[4]),"+f"(d[5]),"+f"(d[6]),"+f"(d[7]),"+f"(d[8]),"+f"(d[9]),"+f"(d[10]),"+f"(d[11]),"+f"(d[12]),"+f"(d[13]),"+f"(d[14]),"+f"(d[15]),"+f"(d[16]),"+f"(d[17]),"+f"(d[18]),"+f"(d[19]),"+f"(d[20]),"+f"(d[21]),"+f"(d[22]),"+f"(d[23]),"+f"(d[24]),"+f"(d[25]),"+f"(d[26]),"+f"(d[27]),"+f"(d[28]),"+f"(d[29]),"+f"(d[30]),"+f"(d[31]),"+f"(d[32]),"+f"(d[33]),"+f"(d[34]),"+f"(d[35]),"+f"(d[36]),"+f"(d[37]),"+f"(d[38]),"+f"(d[39]),"+f"(d[40]),"+f"(d[41]),"+f"(d[42]),"+f"(d[43]),"+f"(d[44]),"+f"(d[45]),"+f"(d[46]),"+f"(d[47]),"+f"(d[48]),"+f"(d[49]),"+f"(d[50]),"+f"(d[51]),"+f"(d[52]),"+f"(d[53]),"+f"(d[54]),"+f"(d[55]),"+f"(d[56]),"+f"(d[57]),"+f"(d[58]),"+f"(d[59]),"+f"(d[60]),"+f"(d[61]),"+f"(d[62]),"+f"(d[63]),"+f"(d[64]),"+f"(d[65]),"+f"(d[66]),"+f"(d[67]),"+f"(d[68]),"+f"(d[69]),"+f"(d[70]),"+f"(d[71]),"+f"(d[72]),"+f"(d[73]),"+f"(d[74]),"+f"(d[75]),"+f"(d[76]),"+f"(d[77]),"+f"(d[78]),"+f"(d[79]),"+f"(d[80]),"+f"(d[81]),"+f"(d[82]),"+f"(d[83]),"+f"(d[84]),"+f"(d[85]),"+f"(d[86]),"+f"(d[87]),"+f"(d[88]),"+f"(d[89]),"+f"(d[90]),"+f"(d[91])
    : "l"(da), "l"(db), "r"(acc));
}
__device__ __forceinline__ void mma_ss_224(float (&d)[112], uint64_t da, uint64_t db, int acc) {
  asm volatile("{.reg .pred p; setp.ne.b32 p, %114, 0;\n"
    "wgmma.mma_async.sync.aligned.m64n224k16.f32.bf16.bf16 {%0,%1,%2,%3,%4,%5,%6,%7,%8,%9,%10,%11,%12,%13,%14,%15,%16,%17,%18,%19,%20,%21,%22,%23,%24,%25,%26,%27,%28,%29,%30,%31,%32,%33,%34,%35,%36,%37,%38,%39,%40,%41,%42,%43,%44,%45,%46,%47,%48,%49,%50,%51,%52,%53,%54,%55,%56,%57,%58,%59,%60,%61,%62,%63,%64,%65,%66,%67,%68,%69,%70,%71,%72,%73,%74,%75,%76,%77,%78,%79,%80,%81,%82,%83,%84,%85,%86,%87,%88,%89,%90,%91,%92,%93,%94,%95,%96,%97,%98,%99,%100,%101,%102,%103,%104,%105,%106,%107,%108,%109,%110,%111}, %112, %113, p, 1, 1, 0, 1;}\n"
    : "+f"(d[0]),"+f"(d[1]),"+f"(d[2]),"+f"(d[3]),"+f"(d[4]),"+f"(d[5]),"+f"(d[6]),"+f"(d[7]),"+f"(d[8]),"+f"(d[9]),"+f"(d[10]),"+f"(d[11]),"+f"(d[12]),"+f"(d[13]),"+f"(d[14]),"+f"(d[15]),"+f"(d[16]),"+f"(d[17]),"+f"(d[18]),"+f"(d[19]),"+f"(d[20]),"+f"(d[21]),"+f"(d[22]),"+f"(d[23]),"+f"(d[24]),"+f"(d[25]),"+f"(d[26]),"+f"(d[27]),"+f"(d[28]),"+f"(d[29]),"+f"(d[30]),"+f"(d[31]),"+f"(d[32]),"+f"(d[33]),"+f"(d[34]),"+f"(d[35]),"+f"(d[36]),"+f"(d[37]),"+f"(d[38]),"+f"(d[39]),"+f"(d[40]),"+f"(d[41]),"+f"(d[42]),"+f"(d[43]),"+f"(d[44]),"+f"(d[45]),"+f"(d[46]),"+f"(d[47]),"+f"(d[48]),"+f"(d[49]),"+f"(d[50]),"+f"(d[51]),"+f"(d[52]),"+f"(d[53]),"+f"(d[54]),"+f"(d[55]),"+f"(d[56]),"+f"(d[57]),"+f"(d[58]),"+f"(d[59]),"+f"(d[60]),"+f"(d[61]),"+f"(d[62]),"+f"(d[63]),"+f"(d[64]),"+f"(d[65]),"+f"(d[66]),"+f"(d[67]),"+f"(d[68]),"+f"(d[69]),"+f"(d[70]),"+f"(d[71]),"+f"(d[72]),"+f"(d[73]),"+f"(d[74]),"+f"(d[75]),"+f"(d[76]),"+f"(d[77]),"+f"(d[78]),"+f"(d[79]),"+f"(d[80]),"+f"(d[81]),"+f"(d[82]),"+f"(d[83]),"+f"(d[84]),"+f"(d[85]),"+f"(d[86]),"+f"(d[87]),"+f"(d[88]),"+f"(d[89]),"+f"(d[90]),"+f"(d[91]),"+f"(d[92]),"+f"(d[93]),"+f"(d[94]),"+f"(d[95]),"+f"(d[96]),"+f"(d[97]),"+f"(d[98]),"+f"(d[99]),"+f"(d[100]),"+f"(d[101]),"+f"(d[102]),"+f"(d[103]),"+f"(d[104]),"+f"(d[105]),"+f"(d[106]),"+f"(d[107]),"+f"(d[108]),"+f"(d[109]),"+f"(d[110]),"+f"(d[111])
    : "l"(da), "l"(db), "r"(acc));
}
__device__ __forceinline__ void mma_ss_56(float (&d)[28], uint64_t da, uint64_t db, int acc) {
  asm volatile("{.reg .pred p; setp.ne.b32 p, %30, 0;\n"
    "wgmma.mma_async.sync.aligned.m64n56k16.f32.bf16.bf16 {%0,%1,%2,%3,%4,%5,%6,%7,%8,%9,%10,%11,%12,%13,%14,%15,%16,%17,%18,%19,%20,%21,%22,%23,%24,%25,%26,%27}, %28, %29, p, 1, 1, 0, 1;}\n"
    : "+f"(d[0]),"+f"(d[1]),"+f"(d[2]),"+f"(d[3]),"+f"(d[4]),"+f"(d[5]),"+f"(d[6]),"+f"(d[7]),"+f"(d[8]),"+f"(d[9]),"+f"(d[10]),"+f"(d[11]),"+f"(d[12]),"+f"(d[13]),"+f"(d[14]),"+f"(d[15]),"+f"(d[16]),"+f"(d[17]),"+f"(d[18]),"+f"(d[19]),"+f"(d[20]),"+f"(d[21]),"+f"(d[22]),"+f"(d[23]),"+f"(d[24]),"+f"(d[25]),"+f"(d[26]),"+f"(d[27])
    : "l"(da), "l"(db), "r"(acc));
}
__device__ __forceinline__ void mma_rs_56(float (&d)[28], uint32_t a0, uint32_t a1, uint32_t a2, uint32_t a3, uint64_t db, int acc) {
  asm volatile("{.reg .pred p; setp.ne.b32 p, %33, 0;\n"
    "wgmma.mma_async.sync.aligned.m64n56k16.f32.bf16.bf16 {%0,%1,%2,%3,%4,%5,%6,%7,%8,%9,%10,%11,%12,%13,%14,%15,%16,%17,%18,%19,%20,%21,%22,%23,%24,%25,%26,%27}, {%28,%29,%30,%31}, %32, p, 1, 1, 1;}\n"
    : "+f"(d[0]),"+f"(d[1]),"+f"(d[2]),"+f"(d[3]),"+f"(d[4]),"+f"(d[5]),"+f"(d[6]),"+f"(d[7]),"+f"(d[8]),"+f"(d[9]),"+f"(d[10]),"+f"(d[11]),"+f"(d[12]),"+f"(d[13]),"+f"(d[14]),"+f"(d[15]),"+f"(d[16]),"+f"(d[17]),"+f"(d[18]),"+f"(d[19]),"+f"(d[20]),"+f"(d[21]),"+f"(d[22]),"+f"(d[23]),"+f"(d[24]),"+f"(d[25]),"+f"(d[26]),"+f"(d[27])
    : "r"(a0), "r"(a1), "r"(a2), "r"(a3), "l"(db), "r"(acc));
}
__device__ __forceinline__ void mma_ss_64t(float (&d)[32], uint64_t da, uint64_t db, int acc) {
  asm volatile("{.reg .pred p; setp.ne.b32 p, %34, 0;\n"
    "wgmma.mma_async.sync.aligned.m64n64k16.f32.bf16.bf16 {%0,%1,%2,%3,%4,%5,%6,%7,%8,%9,%10,%11,%12,%13,%14,%15,%16,%17,%18,%19,%20,%21,%22,%23,%24,%25,%26,%27,%28,%29,%30,%31}, %32, %33, p, 1, 1, 1, 1;}\n"
    : "+f"(d[0]),"+f"(d[1]),"+f"(d[2]),"+f"(d[3]),"+f"(d[4]),"+f"(d[5]),"+f"(d[6]),"+f"(d[7]),"+f"(d[8]),"+f"(d[9]),"+f"(d[10]),"+f"(d[11]),"+f"(d[12]),"+f"(d[13]),"+f"(d[14]),"+f"(d[15]),"+f"(d[16]),"+f"(d[17]),"+f"(d[18]),"+f"(d[19]),"+f"(d[20]),"+f"(d[21]),"+f"(d[22]),"+f"(d[23]),"+f"(d[24]),"+f"(d[25]),"+f"(d[26]),"+f"(d[27]),"+f"(d[28]),"+f"(d[29]),"+f"(d[30]),"+f"(d[31])
    : "l"(da), "l"(db), "r"(acc));
}
__device__ __forceinline__ void mma_rs_64(float (&d)[32], uint32_t a0, uint32_t a1, uint32_t a2, uint32_t a3, uint64_t db, int acc) {
  asm volatile("{.reg .pred p; setp.ne.b32 p, %37, 0;\n"
    "wgmma.mma_async.sync.aligned.m64n64k16.f32.bf16.bf16 {%0,%1,%2,%3,%4,%5,%6,%7,%8,%9,%10,%11,%12,%13,%14,%15,%16,%17,%18,%19,%20,%21,%22,%23,%24,%25,%26,%27,%28,%29,%30,%31}, {%32,%33,%34,%35}, %36, p, 1, 1, 1;}\n"
    : "+f"(d[0]),"+f"(d[1]),"+f"(d[2]),"+f"(d[3]),"+f"(d[4]),"+f"(d[5]),"+f"(d[6]),"+f"(d[7]),"+f"(d[8]),"+f"(d[9]),"+f"(d[10]),"+f"(d[11]),"+f"(d[12]),"+f"(d[13]),"+f"(d[14]),"+f"(d[15]),"+f"(d[16]),"+f"(d[17]),"+f"(d[18]),"+f"(d[19]),"+f"(d[20]),"+f"(d[21]),"+f"(d[22]),"+f"(d[23]),"+f"(d[24]),"+f"(d[25]),"+f"(d[26]),"+f"(d[27]),"+f"(d[28]),"+f"(d[29]),"+f"(d[30]),"+f"(d[31])
    : "r"(a0), "r"(a1), "r"(a2), "r"(a3), "l"(db), "r"(acc));
}

__device__ __forceinline__ void dual_softmax(const float (&p)[28], uint32_t (&phi)[4][7]) {
  constexpr float L2E = 1.4426950408889634f;
#pragma unroll
  for (int i = 0; i < 4; i++) {
    float mx = p[i], mn = p[i];
#pragma unroll
    for (int j = 1; j < 7; j++) { mx = fmaxf(mx, p[4 * j + i]); mn = fminf(mn, p[4 * j + i]); }
    mx = fmaxf(mx, __shfl_xor_sync(~0u, mx, 1)); mn = fminf(mn, __shfl_xor_sync(~0u, mn, 1));
    mx = fmaxf(mx, __shfl_xor_sync(~0u, mx, 2)); mn = fminf(mn, __shfl_xor_sync(~0u, mn, 2));
    float a[7], b[7], sa = 0.f, sb = 0.f;
    const float mxl = mx * L2E, mnl = mn * L2E;
#pragma unroll
    for (int j = 0; j < 7; j++) {
      a[j] = ex2(fmaf(p[4 * j + i], L2E, -mxl)); b[j] = ex2(fmaf(p[4 * j + i], -L2E, mnl));
      sa += a[j]; sb += b[j];
    }
    sa += __shfl_xor_sync(~0u, sa, 1); sb += __shfl_xor_sync(~0u, sb, 1);
    sa += __shfl_xor_sync(~0u, sa, 2); sb += __shfl_xor_sync(~0u, sb, 2);
    const float ra = __fdividef(1.f, sa), rb = __fdividef(1.f, sb);
#pragma unroll
    for (int j = 0; j < 7; j++) phi[i][j] = pack(a[j] * ra, b[j] * rb);
  }
}

struct Ring {
  uint32_t full, empty, base; int slot, par;
  __device__ __forceinline__ void uniform() { slot = __shfl_sync(~0u, slot, 0); par = __shfl_sync(~0u, par, 0); }
  __device__ __forceinline__ uint32_t acquire() { mbar_wait(full + slot * 8, par); return base + slot * SLOT; }
  __device__ __forceinline__ int advance() { int s = slot; if (++slot == NSLOT) { slot = 0; par ^= 1; } return s; }
  __device__ __forceinline__ void release(int s, bool elect) { if (elect) mbar_arrive(empty + s * 8); }
};
constexpr int UNR = 14;
constexpr int FL_KV = 448, FL_CS = FL_KV + 16, FL_DONE = FL_KV + 32;

__global__ void __launch_bounds__(384, 1)
fused_kernel(const __grid_constant__ CUtensorMap mQKV, const __grid_constant__ CUtensorMap mWO,
             const __grid_constant__ CUtensorMap mW1, const __grid_constant__ CUtensorMap mW2,
             const __grid_constant__ CUtensorMap mX, const __nv_bfloat16* __restrict__ wphi,
             const __nv_bfloat16* __restrict__ b1, const __nv_bfloat16* __restrict__ b2,
             const __nv_bfloat16* __restrict__ wqkv, const __nv_bfloat16* __restrict__ wo, const __nv_bfloat16* __restrict__ w1,
             const __nv_bfloat16* __restrict__ w2, __nv_bfloat16* __restrict__ out) {
  extern __shared__ unsigned char smem_raw[];
  const uint32_t sb = (smem_u32(smem_raw) + 1023) & ~1023u;
  unsigned char* sg = smem_raw + (sb - smem_u32(smem_raw));
  const int tid = threadIdx.x, lane = tid & 31;
  const int G = blockIdx.x >> 3, r = blockIdx.x & 7;
  const uint32_t barFull = sb + OFF_BAR, barEmpty = barFull + 56, barA = barEmpty + 56, barCS = barA + 112, barX = barCS + 16;
  const int warp = __shfl_sync(~0u, tid >> 5, 0);
  uint32_t wv[7], bv;
#pragma unroll
  for (int i = 0; i < 7; i++)
    wv[i] = __ldg(reinterpret_cast<const unsigned short*>(wphi) + (56 * r + i * 8 + (warp & 7)) * 28 + min(lane, 27));
  bv = __ldg(reinterpret_cast<const unsigned short*>(b1) + 224 * r + min(tid, 223));
  if (lane == 0) {
    if (warp >= 10) {
      const int cc = warp - 10;
      mbar_init(barX + cc * 8, 1);
      fence_async_smem();
      mbar_expect(barX + cc * 8, ABYTES);
#pragma unroll 1
      for (int k = 0; k < 7; k++) tma2(sb + cc * ABYTES + k * 8192, &mX, 64 * k, G * 128 + 64 * cc, barX + cc * 8);
    } else if (warp < 7) { mbar_init(barFull + warp * 8, 1); mbar_init(barEmpty + warp * 8, 2); mbar_init(barA + warp * 8, 1); mbar_init(barA + 56 + warp * 8, 1); }
    else if (warp < 9) mbar_init(barCS + (warp - 7) * 8, 96);
    else
      asm volatile("cp.async.bulk.prefetch.L2.global [%0], %1;" ::"l"((const char*)wqkv + blockIdx.x * 9408), "r"(9408) : "memory");
    asm volatile("fence.mbarrier_init.release.cluster;" ::: "memory");
  }
  if (tid < 192) reinterpret_cast<float*>(sg + OFF_CS)[tid] = 0.f;
  __syncthreads();
  const int wgid = warp >> 2;
  if (wgid == 2) {
    asm volatile("setmaxnreg.dec.sync.aligned.u32 40;");
    if (warp == 8) {
      int slot = 0, par = 1;
#pragma unroll 1
      for (int it = 0; it < 2 * TILES_PER_LAYER; it++) {
        const int i = it >= TILES_PER_LAYER ? it - TILES_PER_LAYER : it;
        mbar_wait(barEmpty + slot * 8, par);
        const uint32_t dst = sb + OFF_RING + slot * SLOT, fb = barFull + slot * 8;
        if (elect_one()) {
          mbar_expect(fb, i < 14 ? 12288 : SLOT);
          if (i < 14) tma3(dst, &mQKV, 56 * r, 32 * i, 0, fb);
          else if (i < 18) tma2(dst, &mWO, 56 * r, 112 * (i - 14), fb);
          else if (i < 32) tma3(dst, &mW1, 0, 32 * (i - 18), 7 * r, fb);
          else tma2(dst, &mW2, 64 * ((i - 32) >> 1), 224 * r + 112 * (i & 1), fb);
        }
        if (++slot == NSLOT) { slot = 0; par ^= 1; }
      }
    } else {
      unsigned ep;
      asm volatile("ld.relaxed.gpu.global.u32 %0, [%1];" : "=r"(ep) : "l"(gFlag + FL_DONE * 32) : "memory");
      const int idx = tid - 288;
      ep = (ep / NCTA + 1) * 3;
      if (G == 0) {
#pragma unroll 1
        for (int i = idx; i < 2 * 1280; i += 96) gKV[((i >= 1280) * 7 + r) * 1280 + i] = make_float4(0.f, 0.f, 0.f, 0.f);
        __syncwarp();
        if (lane == 0) flag_arrive(gFlag + (FL_CS + r) * 32);
      }
      mbar_wait(barFull + 48, 0); mbar_wait(barFull + 48, 1);
      if (idx < 2) {
        const char* pf = idx ? (const char*)w2 + blockIdx.x * 12544 : (const char*)wo + blockIdx.x * 3136;
        asm volatile("cp.async.bulk.prefetch.L2.global [%0], %1;" ::"l"(pf), "r"(idx ? 12544 : 3136) : "memory");
      }
      if (lane == 0) flag_wait(gFlag + (FL_CS + r) * 32, ep);
      __syncwarp();
      mbar_arrive(barCS);
#pragma unroll 1
      for (int ps = 0; ps < 3; ps++) {
        const int nch = ps ? 14 : 21, ch = min(idx >> 2, nch - 1), p = ch / 7, k0 = G * 28 + (idx & 3) * 7;
        const uint4* src = ps ? reinterpret_cast<const uint4*>(w1 + (size_t)k0 * 1792 + 224 * r) + (ps - 1) * 14 + ch
                              : reinterpret_cast<const uint4*>(wqkv + (size_t)k0 * 1344 + p * 448 + 56 * r) + (ch - 7 * p);
        uint4 cu[7];
#pragma unroll
        for (int i = 0; i < 7; i++) cu[i] = __ldg(src + i * (ps ? 224 : 168));
        float s[8] = {};
#pragma unroll
        for (int i = 0; i < 7; i++) { s[0] += lo(cu[i].x); s[1] += hi(cu[i].x); s[2] += lo(cu[i].y); s[3] += hi(cu[i].y); s[4] += lo(cu[i].z); s[5] += hi(cu[i].z); s[6] += lo(cu[i].w); s[7] += hi(cu[i].w); }
#pragma unroll
        for (int i = 0; i < 8; i++) { s[i] += __shfl_xor_sync(~0u, s[i], 1); s[i] += __shfl_xor_sync(~0u, s[i], 2); }
        if ((idx & 3) < 2 && idx < nch * 4) gCS[(r * 16 + G) * 104 + (ps ? 10 + ps * 14 + ch : ch + p) * 2 + (idx & 1)] = (idx & 1) ? make_float4(s[4], s[5], s[6], s[7]) : make_float4(s[0], s[1], s[2], s[3]);
      }
      __syncwarp();
      if (lane == 0) { flag_arrive(gFlag + (FL_CS + 8 + r) * 32); flag_wait(gFlag + (FL_CS + 8 + r) * 32, ep * 16); }
      __syncwarp();
#pragma unroll 1
      for (int j = idx; j < 208; j += 96) {
        float2 a = make_float2(0.f, 0.f);
#pragma unroll 8
        for (int i = 0; i < 16; i++) { const float2 v = __ldcg(reinterpret_cast<const float2*>(gCS + (r * 16 + i) * 104) + j); a.x += v.x; a.y += v.y; }
        reinterpret_cast<float2*>(sg + OFF_CS)[j] = a;
      }
      mbar_arrive(barCS + 8);
    }
  } else {
  asm volatile("setmaxnreg.inc.sync.aligned.u32 232;");
  const int c = wgid, w = warp & 3, g = lane >> 2, t = lane & 3;
  int elect_i = (tid & 127) == 0;
  asm volatile("" : "+r"(elect_i));
  const bool elect = elect_i;
  const uint32_t abuf = sb + c * ABYTES, barAc = barA + c * 56;
  const int row0 = G * 128 + c * 64;
  unsigned epoch;
  asm volatile("ld.relaxed.gpu.global.u32 %0, [%1];" : "=r"(epoch) : "l"(gFlag + FL_DONE * 32) : "memory");
  STAMP(24);
  float mean[2], rstd[2] = {0.f, 0.f};
  uint4 su[2] = {};
  uint32_t xs[7][2];
  {
#pragma unroll
    for (int i = 0; i < 8; i++) {
      const int k = i * 8 + (tid >> 5);
      *reinterpret_cast<uint32_t*>(sg + OFF_WPHI + k * 128 + ((g ^ (k & 7)) << 4) + t * 4) = (i < 7 && lane < 28) ? wv[i % 7] << (k >= 28 ? 16 : 0) : 0u;
    }
    if (tid < 224) reinterpret_cast<uint32_t*>(sg + OFF_B1)[tid] = bv << 16;
    mbar_wait(barX + c * 8, 0);
    STAMP(25);
#pragma unroll
    for (int j = 0; j < 7; j++) {
      const int ci = 7 * r + j;
      const uint32_t a = abuf + (ci >> 3) * 8192 + (w * 16 + g) * 128 + (((ci & 7) ^ g) << 4) + t * 4;
      xs[j][0] = lds32(a); xs[j][1] = lds32(a + 1024);
    }
    __syncwarp();
#pragma unroll 1
    for (int hh = 0; hh < 2; hh++) {
      uint4* p = reinterpret_cast<uint4*>(sg + c * ABYTES + (w * 16 + hh * 8 + g) * 128) + t;
      uint4 v[14];
#pragma unroll
      for (int k = 0; k < 14; k++) v[k] = p[(k >> 1) * 512 + ((k ^ g) & 1) * 4];
      float a8[8] = {};
#pragma unroll
      for (int k = 0; k < 14; k++) {
        const uint32_t e[4] = {v[k].x, v[k].y, v[k].z, v[k].w};
#pragma unroll
        for (int z = 0; z < 4; z++) { a8[2 * z] += lo(e[z]); a8[2 * z + 1] += hi(e[z]); }
      }
      float sm = ((a8[0] + a8[1]) + (a8[2] + a8[3])) + ((a8[4] + a8[5]) + (a8[6] + a8[7]));
      sm += __shfl_xor_sync(~0u, sm, 1); sm += __shfl_xor_sync(~0u, sm, 2);
      sm *= 1.f / DM;
#pragma unroll
      for (int k = 0; k < 14; k++) {
        uint32_t e[4] = {v[k].x, v[k].y, v[k].z, v[k].w};
#pragma unroll
        for (int z = 0; z < 4; z++) {
          const float a = lo(e[z]) - sm, b = hi(e[z]) - sm;
          a8[2 * z] = fmaf(a, a, k ? a8[2 * z] : 0.f); a8[2 * z + 1] = fmaf(b, b, k ? a8[2 * z + 1] : 0.f);
          e[z] = pack(a, b);
        }
        p[(k >> 1) * 512 + ((k ^ g) & 1) * 4] = make_uint4(e[0], e[1], e[2], e[3]);
      }
      float q = ((a8[0] + a8[1]) + (a8[2] + a8[3])) + ((a8[4] + a8[5]) + (a8[6] + a8[7]));
      q += __shfl_xor_sync(~0u, q, 1); q += __shfl_xor_sync(~0u, q, 2);
      rstd[1] = rsqrtf(q * (1.f / DM) + 1e-5f);
      if (hh == 0) rstd[0] = rstd[1];
    }
    fence_async_smem();
    bar_sync<3, 256>();
    epoch = epoch / NCTA + 1;
    mean[0] = mean[1] = 0.f;
  }
  STAMP(0);
  Ring ring{barFull, barEmpty, sb + OFF_RING, 0, 0};
  int apar = 1;
  const uint32_t stsm_off = (w * 16 + ((lane >> 3) & 1) * 8 + (lane & 7)) * 128;
  const uint32_t stsm_hi = lane >> 4;
  const uint64_t dA = mkdesc(abuf, 1024, 128, 0);

  auto gather = [&](unsigned* fl, const unsigned char* img) {
    __syncwarp();
    if (lane == 0) {
      flag_arrive(fl);
      STAMP(27);
      flag_wait(fl, epoch * 32);
      STAMP(28);
      fence_async();
      mbar_expect(barAc + w * 8, 8192); bulk_ld(abuf + w * 8192, img + w * 8192, 8192, barAc + w * 8);
      if (w < 3) { mbar_expect(barAc + 32 + w * 8, 8192); bulk_ld(abuf + 32768 + w * 8192, img + 32768 + w * 8192, 8192, barAc + 32 + w * 8); }
    }
    __syncwarp();
    apar ^= 1;
  };
  auto slice_off = [&](int j, int hh) -> uint32_t {
    return (7 * r + j) * 1024 + (w * 2 + hh) * 128 + lane * 4;
  };
  auto load_stats = [&](const float2* st) {
    mbar_wait(barAc, apar);
#pragma unroll
    for (int hh = 0; hh < 2; hh++) su[hh] = ldcg4(st + (size_t)(row0 + w * 16 + hh * 8 + g) * 8 + 2 * t);
  };
  auto finish_stats = [&]() {
#pragma unroll
    for (int hh = 0; hh < 2; hh++) {
      const float m0 = __uint_as_float(su[hh].x), m1 = __uint_as_float(su[hh].z);
      float m = m0 + m1;
      m += __shfl_xor_sync(~0u, m, 1); m += __shfl_xor_sync(~0u, m, 2);
      m *= 0.125f;
      float q = __uint_as_float(su[hh].y) + __uint_as_float(su[hh].w) + 56.f * ((m0 - m) * (m0 - m) + (m1 - m) * (m1 - m));
      q += __shfl_xor_sync(~0u, q, 1); q += __shfl_xor_sync(~0u, q, 2);
      mean[hh] = m; rstd[hh] = rsqrtf(q * (1.f / DM) + 1e-5f);
    }
  };

#pragma unroll 1
  for (int lyr = 0; lyr < 2; lyr++) {
    const int layer = __shfl_sync(~0u, lyr, 0);
    unsigned* const fl = gFlag + (layer * 32 + G * 2 + c) * 7 * 32;
    uint32_t phiq[4][7];
    {
      float acc[92]; reg_def(acc);
      int prev = 0, prev2 = 0;
      ring.uniform();
      const uint64_t dQ = layer ? dA : mkdesc(abuf, 16, 1024, 1);
      const int kstep = layer ? 128 : 2;
      if (layer) load_stats(gStat + 2048 * 8);
#pragma unroll UNR
      for (int st = 0; st < 14; st++) {
        if (!(st & 1) && layer) mbar_wait(barAc + (st >> 1) * 8, apar);
        const uint64_t da = dQ + (st >> 1) * 512 + (st & 1) * 2 * kstep, db = mkdesc(ring.acquire(), 4096, 1024, 1);
        wg_fence();
        mma_ss_184(acc, da, db, 1);
        mma_ss_184(acc, da + kstep, db + 128, 1);
        wg_commit();
        if (st > 1) { wg_wait<2>(); ring.release(prev2, elect); }
        prev2 = prev; prev = ring.advance();
      }
      if (layer) {
        finish_stats();
#pragma unroll
        for (int j = 0; j < 7; j++) { xs[j][0] = lds32(abuf + slice_off(j, 0)); xs[j][1] = lds32(abuf + slice_off(j, 1)); }
      }
      wg_wait<0>(); reg_fence(acc);
      ring.release(prev2, elect); ring.release(prev, elect);
      STAMP(1 + layer * 12);
      uint32_t f[3][14];
      {
        const float2* cs = reinterpret_cast<const float2*>(sg + OFF_CS) + t;
        const float mr0 = -mean[0] * rstd[0], mr1 = -mean[1] * rstd[1];
#pragma unroll
        for (int p = 0; p < 3; p++)
#pragma unroll
          for (int j = 0; j < 7; j++) {
            const float2 s = cs[p * 32 + j * 4];
            const int b = p * 32 + j * 4;
            f[p][2 * j] = pack(fmaf(acc[b], rstd[0], s.x * mr0), fmaf(acc[b + 1], rstd[0], s.y * mr0));
            f[p][2 * j + 1] = pack(fmaf(acc[b + 2], rstd[1], s.x * mr1), fmaf(acc[b + 3], rstd[1], s.y * mr1));
          }
      }
      float pk[28], pq[28]; reg_def(pk); reg_def(pq);
      const uint64_t dW = mkdesc(sb + OFF_WPHI, 4096, 1024, 1);
      wg_fence();
#pragma unroll
      for (int s = 0; s < 4; s++) {
        mma_rs_56(pk, f[1][4 * s], f[1][4 * s + 1], s < 3 ? f[1][(4 * s + 2) % 14] : 0u, s < 3 ? f[1][(4 * s + 3) % 14] : 0u, dW + s * 128, s);
        mma_rs_56(pq, f[0][4 * s], f[0][4 * s + 1], s < 3 ? f[0][(4 * s + 2) % 14] : 0u, s < 3 ? f[0][(4 * s + 3) % 14] : 0u, dW + s * 128, s);
      }
      wg_commit();
      bar_wg(c);
      const uint32_t srow = abuf + stsm_off, ones = t == 0 ? 0x3F803F80u : 0u;
#pragma unroll
      for (int jp = 0; jp < 4; jp++)
        stsm4(srow + 16384 + (((2 * jp + stsm_hi) ^ (lane & 7)) << 4), f[2][4 * jp], f[2][4 * jp + 1],
              jp < 3 ? f[2][(4 * jp + 2) % 14] : ones, jp < 3 ? f[2][(4 * jp + 3) % 14] : ones);
      wg_wait<0>(); reg_fence(pk); reg_fence(pq);
#pragma unroll 1
      for (int pass = 0; pass < 2; pass++) {
        dual_softmax(pk, phiq);
        if (pass) break;
#pragma unroll
        for (int e = 0; e < 2; e++)
#pragma unroll
          for (int jp = 0; jp < 4; jp++)
            stsm4(srow + e * 8192 + (((2 * jp + stsm_hi) ^ (lane & 7)) << 4), phiq[e][2 * jp], phiq[2 + e][2 * jp],
                  jp < 3 ? phiq[e][(2 * jp + 1) % 7] : 0u, jp < 3 ? phiq[2 + e][(2 * jp + 1) % 7] : 0u);
        fence_async_smem();
        bar_sync<3, 256>();
        float kv[32], kw[32]; reg_def(kv); reg_def(kw);
        const uint64_t dP = mkdesc(sb + c * 8192, 4096, 1024, 1), dV = mkdesc(sb + 16384, 4096, 1024, 1);
        wg_fence();
#pragma unroll
        for (int s = 0; s < 4; s++) { mma_ss_64t(kv, dP + s * 128, dV + s * 128, s); mma_ss_64t(kw, dP + ABYTES / 16 + s * 128, dV + ABYTES / 16 + s * 128, s); }
        wg_commit();
        mbar_wait(barCS, 0);
        wg_wait<0>(); reg_fence(kv); reg_fence(kw);
#pragma unroll
        for (int i = 0; i < 32; i++) kv[i] += kw[i];
        float4* kvg = gKV + ((layer * 8 + r) * 2 + c) * 640 + (tid & 127);
#pragma unroll
        for (int i = 0; i < 5; i++) {
          float v0, v1, v2, v3;
          if (i == 4) { v0 = kv[28]; v1 = kv[29]; v2 = kv[30]; v3 = kv[31]; }
          else { v0 = c ? kv[12 + 4 * i] : kv[4 * i]; v1 = c ? kv[13 + 4 * i] : kv[1 + 4 * i]; v2 = c ? kv[14 + 4 * i] : kv[2 + 4 * i]; v3 = c ? kv[15 + 4 * i] : kv[3 + 4 * i]; }
          const bool use = i == 4 ? t == 0 : (i == 0 ? (c == 0 || t >= 2) : (i == 3 ? (c == 1 || t < 2) : true));
          if (use) asm volatile("red.relaxed.gpu.global.add.v4.f32 [%0], {%1,%2,%3,%4};" ::"l"(kvg + i * 128), "f"(v0), "f"(v1), "f"(v2), "f"(v3) : "memory");
        }
        __syncwarp();
        if (lane == 0) flag_arrive(gFlag + (FL_KV + layer * 8 + r) * 32);
        __syncwarp();
        STAMP(2 + layer * 12);
#pragma unroll
        for (int i = 0; i < 28; i++) pk[i] = pq[i];
      }
    }
    {
      if (elect) flag_wait(gFlag + (FL_KV + layer * 8 + r) * 32, epoch * 128);
      bar_wg(c);
      STAMP(3 + layer * 12);
      const float4* kvg = gKV + (layer * 8 + r) * 1280 + c * 640 + (tid & 127);
      uint4 kk[5];
#pragma unroll
      for (int i = 0; i < 5; i++) kk[i] = ldcg4(kvg + i * 128);
      uint32_t f[5][2];
#pragma unroll
      for (int i = 0; i < 5; i++) { f[i][0] = pack(__uint_as_float(kk[i].x), __uint_as_float(kk[i].y)); f[i][1] = pack(__uint_as_float(kk[i].z), __uint_as_float(kk[i].w)); }
      const uint32_t zm = c ? 0xFFFF0000u : 0xFFFFu;
      const uint32_t srow = abuf + 24576 + stsm_off;
#pragma unroll
      for (int jp = 0; jp < 4; jp++) {
        uint32_t v[2][2];
#pragma unroll
        for (int u = 0; u < 2; u++) {
          const int j = 2 * jp + u;
#pragma unroll
          for (int hh = 0; hh < 2; hh++) v[u][hh] = j == 7 ? f[4][hh] & zm : (c ? (j >= 3 ? f[(j + 2) % 5][hh] : 0u) : (j < 4 ? f[j % 5][hh] : 0u));
        }
        stsm4(srow + (((2 * jp + stsm_hi) ^ (lane & 7)) << 4), v[0][0], v[0][1], v[1][0], v[1][1]);
      }
      fence_async_smem();
      bar_sync<3, 256>();
      float num[32], nub[32]; reg_def(num); reg_def(nub);
      const uint64_t dK = mkdesc(sb + 24576, 4096, 1024, 1);
      wg_fence();
#pragma unroll
      for (int s = 0; s < 4; s++) {
        mma_rs_64(num, phiq[0][2 * s], phiq[2][2 * s], s < 3 ? phiq[0][(2 * s + 1) % 7] : 0u, s < 3 ? phiq[2][(2 * s + 1) % 7] : 0u, dK + s * 128, s);
        mma_rs_64(nub, phiq[1][2 * s], phiq[3][2 * s], s < 3 ? phiq[1][(2 * s + 1) % 7] : 0u, s < 3 ? phiq[3][(2 * s + 1) % 7] : 0u, dK + ABYTES / 16 + s * 128, s);
      }
      wg_commit();
      wg_wait<0>(); reg_fence(num); reg_fence(nub);
      bar_sync<3, 256>();
#pragma unroll
      for (int i = 12; i < 32; i++) num[i] += nub[i];
      float rd[4];
#pragma unroll
      for (int i = 0; i < 4; i++) rd[i] = __fdividef(1.f, __shfl_sync(~0u, num[28 + i], lane & ~3) + 1e-6f);
      unsigned char* img = gImg + (size_t)(G * 2 + c) * ABYTES;
#pragma unroll
      for (int j = 0; j < 7; j++) {
        const bool hb = j > 3 || (j == 3 && t >= 2);
        const float r0 = hb ? rd[1] : rd[0], r1 = hb ? rd[3] : rd[2];
        *reinterpret_cast<uint32_t*>(img + slice_off(j, 0)) = pack(num[4 * j] * r0, num[4 * j + 1] * r0);
        *reinterpret_cast<uint32_t*>(img + slice_off(j, 1)) = pack(num[4 * j + 2] * r1, num[4 * j + 3] * r1);
      }
      STAMP(4 + layer * 12);
      gather(fl, img);
      STAMP(5 + layer * 12);
    }
    {
      float acc[28], acc2[28]; reg_def(acc); reg_def(acc2); reg_fence(acc); reg_fence(acc2);
      int sl[4];
      ring.uniform();
#pragma unroll
      for (int st = 0; st < 4; st++) {
        const uint64_t db = mkdesc(ring.acquire(), 4096, 1024, 1);
        sl[st] = ring.advance();
#pragma unroll
        for (int s = 0; s < 7; s++) {
          const int ks = st * 7 + s;
          if (!(ks & 3)) mbar_wait(barAc + (ks >> 2) * 8, apar);
          if (!(ks & 3) || !s) wg_fence();
          if (ks & 1) mma_ss_56(acc2, dA + ks * 128, db + s * 128, ks > 1); else mma_ss_56(acc, dA + ks * 128, db + s * 128, ks > 1);
        }
        wg_commit();
      }
      wg_wait<0>(); reg_fence(acc); reg_fence(acc2);
      unsigned char* img = gImg + (size_t)(32 + G * 2 + c) * ABYTES;
#pragma unroll
      for (int hh = 0; hh < 2; hh++) {
        float s = 0.f, q = 0.f;
#pragma unroll
        for (int j = 0; j < 7; j++) {
          xs[j][hh] = pack(lo(xs[j][hh]) + (acc[4 * j + 2 * hh] + acc2[4 * j + 2 * hh]), hi(xs[j][hh]) + (acc[4 * j + 2 * hh + 1] + acc2[4 * j + 2 * hh + 1]));
          *reinterpret_cast<uint32_t*>(img + slice_off(j, hh)) = xs[j][hh];
          s += lo(xs[j][hh]) + hi(xs[j][hh]);
        }
        s += __shfl_xor_sync(~0u, s, 1); s += __shfl_xor_sync(~0u, s, 2);
        s *= 1.f / 56.f;
#pragma unroll
        for (int j = 0; j < 7; j++) { const float a = lo(xs[j][hh]) - s, b = hi(xs[j][hh]) - s; q = fmaf(a, a, q); q = fmaf(b, b, q); }
        q += __shfl_xor_sync(~0u, q, 1); q += __shfl_xor_sync(~0u, q, 2);
        if (t == 0) gStat[(size_t)(row0 + w * 16 + hh * 8 + g) * 8 + r] = make_float2(s, q);
      }
#pragma unroll
      for (int j = 0; j < 7; j++) xs[j][0] = xs[j][1] = 0u;
      STAMP(6 + layer * 12);
      gather(fl + 32, img);
#pragma unroll
      for (int st = 0; st < 4; st++) ring.release(sl[st], elect);
      STAMP(7 + layer * 12);
    }
    {
      uint32_t hf[28][2];
      {
        float acc[112]; reg_def(acc);
        int prev = 0, prev2 = 0;
        load_stats(gStat);
        ring.uniform();
#pragma unroll UNR
        for (int st = 0; st < 14; st++) {
          if (!(st & 1)) mbar_wait(barAc + (st >> 1) * 8, apar);
          const uint64_t da = dA + st * 256, db = mkdesc(ring.acquire(), 2048, 512, 2);
          wg_fence();
          mma_ss_224(acc, da, db, 1);
          mma_ss_224(acc, da + 128, db + 64, 1);
          wg_commit();
          if (st > 1) { wg_wait<2>(); ring.release(prev2, elect); }
          prev2 = prev; prev = ring.advance();
        }
        finish_stats();
        mbar_wait(barCS + 8, 0);
        wg_wait<0>(); reg_fence(acc);
        ring.release(prev2, elect); ring.release(prev, elect);
        STAMP(8 + layer * 12);
        const float2* bs = reinterpret_cast<const float2*>(sg + OFF_B1) + t;
        const float2* cs = reinterpret_cast<const float2*>(sg + OFF_CS + 768) + t;
        const float mr0 = -mean[0] * rstd[0], mr1 = -mean[1] * rstd[1];
#pragma unroll
        for (int j = 0; j < 28; j++) {
          const float2 b = bs[4 * j], s = cs[4 * j];
          hf[j][0] = relu_sq(fmaf(acc[4 * j], rstd[0], fmaf(s.x, mr0, b.x)), fmaf(acc[4 * j + 1], rstd[0], fmaf(s.y, mr0, b.y)));
          hf[j][1] = relu_sq(fmaf(acc[4 * j + 2], rstd[1], fmaf(s.x, mr1, b.x)), fmaf(acc[4 * j + 3], rstd[1], fmaf(s.y, mr1, b.y)));
        }
      }
      unsigned char* pd[2]; int pstr[2];
#pragma unroll
      for (int hh = 0; hh < 2; hh++) {
        const bool own = 2 * w + hh == r;
        pd[hh] = own ? sg + c * ABYTES + (lane >> 4) * 1024 + (r ^ 1) * 128 + (lane & 15) * 8
                     : gP + (size_t)(((G * 2 + c) * 8 + 2 * w + hh) * 8 + r) * 7168 + lane * 8;
        pstr[hh] = own ? 2048 : 256;
      }
      uint2 pk[8] = {};
      ring.uniform();
#pragma unroll 1
      for (int ch = 0; ch < 7; ch++) {
        float acc[32], acc2[32]; reg_def(acc); reg_def(acc2);
        const uint64_t db0 = mkdesc(ring.acquire(), 4096, 1024, 1);
        const int sl0 = ring.advance();
        const uint64_t db1 = mkdesc(ring.acquire(), 4096, 1024, 1);
        const int sl1 = ring.advance();
        wg_fence();
#pragma unroll
        for (int s = 0; s < 7; s++) {
          mma_rs_64(acc, hf[2 * s][0], hf[2 * s][1], hf[2 * s + 1][0], hf[2 * s + 1][1], db0 + s * 128, s);
          mma_rs_64(acc2, hf[14 + 2 * s][0], hf[14 + 2 * s][1], hf[15 + 2 * s][0], hf[15 + 2 * s][1], db1 + s * 128, s);
        }
        wg_commit();
        if (ch > 0) {
#pragma unroll
          for (int i = 0; i < 8; i++) { *reinterpret_cast<uint2*>(pd[i & 1]) = pk[i]; pd[i & 1] += pstr[i & 1]; }
        }
        wg_wait<0>(); reg_fence(acc); reg_fence(acc2); ring.release(sl0, elect); ring.release(sl1, elect);
#pragma unroll
        for (int i = 0; i < 8; i++) {
          const int b = (i >> 1) * 8 + (i & 1) * 2;
          pk[i] = make_uint2((pack(acc[b] + acc2[b], acc[b + 1] + acc2[b + 1]) & ~1u) | (layer ^ 1), pack(acc[b + 4] + acc2[b + 4], acc[b + 5] + acc2[b + 5]));
        }
      }
#pragma unroll
      for (int i = 0; i < 8; i++) { *reinterpret_cast<uint2*>(pd[i & 1]) = pk[i]; pd[i & 1] += pstr[i & 1]; }
      STAMP(9 + layer * 12);
    }
    {
      uint32_t bx[14];
#pragma unroll
      for (int j = 0; j < 14; j++) bx[j] = __ldg(reinterpret_cast<const uint32_t*>(b2 + (j >> 1) * 64 + w * 16 + (j & 1) * 8 + 2 * t));
      const unsigned char* psrc = gP + (size_t)(((G * 2 + c) * 8 + r) * 8) * 7168 + w * 256 + lane * 8;
      unsigned char* img = gImg + (size_t)(64 + G * 2 + c) * ABYTES;
      uint2 pv[7][7];
      const unsigned char* ps[7];
#pragma unroll
      for (int s = 0; s < 7; s++) ps[s] = psrc + ((r + 1 + s) & 7) * 7168;
#pragma unroll
      for (int i = 0; i < 5; i++)
#pragma unroll
        for (int s = 0; s < 7; s++) pv[s][i] = ldcg2(ps[s] + i * 1024);
      bar_wg(c);
      const uint32_t off = w * 2048 + r * 128 + lane * 4;
      unsigned char* dst = layer ? reinterpret_cast<unsigned char*>(out + (size_t)(row0 + r * 8 + g) * DM + w * 16 + 4 * t) : img + off;
      float sm = 0.f, q = 0.f;
#pragma unroll
      for (int i = 0; i < 7; i++) {
        const uint2 own = *reinterpret_cast<const uint2*>(sg + c * ABYTES + i * 8192 + w * 2048 + (lane >> 4) * 1024 + (r ^ 1) * 128 + (lane & 15) * 8);
#pragma unroll 1
        for (int n = 0; n < (1 << 16); n++) {
          const uint32_t all = pv[0][i].x & pv[1][i].x & pv[2][i].x & pv[3][i].x & pv[4][i].x & pv[5][i].x & pv[6][i].x;
          const uint32_t any = pv[0][i].x | pv[1][i].x | pv[2][i].x | pv[3][i].x | pv[4][i].x | pv[5][i].x | pv[6][i].x;
          if (!__any_sync(~0u, (layer ? any : ~all) & 1u)) break;
#pragma unroll
          for (int s = 0; s < 7; s++) pv[s][i] = ldcg2(ps[s] + i * 1024);
        }
        if (i < 2) {
#pragma unroll
          for (int s = 0; s < 7; s++) pv[s][5 + (i & 1)] = ldcg2(ps[s] + (5 + i) * 1024);
        }
#pragma unroll
        for (int jj = 0; jj < 2; jj++) {
          const int j = 2 * i + jj;
          const uint32_t xo = lds32(abuf + off + i * 8192 + jj * 1024), uo = jj ? own.y : own.x;
          float y0 = lo(bx[j]) + lo(xo) + lo(uo), y1 = hi(bx[j]) + hi(xo) + hi(uo);
#pragma unroll
          for (int s = 0; s < 7; s++) { const uint32_t u = jj ? pv[s][i].y : pv[s][i].x; y0 += lo(u); y1 += hi(u); }
          bx[j] = pack(y0, y1);
          if (!layer) *reinterpret_cast<uint32_t*>(dst + (i * 8 + jj) * 1024) = bx[j];
          sm += lo(bx[j]) + hi(bx[j]);
        }
        if (layer) {
          const int sl = (lane & ~3) | ((t & 1) << 1);
          const uint32_t a0 = __shfl_sync(~0u, bx[2 * i], sl), a1 = __shfl_sync(~0u, bx[2 * i], sl + 1);
          const uint32_t b0 = __shfl_sync(~0u, bx[2 * i + 1], sl), b1v = __shfl_sync(~0u, bx[2 * i + 1], sl + 1);
          *reinterpret_cast<uint2*>(dst + i * 128) = t < 2 ? make_uint2(a0, a1) : make_uint2(b0, b1v);
        }
      }
      if (layer) break;
      sm += __shfl_xor_sync(~0u, sm, 1); sm += __shfl_xor_sync(~0u, sm, 2);
      sm *= 1.f / 112.f;
#pragma unroll
      for (int j = 0; j < 14; j++) { const float a = lo(bx[j]) - sm, b = hi(bx[j]) - sm; q = fmaf(a, a, q); q = fmaf(b, b, q); }
      q += __shfl_xor_sync(~0u, q, 1); q += __shfl_xor_sync(~0u, q, 2);
      if (t < 2) gStat[(size_t)(2048 + row0 + r * 8 + g) * 8 + 2 * w + t] = make_float2(sm, q * 0.5f);
      STAMP(11);
      gather(fl + 64, img);
      STAMP(12);
    }
  }
  STAMP(30);
  if (tid == 0) asm volatile("red.relaxed.gpu.global.add.u32 [%0], 1;" ::"l"(gFlag + FL_DONE * 32) : "memory");
  }
}

typedef CUresult (*EncFn)(CUtensorMap*, CUtensorMapDataType, cuuint32_t, void*, const cuuint64_t*, const cuuint64_t*,
                          const cuuint32_t*, const cuuint32_t*, CUtensorMapInterleave, CUtensorMapSwizzle,
                          CUtensorMapL2promotion, CUtensorMapFloatOOBfill);

void make_map(EncFn enc, CUtensorMap* m, void* p, int rank, uint64_t d0, uint64_t d1, uint64_t d2, uint64_t s1, uint64_t s2,
              uint32_t b0, uint32_t b1, uint32_t b2, CUtensorMapSwizzle sw) {
  cuuint64_t dims[3] = {d0, d1, d2}, strides[2] = {s1, s2};
  cuuint32_t box[3] = {b0, b1, b2}, es[3] = {1, 1, 1};
  enc(m, CU_TENSOR_MAP_DATA_TYPE_BFLOAT16, rank, p, dims, strides, box, es, CU_TENSOR_MAP_INTERLEAVE_NONE, sw,
      CU_TENSOR_MAP_L2_PROMOTION_L2_128B, CU_TENSOR_MAP_FLOAT_OOB_FILL_NONE);
}

}

extern "C" void kernel_launch(void* const* d_in, const int* in_sizes, int n_in, void* d_out, int out_size) {
  static EncFn enc = nullptr;
  if (!enc) {
    cudaDriverEntryPointQueryResult st;
    void* fn = nullptr;
    cudaGetDriverEntryPoint("cuTensorMapEncodeTiled", &fn, cudaEnableDefault, &st);
    enc = (EncFn)fn;
    cudaFuncSetAttribute(fused_kernel, cudaFuncAttributeMaxDynamicSharedMemorySize, SMEM_BYTES);
  }
  CUtensorMap mQKV, mWO, mW1, mW2, mX;
  make_map(enc, &mX, d_in[0], 2, 448, 2048, 1, 896, 0, 64, 64, 1, CU_TENSOR_MAP_SWIZZLE_128B);
  make_map(enc, &mQKV, d_in[1], 3, 448, 448, 3, 2688, 896, 64, 32, 3, CU_TENSOR_MAP_SWIZZLE_128B);
  make_map(enc, &mWO, d_in[3], 2, 448, 448, 1, 896, 0, 64, 112, 1, CU_TENSOR_MAP_SWIZZLE_128B);
  make_map(enc, &mW1, d_in[5], 3, 32, 448, 56, 3584, 64, 32, 32, 7, CU_TENSOR_MAP_SWIZZLE_64B);
  make_map(enc, &mW2, d_in[7], 2, 448, 1792, 1, 896, 0, 64, 112, 1, CU_TENSOR_MAP_SWIZZLE_128B);
  fused_kernel<<<NCTA, 384, SMEM_BYTES, cudaStreamPerThread>>>(
      mQKV, mWO, mW1, mW2, mX, (const __nv_bfloat16*)d_in[2], (const __nv_bfloat16*)d_in[6],
      (const __nv_bfloat16*)d_in[8], (const __nv_bfloat16*)d_in[1], (const __nv_bfloat16*)d_in[3], (const __nv_bfloat16*)d_in[5],
      (const __nv_bfloat16*)d_in[7], (__nv_bfloat16*)d_out);
}
```

```cpp
#include <cuda_runtime.h>
#include <cuda_bf16.h>
#include <cuda.h>
#include <stdint.h>

namespace {

constexpr int DM = 448, NCTA = 128;
constexpr int ABYTES = 57344;
constexpr int SLOT = 14336, NSLOT = 7;
constexpr int OFF_RING = 2 * ABYTES;
constexpr int OFF_WPHI = OFF_RING + NSLOT * SLOT;
constexpr int OFF_B1 = OFF_WPHI + 8192;
constexpr int OFF_CS = OFF_B1 + 896;
constexpr int OFF_BAR = OFF_CS + 1664;
constexpr int SMEM_BYTES = OFF_BAR + 272 + 1024;
constexpr int TILES_PER_LAYER = 46;

__device__ __align__(1024) unsigned char gP[16 * 2 * 8 * 8 * 7168];
__device__ __align__(1024) unsigned char gImg[3 * 32 * ABYTES];
__device__ __align__(1024) float2 gStat[2 * 2048 * 8];
__device__ __align__(1024) float4 gKV[2 * 8 * 2 * 5 * 128];
__device__ __align__(1024) float4 gCS[8 * 16 * 104];
__device__ __align__(128) unsigned gFlag[(2 * 32 * 7 + 32 + 1 + 16) * 32];
#define STAMP(i)

__device__ __forceinline__ uint32_t smem_u32(const void* p) { return (uint32_t)__cvta_generic_to_shared(p); }
__device__ __forceinline__ void mbar_init(uint32_t b, int c) { asm volatile("mbarrier.init.shared::cta.b64 [%0], %1;" ::"r"(b), "r"(c)); }
__device__ __forceinline__ void mbar_expect(uint32_t b, int bytes) { asm volatile("mbarrier.arrive.expect_tx.shared::cta.b64 _, [%0], %1;" ::"r"(b), "r"(bytes) : "memory"); }
__device__ __forceinline__ void mbar_arrive(uint32_t b) { asm volatile("mbarrier.arrive.shared::cta.b64 _, [%0];" ::"r"(b) : "memory"); }
__device__ __forceinline__ void mbar_wait(uint32_t b, int par) {
  uint32_t ok; int n = 0;
#pragma unroll 1
  while (true) {
    asm volatile("{.reg .pred p; mbarrier.try_wait.parity.shared::cta.b64 p, [%1], %2; selp.u32 %0,1,0,p;}" : "=r"(ok) : "r"(b), "r"(par) : "memory");
    if (ok) break;
    if (++n > (1 << 22)) break;
  }
}
__device__ __forceinline__ void flag_wait(const unsigned* f, unsigned target) {
  unsigned v; int n = 0;
#pragma unroll 1
  while (true) {
    asm volatile("ld.acquire.gpu.global.u32 %0, [%1];" : "=r"(v) : "l"(f) : "memory");
    if ((int)(v - target) >= 0) break;
    if (++n > (1 << 21)) break;
  }
}
__device__ __forceinline__ void flag_arrive(unsigned* f) { asm volatile("red.release.gpu.global.add.u32 [%0], 1;" ::"l"(f) : "memory"); }
__device__ __forceinline__ bool elect_one() {
  uint32_t p; asm volatile("{.reg .pred P; elect.sync _|P, 0xffffffff; selp.u32 %0, 1, 0, P;}" : "=r"(p)); return p;
}
__device__ __forceinline__ void fence_async() { asm volatile("fence.proxy.async.global;" ::: "memory"); }
__device__ __forceinline__ void fence_async_smem() { asm volatile("fence.proxy.async.shared::cta;" ::: "memory"); }
template <int ID, int N> __device__ __forceinline__ void bar_sync() { asm volatile("bar.sync %0, %1;" ::"n"(ID), "n"(N) : "memory"); }
__device__ __forceinline__ void bar_wg(int c) { if (c) bar_sync<2, 128>(); else bar_sync<1, 128>(); }
__device__ __forceinline__ void wg_fence() { asm volatile("wgmma.fence.sync.aligned;" ::: "memory"); }
__device__ __forceinline__ void wg_commit() { asm volatile("wgmma.commit_group.sync.aligned;" ::: "memory"); }
template <int N> __device__ __forceinline__ void wg_wait() { asm volatile("wgmma.wait_group.sync.aligned %0;" ::"n"(N) : "memory"); }
template <int N> __device__ __forceinline__ void reg_fence(float (&d)[N]) {
#pragma unroll
  for (int i = 0; i < N; i++) asm volatile("" : "+f"(d[i])::"memory");
}
template <int N> __device__ __forceinline__ void reg_def(float (&d)[N]) {
#pragma unroll
  for (int i = 0; i < N; i++) d[i] = 0.f;
}
__device__ __forceinline__ uint64_t mkdesc(uint32_t addr, uint32_t lbo, uint32_t sbo, uint64_t swz) {
  return (uint64_t)((addr & 0x3FFFF) >> 4) | ((uint64_t)(lbo >> 4) << 16) | ((uint64_t)(sbo >> 4) << 32) | (swz << 62);
}
__device__ __forceinline__ uint32_t pack(float a, float b) {
  uint32_t r; asm("cvt.rn.bf16x2.f32 %0, %1, %2;" : "=r"(r) : "f"(b), "f"(a)); return r;
}
__device__ __forceinline__ uint32_t relu_sq(float a, float b) {
  uint32_t r; asm("{.reg .b32 v; cvt.rn.relu.bf16x2.f32 v, %1, %2; mul.rn.bf16x2 %0, v, v;}" : "=r"(r) : "f"(b), "f"(a)); return r;
}
__device__ __forceinline__ float lo(uint32_t u) { return __uint_as_float(u << 16); }
__device__ __forceinline__ float hi(uint32_t u) { return __uint_as_float(u & 0xFFFF0000u); }
__device__ __forceinline__ float ex2(float x) { float y; asm("ex2.approx.ftz.f32 %0, %1;" : "=f"(y) : "f"(x)); return y; }
__device__ __forceinline__ void stsm4(uint32_t a, uint32_t r0, uint32_t r1, uint32_t r2, uint32_t r3) {
  asm volatile("stmatrix.sync.aligned.m8n8.x4.shared.b16 [%0], {%1,%2,%3,%4};" ::"r"(a), "r"(r0), "r"(r1), "r"(r2), "r"(r3) : "memory");
}
__device__ __forceinline__ void tma3(uint32_t dst, const CUtensorMap* m, int c0, int c1, int c2, uint32_t bar) {
  asm volatile("cp.async.bulk.tensor.3d.shared::cluster.global.mbarrier::complete_tx::bytes [%0], [%1, {%3,%4,%5}], [%2];"
               ::"r"(dst), "l"(m), "r"(bar), "r"(c0), "r"(c1), "r"(c2) : "memory");
}
__device__ __forceinline__ void tma2(uint32_t dst, const CUtensorMap* m, int c0, int c1, uint32_t bar) {
  asm volatile("cp.async.bulk.tensor.2d.shared::cluster.global.mbarrier::complete_tx::bytes [%0], [%1, {%3,%4}], [%2];"
               ::"r"(dst), "l"(m), "r"(bar), "r"(c0), "r"(c1) : "memory");
}
__device__ __forceinline__ uint32_t lds32(uint32_t a) { uint32_t v; asm volatile("ld.shared.u32 %0, [%1];" : "=r"(v) : "r"(a) : "memory"); return v; }
__device__ __forceinline__ void bulk_ld(uint32_t dst, const void* src, int bytes, uint32_t bar) {
  asm volatile("cp.async.bulk.shared::cluster.global.mbarrier::complete_tx::bytes [%0], [%1], %2, [%3];" ::"r"(dst), "l"(src), "r"(bytes), "r"(bar) : "memory");
}
__device__ __forceinline__ uint4 ldcg4(const void* p) {
  uint4 v; asm volatile("ld.global.cg.v4.u32 {%0,%1,%2,%3}, [%4];" : "=r"(v.x), "=r"(v.y), "=r"(v.z), "=r"(v.w) : "l"(p) : "memory"); return v;
}

__device__ __forceinline__ uint2 ldcg2(const void* p) {
  uint2 v; asm volatile("ld.global.cg.v2.u32 {%0,%1}, [%2];" : "=r"(v.x), "=r"(v.y) : "l"(p) : "memory"); return v;
}

__device__ __forceinline__ void mma_ss_184(float (&d)[92], uint64_t da, uint64_t db, int acc) {
  asm volatile("{.reg .pred p; setp.ne.b32 p, %94, 0;\n"
    "wgmma.mma_async.sync.aligned.m64n184k16.f32.bf16.bf16 {%0,%1,%2,%3,%4,%5,%6,%7,%8,%9,%10,%11,%12,%13,%14,%15,%16,%17,%18,%19,%20,%21,%22,%23,%24,%25,%26,%27,%28,%29,%30,%31,%32,%33,%34,%35,%36,%37,%38,%39,%40,%41,%42,%43,%44,%45,%46,%47,%48,%49,%50,%51,%52,%53,%54,%55,%56,%57,%58,%59,%60,%61,%62,%63,%64,%65,%66,%67,%68,%69,%70,%71,%72,%73,%74,%75,%76,%77,%78,%79,%80,%81,%82,%83,%84,%85,%86,%87,%88,%89,%90,%91}, %92, %93, p, 1, 1, 0, 1;}\n"
    : "+f"(d[0]),"+f"(d[1]),"+f"(d[2]),"+f"(d[3]),"+f"(d[4]),"+f"(d[5]),"+f"(d[6]),"+f"(d[7]),"+f"(d[8]),"+f"(d[9]),"+f"(d[10]),"+f"(d[11]),"+f"(d[12]),"+f"(d[13]),"+f"(d[14]),"+f"(d[15]),"+f"(d[16]),"+f"(d[17]),"+f"(d[18]),"+f"(d[19]),"+f"(d[20]),"+f"(d[21]),"+f"(d[22]),"+f"(d[23]),"+f"(d[24]),"+f"(d[25]),"+f"(d[26]),"+f"(d[27]),"+f"(d[28]),"+f"(d[29]),"+f"(d[30]),"+f"(d[31]),"+f"(d[32]),"+f"(d[33]),"+f"(d[34]),"+f"(d[35]),"+f"(d[36]),"+f"(d[37]),"+f"(d[38]),"+f"(d[39]),"+f"(d[40]),"+f"(d[41]),"+f"(d[42]),"+f"(d[43]),"+f"(d[44]),"+f"(d[45]),"+f"(d[46]),"+f"(d[47]),"+f"(d[48]),"+f"(d[49]),"+f"(d[50]),"+f"(d[51]),"+f"(d[52]),"+f"(d[53]),"+f"(d[54]),"+f"(d[55]),"+f"(d[56]),"+f"(d[57]),"+f"(d[58]),"+f"(d[59]),"+f"(d[60]),"+f"(d[61]),"+f"(d[62]),"+f"(d[63]),"+f"(d[64]),"+f"(d[65]),"+f"(d[66]),"+f"(d[67]),"+f"(d[68]),"+f"(d[69]),"+f"(d[70]),"+f"(d[71]),"+f"(d[72]),"+f"(d[73]),"+f"(d[74]),"+f"(d[75]),"+f"(d[76]),"+f"(d[77]),"+f"(d[78]),"+f"(d[79]),"+f"(d[80]),"+f"(d[81]),"+f"(d[82]),"+f"(d[83]),"+f"(d[84]),"+f"(d[85]),"+f"(d[86]),"+f"(d[87]),"+f"(d[88]),"+f"(d[89]),"+f"(d[90]),"+f"(d[91])
    : "l"(da), "l"(db), "r"(acc));
}
__device__ __forceinline__ void mma_ss_224(float (&d)[112], uint64_t da, uint64_t db, int acc) {
  asm volatile("{.reg .pred p; setp.ne.b32 p, %114, 0;\n"
    "wgmma.mma_async.sync.aligned.m64n224k16.f32.bf16.bf16 {%0,%1,%2,%3,%4,%5,%6,%7,%8,%9,%10,%11,%12,%13,%14,%15,%16,%17,%18,%19,%20,%21,%22,%23,%24,%25,%26,%27,%28,%29,%30,%31,%32,%33,%34,%35,%36,%37,%38,%39,%40,%41,%42,%43,%44,%45,%46,%47,%48,%49,%50,%51,%52,%53,%54,%55,%56,%57,%58,%59,%60,%61,%62,%63,%64,%65,%66,%67,%68,%69,%70,%71,%72,%73,%74,%75,%76,%77,%78,%79,%80,%81,%82,%83,%84,%85,%86,%87,%88,%89,%90,%91,%92,%93,%94,%95,%96,%97,%98,%99,%100,%101,%102,%103,%104,%105,%106,%107,%108,%109,%110,%111}, %112, %113, p, 1, 1, 0, 1;}\n"
    : "+f"(d[0]),"+f"(d[1]),"+f"(d[2]),"+f"(d[3]),"+f"(d[4]),"+f"(d[5]),"+f"(d[6]),"+f"(d[7]),"+f"(d[8]),"+f"(d[9]),"+f"(d[10]),"+f"(d[11]),"+f"(d[12]),"+f"(d[13]),"+f"(d[14]),"+f"(d[15]),"+f"(d[16]),"+f"(d[17]),"+f"(d[18]),"+f"(d[19]),"+f"(d[20]),"+f"(d[21]),"+f"(d[22]),"+f"(d[23]),"+f"(d[24]),"+f"(d[25]),"+f"(d[26]),"+f"(d[27]),"+f"(d[28]),"+f"(d[29]),"+f"(d[30]),"+f"(d[31]),"+f"(d[32]),"+f"(d[33]),"+f"(d[34]),"+f"(d[35]),"+f"(d[36]),"+f"(d[37]),"+f"(d[38]),"+f"(d[39]),"+f"(d[40]),"+f"(d[41]),"+f"(d[42]),"+f"(d[43]),"+f"(d[44]),"+f"(d[45]),"+f"(d[46]),"+f"(d[47]),"+f"(d[48]),"+f"(d[49]),"+f"(d[50]),"+f"(d[51]),"+f"(d[52]),"+f"(d[53]),"+f"(d[54]),"+f"(d[55]),"+f"(d[56]),"+f"(d[57]),"+f"(d[58]),"+f"(d[59]),"+f"(d[60]),"+f"(d[61]),"+f"(d[62]),"+f"(d[63]),"+f"(d[64]),"+f"(d[65]),"+f"(d[66]),"+f"(d[67]),"+f"(d[68]),"+f"(d[69]),"+f"(d[70]),"+f"(d[71]),"+f"(d[72]),"+f"(d[73]),"+f"(d[74]),"+f"(d[75]),"+f"(d[76]),"+f"(d[77]),"+f"(d[78]),"+f"(d[79]),"+f"(d[80]),"+f"(d[81]),"+f"(d[82]),"+f"(d[83]),"+f"(d[84]),"+f"(d[85]),"+f"(d[86]),"+f"(d[87]),"+f"(d[88]),"+f"(d[89]),"+f"(d[90]),"+f"(d[91]),"+f"(d[92]),"+f"(d[93]),"+f"(d[94]),"+f"(d[95]),"+f"(d[96]),"+f"(d[97]),"+f"(d[98]),"+f"(d[99]),"+f"(d[100]),"+f"(d[101]),"+f"(d[102]),"+f"(d[103]),"+f"(d[104]),"+f"(d[105]),"+f"(d[106]),"+f"(d[107]),"+f"(d[108]),"+f"(d[109]),"+f"(d[110]),"+f"(d[111])
    : "l"(da), "l"(db), "r"(acc));
}
__device__ __forceinline__ void mma_ss_56(float (&d)[28], uint64_t da, uint64_t db, int acc) {
  asm volatile("{.reg .pred p; setp.ne.b32 p, %30, 0;\n"
    "wgmma.mma_async.sync.aligned.m64n56k16.f32.bf16.bf16 {%0,%1,%2,%3,%4,%5,%6,%7,%8,%9,%10,%11,%12,%13,%14,%15,%16,%17,%18,%19,%20,%21,%22,%23,%24,%25,%26,%27}, %28, %29, p, 1, 1, 0, 1;}\n"
    : "+f"(d[0]),"+f"(d[1]),"+f"(d[2]),"+f"(d[3]),"+f"(d[4]),"+f"(d[5]),"+f"(d[6]),"+f"(d[7]),"+f"(d[8]),"+f"(d[9]),"+f"(d[10]),"+f"(d[11]),"+f"(d[12]),"+f"(d[13]),"+f"(d[14]),"+f"(d[15]),"+f"(d[16]),"+f"(d[17]),"+f"(d[18]),"+f"(d[19]),"+f"(d[20]),"+f"(d[21]),"+f"(d[22]),"+f"(d[23]),"+f"(d[24]),"+f"(d[25]),"+f"(d[26]),"+f"(d[27])
    : "l"(da), "l"(db), "r"(acc));
}
__device__ __forceinline__ void mma_rs_56(float (&d)[28], uint32_t a0, uint32_t a1, uint32_t a2, uint32_t a3, uint64_t db, int acc) {
  asm volatile("{.reg .pred p; setp.ne.b32 p, %33, 0;\n"
    "wgmma.mma_async.sync.aligned.m64n56k16.f32.bf16.bf16 {%0,%1,%2,%3,%4,%5,%6,%7,%8,%9,%10,%11,%12,%13,%14,%15,%16,%17,%18,%19,%20,%21,%22,%23,%24,%25,%26,%27}, {%28,%29,%30,%31}, %32, p, 1, 1, 1;}\n"
    : "+f"(d[0]),"+f"(d[1]),"+f"(d[2]),"+f"(d[3]),"+f"(d[4]),"+f"(d[5]),"+f"(d[6]),"+f"(d[7]),"+f"(d[8]),"+f"(d[9]),"+f"(d[10]),"+f"(d[11]),"+f"(d[12]),"+f"(d[13]),"+f"(d[14]),"+f"(d[15]),"+f"(d[16]),"+f"(d[17]),"+f"(d[18]),"+f"(d[19]),"+f"(d[20]),"+f"(d[21]),"+f"(d[22]),"+f"(d[23]),"+f"(d[24]),"+f"(d[25]),"+f"(d[26]),"+f"(d[27])
    : "r"(a0), "r"(a1), "r"(a2), "r"(a3), "l"(db), "r"(acc));
}
__device__ __forceinline__ void mma_ss_64t(float (&d)[32], uint64_t da, uint64_t db, int acc) {
  asm volatile("{.reg .pred p; setp.ne.b32 p, %34, 0;\n"
    "wgmma.mma_async.sync.aligned.m64n64k16.f32.bf16.bf16 {%0,%1,%2,%3,%4,%5,%6,%7,%8,%9,%10,%11,%12,%13,%14,%15,%16,%17,%18,%19,%20,%21,%22,%23,%24,%25,%26,%27,%28,%29,%30,%31}, %32, %33, p, 1, 1, 1, 1;}\n"
    : "+f"(d[0]),"+f"(d[1]),"+f"(d[2]),"+f"(d[3]),"+f"(d[4]),"+f"(d[5]),"+f"(d[6]),"+f"(d[7]),"+f"(d[8]),"+f"(d[9]),"+f"(d[10]),"+f"(d[11]),"+f"(d[12]),"+f"(d[13]),"+f"(d[14]),"+f"(d[15]),"+f"(d[16]),"+f"(d[17]),"+f"(d[18]),"+f"(d[19]),"+f"(d[20]),"+f"(d[21]),"+f"(d[22]),"+f"(d[23]),"+f"(d[24]),"+f"(d[25]),"+f"(d[26]),"+f"(d[27]),"+f"(d[28]),"+f"(d[29]),"+f"(d[30]),"+f"(d[31])
    : "l"(da), "l"(db), "r"(acc));
}
__device__ __forceinline__ void mma_rs_64(float (&d)[32], uint32_t a0, uint32_t a1, uint32_t a2, uint32_t a3, uint64_t db, int acc) {
  asm volatile("{.reg .pred p; setp.ne.b32 p, %37, 0;\n"
    "wgmma.mma_async.sync.aligned.m64n64k16.f32.bf16.bf16 {%0,%1,%2,%3,%4,%5,%6,%7,%8,%9,%10,%11,%12,%13,%14,%15,%16,%17,%18,%19,%20,%21,%22,%23,%24,%25,%26,%27,%28,%29,%30,%31}, {%32,%33,%34,%35}, %36, p, 1, 1, 1;}\n"
    : "+f"(d[0]),"+f"(d[1]),"+f"(d[2]),"+f"(d[3]),"+f"(d[4]),"+f"(d[5]),"+f"(d[6]),"+f"(d[7]),"+f"(d[8]),"+f"(d[9]),"+f"(d[10]),"+f"(d[11]),"+f"(d[12]),"+f"(d[13]),"+f"(d[14]),"+f"(d[15]),"+f"(d[16]),"+f"(d[17]),"+f"(d[18]),"+f"(d[19]),"+f"(d[20]),"+f"(d[21]),"+f"(d[22]),"+f"(d[23]),"+f"(d[24]),"+f"(d[25]),"+f"(d[26]),"+f"(d[27]),"+f"(d[28]),"+f"(d[29]),"+f"(d[30]),"+f"(d[31])
    : "r"(a0), "r"(a1), "r"(a2), "r"(a3), "l"(db), "r"(acc));
}

__device__ __forceinline__ void dual_softmax(const float (&p)[28], uint32_t (&phi)[4][7]) {
  constexpr float L2E = 1.4426950408889634f;
#pragma unroll
  for (int i = 0; i < 4; i++) {
    float mx = p[i], mn = p[i];
#pragma unroll
    for (int j = 1; j < 7; j++) { mx = fmaxf(mx, p[4 * j + i]); mn = fminf(mn, p[4 * j + i]); }
    mx = fmaxf(mx, __shfl_xor_sync(~0u, mx, 1)); mn = fminf(mn, __shfl_xor_sync(~0u, mn, 1));
    mx = fmaxf(mx, __shfl_xor_sync(~0u, mx, 2)); mn = fminf(mn, __shfl_xor_sync(~0u, mn, 2));
    float a[7], b[7], sa = 0.f, sb = 0.f;
    const float mxl = mx * L2E, mnl = mn * L2E;
#pragma unroll
    for (int j = 0; j < 7; j++) {
      a[j] = ex2(fmaf(p[4 * j + i], L2E, -mxl)); b[j] = ex2(fmaf(p[4 * j + i], -L2E, mnl));
      sa += a[j]; sb += b[j];
    }
    sa += __shfl_xor_sync(~0u, sa, 1); sb += __shfl_xor_sync(~0u, sb, 1);
    sa += __shfl_xor_sync(~0u, sa, 2); sb += __shfl_xor_sync(~0u, sb, 2);
    const float ra = __fdividef(1.f, sa), rb = __fdividef(1.f, sb);
#pragma unroll
    for (int j = 0; j < 7; j++) phi[i][j] = pack(a[j] * ra, b[j] * rb);
  }
}

struct Ring {
  uint32_t full, empty, base; int slot, par;
  __device__ __forceinline__ void uniform() { slot = __shfl_sync(~0u, slot, 0); par = __shfl_sync(~0u, par, 0); }
  __device__ __forceinline__ uint32_t acquire() { mbar_wait(full + slot * 8, par); return base + slot * SLOT; }
  __device__ __forceinline__ int advance() { int s = slot; if (++slot == NSLOT) { slot = 0; par ^= 1; } return s; }
  __device__ __forceinline__ void release(int s, bool elect) { if (elect) mbar_arrive(empty + s * 8); }
};
constexpr int UNR = 14;
constexpr int FL_KV = 448, FL_CS = FL_KV + 16, FL_DONE = FL_KV + 32;

__global__ void __launch_bounds__(384, 1)
fused_kernel(const __grid_constant__ CUtensorMap mQKV, const __grid_constant__ CUtensorMap mWO,
             const __grid_constant__ CUtensorMap mW1, const __grid_constant__ CUtensorMap mW2,
             const __grid_constant__ CUtensorMap mX, const __nv_bfloat16* __restrict__ wphi,
             const __nv_bfloat16* __restrict__ b1, const __nv_bfloat16* __restrict__ b2,
             const __nv_bfloat16* __restrict__ wqkv, const __nv_bfloat16* __restrict__ wo, const __nv_bfloat16* __restrict__ w1,
             const __nv_bfloat16* __restrict__ w2, __nv_bfloat16* __restrict__ out) {
  extern __shared__ unsigned char smem_raw[];
  const uint32_t sb = (smem_u32(smem_raw) + 1023) & ~1023u;
  unsigned char* sg = smem_raw + (sb - smem_u32(smem_raw));
  const int tid = threadIdx.x, lane = tid & 31;
  const int G = blockIdx.x >> 3, r = blockIdx.x & 7;
  const uint32_t barFull = sb + OFF_BAR, barEmpty = barFull + 56, barA = barEmpty + 56, barCS = barA + 112, barX = barCS + 16;
  const int warp = __shfl_sync(~0u, tid >> 5, 0);
  uint32_t wv[7], bv;
#pragma unroll
  for (int i = 0; i < 7; i++)
    wv[i] = __ldg(reinterpret_cast<const unsigned short*>(wphi) + (56 * r + i * 8 + (warp & 7)) * 28 + min(lane, 27));
  bv = __ldg(reinterpret_cast<const unsigned short*>(b1) + 224 * r + min(tid, 223));
  if (lane == 0) {
    if (warp >= 10) {
      const int cc = warp - 10;
      mbar_init(barX + cc * 8, 1);
      fence_async_smem();
      mbar_expect(barX + cc * 8, ABYTES);
#pragma unroll 1
      for (int k = 0; k < 7; k++) tma2(sb + cc * ABYTES + k * 8192, &mX, 64 * k, G * 128 + 64 * cc, barX + cc * 8);
    } else if (warp < 7) { mbar_init(barFull + warp * 8, 1); mbar_init(barEmpty + warp * 8, 2); mbar_init(barA + warp * 8, 1); mbar_init(barA + 56 + warp * 8, 1); }
    else if (warp < 9) mbar_init(barCS + (warp - 7) * 8, 96);
    else
      asm volatile("cp.async.bulk.prefetch.L2.global [%0], %1;" ::"l"((const char*)wqkv + blockIdx.x * 9408), "r"(9408) : "memory");
    asm volatile("fence.mbarrier_init.release.cluster;" ::: "memory");
  }
  if (tid < 192) reinterpret_cast<float*>(sg + OFF_CS)[tid] = 0.f;
  __syncthreads();
  const int wgid = warp >> 2;
  if (wgid == 2) {
    asm volatile("setmaxnreg.dec.sync.aligned.u32 40;");
    if (warp == 8) {
      int slot = 0, par = 1;
#pragma unroll 1
      for (int it = 0; it < 2 * TILES_PER_LAYER; it++) {
        const int i = it >= TILES_PER_LAYER ? it - TILES_PER_LAYER : it;
        mbar_wait(barEmpty + slot * 8, par);
        const uint32_t dst = sb + OFF_RING + slot * SLOT, fb = barFull + slot * 8;
        if (elect_one()) {
          mbar_expect(fb, i < 14 ? 12288 : SLOT);
          if (i < 14) tma3(dst, &mQKV, 56 * r, 32 * i, 0, fb);
          else if (i < 18) tma2(dst, &mWO, 56 * r, 112 * (i - 14), fb);
          else if (i < 32) tma3(dst, &mW1, 0, 32 * (i - 18), 7 * r, fb);
          else tma2(dst, &mW2, 64 * ((i - 32) >> 1), 224 * r + 112 * (i & 1), fb);
        }
        if (++slot == NSLOT) { slot = 0; par ^= 1; }
      }
    } else {
      unsigned ep;
      asm volatile("ld.relaxed.gpu.global.u32 %0, [%1];" : "=r"(ep) : "l"(gFlag + FL_DONE * 32) : "memory");
      const int idx = tid - 288;
      ep = (ep / NCTA + 1) * 3;
      if (G == 0) {
#pragma unroll 1
        for (int i = idx; i < 2 * 1280; i += 96) gKV[((i >= 1280) * 7 + r) * 1280 + i] = make_float4(0.f, 0.f, 0.f, 0.f);
        __syncwarp();
        if (lane == 0) flag_arrive(gFlag + (FL_CS + r) * 32);
      }
      mbar_wait(barFull + 48, 0); mbar_wait(barFull + 48, 1);
      if (idx < 2) {
        const char* pf = idx ? (const char*)w2 + blockIdx.x * 12544 : (const char*)wo + blockIdx.x * 3136;
        asm volatile("cp.async.bulk.prefetch.L2.global [%0], %1;" ::"l"(pf), "r"(idx ? 12544 : 3136) : "memory");
      }
      if (lane == 0) flag_wait(gFlag + (FL_CS + r) * 32, ep);
      __syncwarp();
      mbar_arrive(barCS);
#pragma unroll 1
      for (int ps = 0; ps < 3; ps++) {
        const int nch = ps ? 14 : 21, ch = min(idx >> 2, nch - 1), p = ch / 7, k0 = G * 28 + (idx & 3) * 7;
        const uint4* src = ps ? reinterpret_cast<const uint4*>(w1 + (size_t)k0 * 1792 + 224 * r) + (ps - 1) * 14 + ch
                              : reinterpret_cast<const uint4*>(wqkv + (size_t)k0 * 1344 + p * 448 + 56 * r) + (ch - 7 * p);
        uint4 cu[7];
#pragma unroll
        for (int i = 0; i < 7; i++) cu[i] = __ldg(src + i * (ps ? 224 : 168));
        float s[8] = {};
#pragma unroll
        for (int i = 0; i < 7; i++) { s[0] += lo(cu[i].x); s[1] += hi(cu[i].x); s[2] += lo(cu[i].y); s[3] += hi(cu[i].y); s[4] += lo(cu[i].z); s[5] += hi(cu[i].z); s[6] += lo(cu[i].w); s[7] += hi(cu[i].w); }
#pragma unroll
        for (int i = 0; i < 8; i++) { s[i] += __shfl_xor_sync(~0u, s[i], 1); s[i] += __shfl_xor_sync(~0u, s[i], 2); }
        if ((idx & 3) < 2 && idx < nch * 4) gCS[(r * 16 + G) * 104 + (ps ? 10 + ps * 14 + ch : ch + p) * 2 + (idx & 1)] = (idx & 1) ? make_float4(s[4], s[5], s[6], s[7]) : make_float4(s[0], s[1], s[2], s[3]);
      }
      __syncwarp();
      if (lane == 0) { flag_arrive(gFlag + (FL_CS + 8 + r) * 32); flag_wait(gFlag + (FL_CS + 8 + r) * 32, ep * 16); }
      __syncwarp();
#pragma unroll 1
      for (int j = idx; j < 208; j += 96) {
        float2 a = make_float2(0.f, 0.f);
#pragma unroll 8
        for (int i = 0; i < 16; i++) { const float2 v = __ldcg(reinterpret_cast<const float2*>(gCS + (r * 16 + i) * 104) + j); a.x += v.x; a.y += v.y; }
        reinterpret_cast<float2*>(sg + OFF_CS)[j] = a;
      }
      mbar_arrive(barCS + 8);
    }
  } else {
  asm volatile("setmaxnreg.inc.sync.aligned.u32 232;");
  const int c = wgid, w = warp & 3, g = lane >> 2, t = lane & 3;
  int elect_i = (tid & 127) == 0;
  asm volatile("" : "+r"(elect_i));
  const bool elect = elect_i;
  const uint32_t abuf = sb + c * ABYTES, barAc = barA + c * 56;
  const int row0 = G * 128 + c * 64;
  unsigned epoch;
  asm volatile("ld.relaxed.gpu.global.u32 %0, [%1];" : "=r"(epoch) : "l"(gFlag + FL_DONE * 32) : "memory");
  STAMP(24);
  float mean[2], rstd[2] = {0.f, 0.f};
  uint4 su[2] = {};
  uint32_t xs[7][2];
  {
#pragma unroll
    for (int i = 0; i < 8; i++) {
      const int k = i * 8 + (tid >> 5);
      *reinterpret_cast<uint32_t*>(sg + OFF_WPHI + k * 128 + ((g ^ (k & 7)) << 4) + t * 4) = (i < 7 && lane < 28) ? wv[i % 7] << (k >= 28 ? 16 : 0) : 0u;
    }
    if (tid < 224) reinterpret_cast<uint32_t*>(sg + OFF_B1)[tid] = bv << 16;
    mbar_wait(barX + c * 8, 0);
    STAMP(25);
#pragma unroll
    for (int j = 0; j < 7; j++) {
      const int ci = 7 * r + j;
      const uint32_t a = abuf + (ci >> 3) * 8192 + (w * 16 + g) * 128 + (((ci & 7) ^ g) << 4) + t * 4;
      xs[j][0] = lds32(a); xs[j][1] = lds32(a + 1024);
    }
    __syncwarp();
#pragma unroll 1
    for (int hh = 0; hh < 2; hh++) {
      uint4* p = reinterpret_cast<uint4*>(sg + c * ABYTES + (w * 16 + hh * 8 + g) * 128) + t;
      uint4 v[14];
#pragma unroll
      for (int k = 0; k < 14; k++) v[k] = p[(k >> 1) * 512 + ((k ^ g) & 1) * 4];
      float a8[8] = {};
#pragma unroll
      for (int k = 0; k < 14; k++) {
        const uint32_t e[4] = {v[k].x, v[k].y, v[k].z, v[k].w};
#pragma unroll
        for (int z = 0; z < 4; z++) { a8[2 * z] += lo(e[z]); a8[2 * z + 1] += hi(e[z]); }
      }
      float sm = ((a8[0] + a8[1]) + (a8[2] + a8[3])) + ((a8[4] + a8[5]) + (a8[6] + a8[7]));
      sm += __shfl_xor_sync(~0u, sm, 1); sm += __shfl_xor_sync(~0u, sm, 2);
      sm *= 1.f / DM;
#pragma unroll
      for (int k = 0; k < 14; k++) {
        uint32_t e[4] = {v[k].x, v[k].y, v[k].z, v[k].w};
#pragma unroll
        for (int z = 0; z < 4; z++) {
          const float a = lo(e[z]) - sm, b = hi(e[z]) - sm;
          a8[2 * z] = fmaf(a, a, k ? a8[2 * z] : 0.f); a8[2 * z + 1] = fmaf(b, b, k ? a8[2 * z + 1] : 0.f);
          e[z] = pack(a, b);
        }
        p[(k >> 1) * 512 + ((k ^ g) & 1) * 4] = make_uint4(e[0], e[1], e[2], e[3]);
      }
      float q = ((a8[0] + a8[1]) + (a8[2] + a8[3])) + ((a8[4] + a8[5]) + (a8[6] + a8[7]));
      q += __shfl_xor_sync(~0u, q, 1); q += __shfl_xor_sync(~0u, q, 2);
      rstd[1] = rsqrtf(q * (1.f / DM) + 1e-5f);
      if (hh == 0) rstd[0] = rstd[1];
    }
    fence_async_smem();
    bar_sync<3, 256>();
    epoch = epoch / NCTA + 1;
    mean[0] = mean[1] = 0.f;
  }
  STAMP(0);
  Ring ring{barFull, barEmpty, sb + OFF_RING, 0, 0};
  int apar = 1;
  const uint32_t stsm_off = (w * 16 + ((lane >> 3) & 1) * 8 + (lane & 7)) * 128;
  const uint32_t stsm_hi = lane >> 4;
  const uint64_t dA = mkdesc(abuf, 1024, 128, 0);

  auto gather = [&](unsigned* fl, const unsigned char* img) {
    bar_wg(c);
    if (w == 0) {
      if (elect_one()) {
        flag_arrive(fl);
        flag_wait(fl, epoch * 8);
        fence_async();
#pragma unroll
        for (int k = 0; k < 7; k++) { mbar_expect(barAc + k * 8, 8192); bulk_ld(abuf + k * 8192, img + k * 8192, 8192, barAc + k * 8); }
      }
      __syncwarp();
    }
    apar ^= 1;
  };
  auto slice_off = [&](int j, int hh) -> uint32_t {
    return (7 * r + j) * 1024 + (w * 2 + hh) * 128 + lane * 4;
  };
  auto load_stats = [&](const float2* st) {
    mbar_wait(barAc, apar);
#pragma unroll
    for (int hh = 0; hh < 2; hh++) su[hh] = ldcg4(st + (size_t)(row0 + w * 16 + hh * 8 + g) * 8 + 2 * t);
  };
  auto finish_stats = [&]() {
#pragma unroll
    for (int hh = 0; hh < 2; hh++) {
      const float m0 = __uint_as_float(su[hh].x), m1 = __uint_as_float(su[hh].z);
      float m = m0 + m1;
      m += __shfl_xor_sync(~0u, m, 1); m += __shfl_xor_sync(~0u, m, 2);
      m *= 0.125f;
      float q = __uint_as_float(su[hh].y) + __uint_as_float(su[hh].w) + 56.f * ((m0 - m) * (m0 - m) + (m1 - m) * (m1 - m));
      q += __shfl_xor_sync(~0u, q, 1); q += __shfl_xor_sync(~0u, q, 2);
      mean[hh] = m; rstd[hh] = rsqrtf(q * (1.f / DM) + 1e-5f);
    }
  };

#pragma unroll 1
  for (int lyr = 0; lyr < 2; lyr++) {
    const int layer = __shfl_sync(~0u, lyr, 0);
    unsigned* const fl = gFlag + (layer * 32 + G * 2 + c) * 7 * 32;
    uint32_t phiq[4][7];
    {
      float acc[92]; reg_def(acc);
      int prev = 0, prev2 = 0;
      ring.uniform();
      const uint64_t dQ = layer ? dA : mkdesc(abuf, 16, 1024, 1);
      const int kstep = layer ? 128 : 2;
      if (layer) load_stats(gStat + 2048 * 8);
#pragma unroll UNR
      for (int st = 0; st < 14; st++) {
        if (!(st & 1) && layer) mbar_wait(barAc + (st >> 1) * 8, apar);
        const uint64_t da = dQ + (st >> 1) * 512 + (st & 1) * 2 * kstep, db = mkdesc(ring.acquire(), 4096, 1024, 1);
        wg_fence();
        mma_ss_184(acc, da, db, 1);
        mma_ss_184(acc, da + kstep, db + 128, 1);
        wg_commit();
        if (st > 1) { wg_wait<2>(); ring.release(prev2, elect); }
        prev2 = prev; prev = ring.advance();
      }
      if (layer) {
        finish_stats();
#pragma unroll
        for (int j = 0; j < 7; j++) { xs[j][0] = lds32(abuf + slice_off(j, 0)); xs[j][1] = lds32(abuf + slice_off(j, 1)); }
      }
      wg_wait<0>(); reg_fence(acc);
      ring.release(prev2, elect); ring.release(prev, elect);
      STAMP(1 + layer * 12);
      uint32_t f[3][14];
      {
        const float2* cs = reinterpret_cast<const float2*>(sg + OFF_CS) + t;
        const float mr0 = -mean[0] * rstd[0], mr1 = -mean[1] * rstd[1];
#pragma unroll
        for (int p = 0; p < 3; p++)
#pragma unroll
          for (int j = 0; j < 7; j++) {
            const float2 s = cs[p * 32 + j * 4];
            const int b = p * 32 + j * 4;
            f[p][2 * j] = pack(fmaf(acc[b], rstd[0], s.x * mr0), fmaf(acc[b + 1], rstd[0], s.y * mr0));
            f[p][2 * j + 1] = pack(fmaf(acc[b + 2], rstd[1], s.x * mr1), fmaf(acc[b + 3], rstd[1], s.y * mr1));
          }
      }
      float pk[28], pq[28]; reg_def(pk); reg_def(pq);
      const uint64_t dW = mkdesc(sb + OFF_WPHI, 4096, 1024, 1);
      wg_fence();
#pragma unroll
      for (int s = 0; s < 4; s++) {
        mma_rs_56(pk, f[1][4 * s], f[1][4 * s + 1], s < 3 ? f[1][(4 * s + 2) % 14] : 0u, s < 3 ? f[1][(4 * s + 3) % 14] : 0u, dW + s * 128, s);
        mma_rs_56(pq, f[0][4 * s], f[0][4 * s + 1], s < 3 ? f[0][(4 * s + 2) % 14] : 0u, s < 3 ? f[0][(4 * s + 3) % 14] : 0u, dW + s * 128, s);
      }
      wg_commit();
      bar_wg(c);
      const uint32_t srow = abuf + stsm_off, ones = t == 0 ? 0x3F803F80u : 0u;
#pragma unroll
      for (int jp = 0; jp < 4; jp++)
        stsm4(srow + 16384 + (((2 * jp + stsm_hi) ^ (lane & 7)) << 4), f[2][4 * jp], f[2][4 * jp + 1],
              jp < 3 ? f[2][(4 * jp + 2) % 14] : ones, jp < 3 ? f[2][(4 * jp + 3) % 14] : ones);
      wg_wait<0>(); reg_fence(pk); reg_fence(pq);
#pragma unroll 1
      for (int pass = 0; pass < 2; pass++) {
        dual_softmax(pk, phiq);
        if (pass) break;
#pragma unroll
        for (int e = 0; e < 2; e++)
#pragma unroll
          for (int jp = 0; jp < 4; jp++)
            stsm4(srow + e * 8192 + (((2 * jp + stsm_hi) ^ (lane & 7)) << 4), phiq[e][2 * jp], phiq[2 + e][2 * jp],
                  jp < 3 ? phiq[e][(2 * jp + 1) % 7] : 0u, jp < 3 ? phiq[2 + e][(2 * jp + 1) % 7] : 0u);
        fence_async_smem();
        bar_sync<3, 256>();
        float kv[32], kw[32]; reg_def(kv); reg_def(kw);
        const uint64_t dP = mkdesc(sb + c * 8192, 4096, 1024, 1), dV = mkdesc(sb + 16384, 4096, 1024, 1);
        wg_fence();
#pragma unroll
        for (int s = 0; s < 4; s++) { mma_ss_64t(kv, dP + s * 128, dV + s * 128, s); mma_ss_64t(kw, dP + ABYTES / 16 + s * 128, dV + ABYTES / 16 + s * 128, s); }
        wg_commit();
        mbar_wait(barCS, 0);
        wg_wait<0>(); reg_fence(kv); reg_fence(kw);
#pragma unroll
        for (int i = 0; i < 32; i++) kv[i] += kw[i];
        float4* kvg = gKV + ((layer * 8 + r) * 2 + c) * 640 + (tid & 127);
#pragma unroll
        for (int i = 0; i < 5; i++) {
          float v0, v1, v2, v3;
          if (i == 4) { v0 = kv[28]; v1 = kv[29]; v2 = kv[30]; v3 = kv[31]; }
          else { v0 = c ? kv[12 + 4 * i] : kv[4 * i]; v1 = c ? kv[13 + 4 * i] : kv[1 + 4 * i]; v2 = c ? kv[14 + 4 * i] : kv[2 + 4 * i]; v3 = c ? kv[15 + 4 * i] : kv[3 + 4 * i]; }
          const bool use = i == 4 ? t == 0 : (i == 0 ? (c == 0 || t >= 2) : (i == 3 ? (c == 1 || t < 2) : true));
          if (use) asm volatile("red.relaxed.gpu.global.add.v4.f32 [%0], {%1,%2,%3,%4};" ::"l"(kvg + i * 128), "f"(v0), "f"(v1), "f"(v2), "f"(v3) : "memory");
        }
        bar_wg(c);
        if (elect) flag_arrive(gFlag + (FL_KV + layer * 8 + r) * 32);
        __syncwarp();
        STAMP(2 + layer * 12);
#pragma unroll
        for (int i = 0; i < 28; i++) pk[i] = pq[i];
      }
    }
    {
      if (elect) flag_wait(gFlag + (FL_KV + layer * 8 + r) * 32, epoch * 32);
      bar_wg(c);
      STAMP(3 + layer * 12);
      const float4* kvg = gKV + (layer * 8 + r) * 1280 + c * 640 + (tid & 127);
      uint4 kk[5];
#pragma unroll
      for (int i = 0; i < 5; i++) kk[i] = ldcg4(kvg + i * 128);
      uint32_t f[5][2];
#pragma unroll
      for (int i = 0; i < 5; i++) { f[i][0] = pack(__uint_as_float(kk[i].x), __uint_as_float(kk[i].y)); f[i][1] = pack(__uint_as_float(kk[i].z), __uint_as_float(kk[i].w)); }
      const uint32_t zm = c ? 0xFFFF0000u : 0xFFFFu;
      const uint32_t srow = abuf + 24576 + stsm_off;
#pragma unroll
      for (int jp = 0; jp < 4; jp++) {
        uint32_t v[2][2];
#pragma unroll
        for (int u = 0; u < 2; u++) {
          const int j = 2 * jp + u;
#pragma unroll
          for (int hh = 0; hh < 2; hh++) v[u][hh] = j == 7 ? f[4][hh] & zm : (c ? (j >= 3 ? f[(j + 2) % 5][hh] : 0u) : (j < 4 ? f[j % 5][hh] : 0u));
        }
        stsm4(srow + (((2 * jp + stsm_hi) ^ (lane & 7)) << 4), v[0][0], v[0][1], v[1][0], v[1][1]);
      }
      fence_async_smem();
      bar_sync<3, 256>();
      float num[32], nub[32]; reg_def(num); reg_def(nub);
      const uint64_t dK = mkdesc(sb + 24576, 4096, 1024, 1);
      wg_fence();
#pragma unroll
      for (int s = 0; s < 4; s++) {
        mma_rs_64(num, phiq[0][2 * s], phiq[2][2 * s], s < 3 ? phiq[0][(2 * s + 1) % 7] : 0u, s < 3 ? phiq[2][(2 * s + 1) % 7] : 0u, dK + s * 128, s);
        mma_rs_64(nub, phiq[1][2 * s], phiq[3][2 * s], s < 3 ? phiq[1][(2 * s + 1) % 7] : 0u, s < 3 ? phiq[3][(2 * s + 1) % 7] : 0u, dK + ABYTES / 16 + s * 128, s);
      }
      wg_commit();
      wg_wait<0>(); reg_fence(num); reg_fence(nub);
      bar_sync<3, 256>();
#pragma unroll
      for (int i = 12; i < 32; i++) num[i] += nub[i];
      float rd[4];
#pragma unroll
      for (int i = 0; i < 4; i++) rd[i] = __fdividef(1.f, __shfl_sync(~0u, num[28 + i], lane & ~3) + 1e-6f);
      unsigned char* img = gImg + (size_t)(G * 2 + c) * ABYTES;
#pragma unroll
      for (int j = 0; j < 7; j++) {
        const bool hb = j > 3 || (j == 3 && t >= 2);
        const float r0 = hb ? rd[1] : rd[0], r1 = hb ? rd[3] : rd[2];
        *reinterpret_cast<uint32_t*>(img + slice_off(j, 0)) = pack(num[4 * j] * r0, num[4 * j + 1] * r0);
        *reinterpret_cast<uint32_t*>(img + slice_off(j, 1)) = pack(num[4 * j + 2] * r1, num[4 * j + 3] * r1);
      }
      STAMP(4 + layer * 12);
      gather(fl, img);
      STAMP(5 + layer * 12);
    }
    {
      float acc[28], acc2[28]; reg_def(acc); reg_def(acc2); reg_fence(acc); reg_fence(acc2);
      int sl[4];
      ring.uniform();
#pragma unroll
      for (int st = 0; st < 4; st++) {
        const uint64_t db = mkdesc(ring.acquire(), 4096, 1024, 1);
        sl[st] = ring.advance();
#pragma unroll
        for (int s = 0; s < 7; s++) {
          const int ks = st * 7 + s;
          if (!(ks & 3)) mbar_wait(barAc + (ks >> 2) * 8, apar);
          if (!(ks & 3) || !s) wg_fence();
          if (ks & 1) mma_ss_56(acc2, dA + ks * 128, db + s * 128, ks > 1); else mma_ss_56(acc, dA + ks * 128, db + s * 128, ks > 1);
        }
        wg_commit();
      }
      wg_wait<0>(); reg_fence(acc); reg_fence(acc2);
      unsigned char* img = gImg + (size_t)(32 + G * 2 + c) * ABYTES;
#pragma unroll
      for (int hh = 0; hh < 2; hh++) {
        float s = 0.f, q = 0.f;
#pragma unroll
        for (int j = 0; j < 7; j++) {
          xs[j][hh] = pack(lo(xs[j][hh]) + (acc[4 * j + 2 * hh] + acc2[4 * j + 2 * hh]), hi(xs[j][hh]) + (acc[4 * j + 2 * hh + 1] + acc2[4 * j + 2 * hh + 1]));
          *reinterpret_cast<uint32_t*>(img + slice_off(j, hh)) = xs[j][hh];
          s += lo(xs[j][hh]) + hi(xs[j][hh]);
        }
        s += __shfl_xor_sync(~0u, s, 1); s += __shfl_xor_sync(~0u, s, 2);
        s *= 1.f / 56.f;
#pragma unroll
        for (int j = 0; j < 7; j++) { const float a = lo(xs[j][hh]) - s, b = hi(xs[j][hh]) - s; q = fmaf(a, a, q); q = fmaf(b, b, q); }
        q += __shfl_xor_sync(~0u, q, 1); q += __shfl_xor_sync(~0u, q, 2);
        if (t == 0) gStat[(size_t)(row0 + w * 16 + hh * 8 + g) * 8 + r] = make_float2(s, q);
      }
#pragma unroll
      for (int j = 0; j < 7; j++) xs[j][0] = xs[j][1] = 0u;
      STAMP(6 + layer * 12);
      gather(fl + 32, img);
#pragma unroll
      for (int st = 0; st < 4; st++) ring.release(sl[st], elect);
      STAMP(7 + layer * 12);
    }
    {
      uint32_t hf[28][2];
      {
        float acc[112]; reg_def(acc);
        int prev = 0, prev2 = 0;
        load_stats(gStat);
        ring.uniform();
#pragma unroll UNR
        for (int st = 0; st < 14; st++) {
          if (!(st & 1)) mbar_wait(barAc + (st >> 1) * 8, apar);
          const uint64_t da = dA + st * 256, db = mkdesc(ring.acquire(), 2048, 512, 2);
          wg_fence();
          mma_ss_224(acc, da, db, 1);
          mma_ss_224(acc, da + 128, db + 64, 1);
          wg_commit();
          if (st > 1) { wg_wait<2>(); ring.release(prev2, elect); }
          prev2 = prev; prev = ring.advance();
        }
        finish_stats();
        mbar_wait(barCS + 8, 0);
        wg_wait<0>(); reg_fence(acc);
        ring.release(prev2, elect); ring.release(prev, elect);
        STAMP(8 + layer * 12);
        const float2* bs = reinterpret_cast<const float2*>(sg + OFF_B1) + t;
        const float2* cs = reinterpret_cast<const float2*>(sg + OFF_CS + 768) + t;
        const float mr0 = -mean[0] * rstd[0], mr1 = -mean[1] * rstd[1];
#pragma unroll
        for (int j = 0; j < 28; j++) {
          const float2 b = bs[4 * j], s = cs[4 * j];
          hf[j][0] = relu_sq(fmaf(acc[4 * j], rstd[0], fmaf(s.x, mr0, b.x)), fmaf(acc[4 * j + 1], rstd[0], fmaf(s.y, mr0, b.y)));
          hf[j][1] = relu_sq(fmaf(acc[4 * j + 2], rstd[1], fmaf(s.x, mr1, b.x)), fmaf(acc[4 * j + 3], rstd[1], fmaf(s.y, mr1, b.y)));
        }
      }
      unsigned char* pd[2]; int pstr[2];
#pragma unroll
      for (int hh = 0; hh < 2; hh++) {
        const bool own = 2 * w + hh == r;
        pd[hh] = own ? sg + c * ABYTES + (lane >> 4) * 1024 + (r ^ 1) * 128 + (lane & 15) * 8
                     : gP + (size_t)(((G * 2 + c) * 8 + 2 * w + hh) * 8 + r) * 7168 + lane * 8;
        pstr[hh] = own ? 2048 : 256;
      }
      uint2 pk[8] = {};
      ring.uniform();
#pragma unroll 1
      for (int ch = 0; ch < 7; ch++) {
        float acc[32], acc2[32]; reg_def(acc); reg_def(acc2);
        const uint64_t db0 = mkdesc(ring.acquire(), 4096, 1024, 1);
        const int sl0 = ring.advance();
        const uint64_t db1 = mkdesc(ring.acquire(), 4096, 1024, 1);
        const int sl1 = ring.advance();
        wg_fence();
#pragma unroll
        for (int s = 0; s < 7; s++) {
          mma_rs_64(acc, hf[2 * s][0], hf[2 * s][1], hf[2 * s + 1][0], hf[2 * s + 1][1], db0 + s * 128, s);
          mma_rs_64(acc2, hf[14 + 2 * s][0], hf[14 + 2 * s][1], hf[15 + 2 * s][0], hf[15 + 2 * s][1], db1 + s * 128, s);
        }
        wg_commit();
        if (ch > 0) {
#pragma unroll
          for (int i = 0; i < 8; i++) { *reinterpret_cast<uint2*>(pd[i & 1]) = pk[i]; pd[i & 1] += pstr[i & 1]; }
        }
        wg_wait<0>(); reg_fence(acc); reg_fence(acc2); ring.release(sl0, elect); ring.release(sl1, elect);
#pragma unroll
        for (int i = 0; i < 8; i++) {
          const int b = (i >> 1) * 8 + (i & 1) * 2;
          pk[i] = make_uint2((pack(acc[b] + acc2[b], acc[b + 1] + acc2[b + 1]) & ~1u) | (layer ^ 1), pack(acc[b + 4] + acc2[b + 4], acc[b + 5] + acc2[b + 5]));
        }
      }
#pragma unroll
      for (int i = 0; i < 8; i++) { *reinterpret_cast<uint2*>(pd[i & 1]) = pk[i]; pd[i & 1] += pstr[i & 1]; }
      STAMP(9 + layer * 12);
    }
    {
      uint32_t bx[14];
#pragma unroll
      for (int j = 0; j < 14; j++) bx[j] = __ldg(reinterpret_cast<const uint32_t*>(b2 + (j >> 1) * 64 + w * 16 + (j & 1) * 8 + 2 * t));
      const unsigned char* psrc = gP + (size_t)(((G * 2 + c) * 8 + r) * 8) * 7168 + w * 256 + lane * 8;
      unsigned char* img = gImg + (size_t)(64 + G * 2 + c) * ABYTES;
      uint2 pv[7][7];
      const unsigned char* ps[7];
#pragma unroll
      for (int s = 0; s < 7; s++) ps[s] = psrc + ((r + 1 + s) & 7) * 7168;
#pragma unroll
      for (int i = 0; i < 5; i++)
#pragma unroll
        for (int s = 0; s < 7; s++) pv[s][i] = ldcg2(ps[s] + i * 1024);
      bar_wg(c);
      const uint32_t off = w * 2048 + r * 128 + lane * 4;
      unsigned char* dst = layer ? reinterpret_cast<unsigned char*>(out + (size_t)(row0 + r * 8 + g) * DM + w * 16 + 4 * t) : img + off;
      float sm = 0.f, q = 0.f;
#pragma unroll
      for (int i = 0; i < 7; i++) {
        const uint2 own = *reinterpret_cast<const uint2*>(sg + c * ABYTES + i * 8192 + w * 2048 + (lane >> 4) * 1024 + (r ^ 1) * 128 + (lane & 15) * 8);
#pragma unroll 1
        for (int n = 0; n < (1 << 16); n++) {
          const uint32_t all = pv[0][i].x & pv[1][i].x & pv[2][i].x & pv[3][i].x & pv[4][i].x & pv[5][i].x & pv[6][i].x;
          const uint32_t any = pv[0][i].x | pv[1][i].x | pv[2][i].x | pv[3][i].x | pv[4][i].x | pv[5][i].x | pv[6][i].x;
          if (!__any_sync(~0u, (layer ? any : ~all) & 1u)) break;
#pragma unroll
          for (int s = 0; s < 7; s++) pv[s][i] = ldcg2(ps[s] + i * 1024);
        }
        if (i < 2) {
#pragma unroll
          for (int s = 0; s < 7; s++) pv[s][5 + (i & 1)] = ldcg2(ps[s] + (5 + i) * 1024);
        }
#pragma unroll
        for (int jj = 0; jj < 2; jj++) {
          const int j = 2 * i + jj;
          const uint32_t xo = lds32(abuf + off + i * 8192 + jj * 1024), uo = jj ? own.y : own.x;
          float y0 = lo(bx[j]) + lo(xo) + lo(uo), y1 = hi(bx[j]) + hi(xo) + hi(uo);
#pragma unroll
          for (int s = 0; s < 7; s++) { const uint32_t u = jj ? pv[s][i].y : pv[s][i].x; y0 += lo(u); y1 += hi(u); }
          bx[j] = pack(y0, y1);
          if (!layer) *reinterpret_cast<uint32_t*>(dst + (i * 8 + jj) * 1024) = bx[j];
          sm += lo(bx[j]) + hi(bx[j]);
        }
        if (layer) {
          const int sl = (lane & ~3) | ((t & 1) << 1);
          const uint32_t a0 = __shfl_sync(~0u, bx[2 * i], sl), a1 = __shfl_sync(~0u, bx[2 * i], sl + 1);
          const uint32_t b0 = __shfl_sync(~0u, bx[2 * i + 1], sl), b1v = __shfl_sync(~0u, bx[2 * i + 1], sl + 1);
          *reinterpret_cast<uint2*>(dst + i * 128) = t < 2 ? make_uint2(a0, a1) : make_uint2(b0, b1v);
        }
      }
      if (layer) break;
      sm += __shfl_xor_sync(~0u, sm, 1); sm += __shfl_xor_sync(~0u, sm, 2);
      sm *= 1.f / 112.f;
#pragma unroll
      for (int j = 0; j < 14; j++) { const float a = lo(bx[j]) - sm, b = hi(bx[j]) - sm; q = fmaf(a, a, q); q = fmaf(b, b, q); }
      q += __shfl_xor_sync(~0u, q, 1); q += __shfl_xor_sync(~0u, q, 2);
      if (t < 2) gStat[(size_t)(2048 + row0 + r * 8 + g) * 8 + 2 * w + t] = make_float2(sm, q * 0.5f);
      STAMP(11);
      gather(fl + 64, img);
      STAMP(12);
    }
  }
  STAMP(30);
  if (tid == 0) asm volatile("red.relaxed.gpu.global.add.u32 [%0], 1;" ::"l"(gFlag + FL_DONE * 32) : "memory");
  }
}

typedef CUresult (*EncFn)(CUtensorMap*, CUtensorMapDataType, cuuint32_t, void*, const cuuint64_t*, const cuuint64_t*,
                          const cuuint32_t*, const cuuint32_t*, CUtensorMapInterleave, CUtensorMapSwizzle,
                          CUtensorMapL2promotion, CUtensorMapFloatOOBfill);

void make_map(EncFn enc, CUtensorMap* m, void* p, int rank, uint64_t d0, uint64_t d1, uint64_t d2, uint64_t s1, uint64_t s2,
              uint32_t b0, uint32_t b1, uint32_t b2, CUtensorMapSwizzle sw) {
  cuuint64_t dims[3] = {d0, d1, d2}, strides[2] = {s1, s2};
  cuuint32_t box[3] = {b0, b1, b2}, es[3] = {1, 1, 1};
  enc(m, CU_TENSOR_MAP_DATA_TYPE_BFLOAT16, rank, p, dims, strides, box, es, CU_TENSOR_MAP_INTERLEAVE_NONE, sw,
      CU_TENSOR_MAP_L2_PROMOTION_L2_128B, CU_TENSOR_MAP_FLOAT_OOB_FILL_NONE);
}

}

extern "C" void kernel_launch(void* const* d_in, const int* in_sizes, int n_in, void* d_out, int out_size) {
  static EncFn enc = nullptr;
  if (!enc) {
    cudaDriverEntryPointQueryResult st;
    void* fn = nullptr;
    cudaGetDriverEntryPoint("cuTensorMapEncodeTiled", &fn, cudaEnableDefault, &st);
    enc = (EncFn)fn;
    cudaFuncSetAttribute(fused_kernel, cudaFuncAttributeMaxDynamicSharedMemorySize, SMEM_BYTES);
  }
  CUtensorMap mQKV, mWO, mW1, mW2, mX;
  make_map(enc, &mX, d_in[0], 2, 448, 2048, 1, 896, 0, 64, 64, 1, CU_TENSOR_MAP_SWIZZLE_128B);
  make_map(enc, &mQKV, d_in[1], 3, 448, 448, 3, 2688, 896, 64, 32, 3, CU_TENSOR_MAP_SWIZZLE_128B);
  make_map(enc, &mWO, d_in[3], 2, 448, 448, 1, 896, 0, 64, 112, 1, CU_TENSOR_MAP_SWIZZLE_128B);
  make_map(enc, &mW1, d_in[5], 3, 32, 448, 56, 3584, 64, 32, 32, 7, CU_TENSOR_MAP_SWIZZLE_64B);
  make_map(enc, &mW2, d_in[7], 2, 448, 1792, 1, 896, 0, 64, 112, 1, CU_TENSOR_MAP_SWIZZLE_128B);
  fused_kernel<<<NCTA, 384, SMEM_BYTES, cudaStreamPerThread>>>(
      mQKV, mWO, mW1, mW2, mX, (const __nv_bfloat16*)d_in[2], (const __nv_bfloat16*)d_in[6],
      (const __nv_bfloat16*)d_in[8], (const __nv_bfloat16*)d_in[1], (const __nv_bfloat16*)d_in[3], (const __nv_bfloat16*)d_in[5],
      (const __nv_bfloat16*)d_in[7], (__nv_bfloat16*)d_out);
}
```

```cpp
#include <cuda_runtime.h>
#include <cuda_bf16.h>
#include <cuda.h>
#include <stdint.h>

namespace {

constexpr int DM = 448, NCTA = 128;
constexpr int ABYTES = 57344;
constexpr int SLOT = 14336, NSLOT = 7;
constexpr int OFF_RING = 2 * ABYTES;
constexpr int OFF_WPHI = OFF_RING + NSLOT * SLOT;
constexpr int OFF_B1 = OFF_WPHI + 8192;
constexpr int OFF_CS = OFF_B1 + 896;
constexpr int OFF_BAR = OFF_CS + 1664;
constexpr int SMEM_BYTES = OFF_BAR + 272 + 1024;
constexpr int TILES_PER_LAYER = 46;

__device__ __align__(1024) unsigned char gP[16 * 2 * 8 * 8 * 7168];
__device__ __align__(1024) unsigned char gImg[3 * 32 * ABYTES];
__device__ __align__(1024) float2 gStat[2 * 2048 * 8];
__device__ __align__(1024) float4 gKV[2 * 8 * 2 * 5 * 128];
__device__ __align__(1024) float4 gCS[8 * 16 * 104];
__device__ __align__(128) unsigned gFlag[(2 * 32 * 7 + 32 + 1 + 16) * 32];
#define STAMP(i)

__device__ __forceinline__ uint32_t smem_u32(const void* p) { return (uint32_t)__cvta_generic_to_shared(p); }
__device__ __forceinline__ void mbar_init(uint32_t b, int c) { asm volatile("mbarrier.init.shared::cta.b64 [%0], %1;" ::"r"(b), "r"(c)); }
__device__ __forceinline__ void mbar_expect(uint32_t b, int bytes) { asm volatile("mbarrier.arrive.expect_tx.shared::cta.b64 _, [%0], %1;" ::"r"(b), "r"(bytes) : "memory"); }
__device__ __forceinline__ void mbar_arrive(uint32_t b) { asm volatile("mbarrier.arrive.shared::cta.b64 _, [%0];" ::"r"(b) : "memory"); }
__device__ __forceinline__ void mbar_wait(uint32_t b, int par) {
  uint32_t ok; int n = 0;
#pragma unroll 1
  while (true) {
    asm volatile("{.reg .pred p; mbarrier.try_wait.parity.shared::cta.b64 p, [%1], %2; selp.u32 %0,1,0,p;}" : "=r"(ok) : "r"(b), "r"(par) : "memory");
    if (ok) break;
    if (++n > (1 << 22)) break;
  }
}
__device__ __forceinline__ void flag_wait(const unsigned* f, unsigned target) {
  unsigned v; int n = 0;
#pragma unroll 1
  while (true) {
    asm volatile("ld.acquire.gpu.global.u32 %0, [%1];" : "=r"(v) : "l"(f) : "memory");
    if ((int)(v - target) >= 0) break;
    if (++n > (1 << 21)) break;
  }
}
__device__ __forceinline__ void flag_arrive(unsigned* f) { asm volatile("red.release.gpu.global.add.u32 [%0], 1;" ::"l"(f) : "memory"); }
__device__ __forceinline__ bool elect_one() {
  uint32_t p; asm volatile("{.reg .pred P; elect.sync _|P, 0xffffffff; selp.u32 %0, 1, 0, P;}" : "=r"(p)); return p;
}
__device__ __forceinline__ void fence_async() { asm volatile("fence.proxy.async.global;" ::: "memory"); }
__device__ __forceinline__ void fence_async_smem() { asm volatile("fence.proxy.async.shared::cta;" ::: "memory"); }
template <int ID, int N> __device__ __forceinline__ void bar_sync() { asm volatile("bar.sync %0, %1;" ::"n"(ID), "n"(N) : "memory"); }
__device__ __forceinline__ void bar_wg(int c) { if (c) bar_sync<2, 128>(); else bar_sync<1, 128>(); }
__device__ __forceinline__ void wg_fence() { asm volatile("wgmma.fence.sync.aligned;" ::: "memory"); }
__device__ __forceinline__ void wg_commit() { asm volatile("wgmma.commit_group.sync.aligned;" ::: "memory"); }
template <int N> __device__ __forceinline__ void wg_wait() { asm volatile("wgmma.wait_group.sync.aligned %0;" ::"n"(N) : "memory"); }
template <int N> __device__ __forceinline__ void reg_fence(float (&d)[N]) {
#pragma unroll
  for (int i = 0; i < N; i++) asm volatile("" : "+f"(d[i])::"memory");
}
template <int N> __device__ __forceinline__ void reg_def(float (&d)[N]) {
#pragma unroll
  for (int i = 0; i < N; i++) d[i] = 0.f;
}
__device__ __forceinline__ uint64_t mkdesc(uint32_t addr, uint32_t lbo, uint32_t sbo, uint64_t swz) {
  return (uint64_t)((addr & 0x3FFFF) >> 4) | ((uint64_t)(lbo >> 4) << 16) | ((uint64_t)(sbo >> 4) << 32) | (swz << 62);
}
__device__ __forceinline__ uint32_t pack(float a, float b) {
  uint32_t r; asm("cvt.rn.bf16x2.f32 %0, %1, %2;" : "=r"(r) : "f"(b), "f"(a)); return r;
}
__device__ __forceinline__ uint32_t relu_sq(float a, float b) {
  uint32_t r; asm("{.reg .b32 v; cvt.rn.relu.bf16x2.f32 v, %1, %2; mul.rn.bf16x2 %0, v, v;}" : "=r"(r) : "f"(b), "f"(a)); return r;
}
__device__ __forceinline__ float lo(uint32_t u) { return __uint_as_float(u << 16); }
__device__ __forceinline__ float hi(uint32_t u) { return __uint_as_float(u & 0xFFFF0000u); }
__device__ __forceinline__ float ex2(float x) { float y; asm("ex2.approx.ftz.f32 %0, %1;" : "=f"(y) : "f"(x)); return y; }
__device__ __forceinline__ void stsm4(uint32_t a, uint32_t r0, uint32_t r1, uint32_t r2, uint32_t r3) {
  asm volatile("stmatrix.sync.aligned.m8n8.x4.shared.b16 [%0], {%1,%2,%3,%4};" ::"r"(a), "r"(r0), "r"(r1), "r"(r2), "r"(r3) : "memory");
}
__device__ __forceinline__ void tma3(uint32_t dst, const CUtensorMap* m, int c0, int c1, int c2, uint32_t bar) {
  asm volatile("cp.async.bulk.tensor.3d.shared::cluster.global.mbarrier::complete_tx::bytes [%0], [%1, {%3,%4,%5}], [%2];"
               ::"r"(dst), "l"(m), "r"(bar), "r"(c0), "r"(c1), "r"(c2) : "memory");
}
__device__ __forceinline__ void tma2(uint32_t dst, const CUtensorMap* m, int c0, int c1, uint32_t bar) {
  asm volatile("cp.async.bulk.tensor.2d.shared::cluster.global.mbarrier::complete_tx::bytes [%0], [%1, {%3,%4}], [%2];"
               ::"r"(dst), "l"(m), "r"(bar), "r"(c0), "r"(c1) : "memory");
}
__device__ __forceinline__ uint32_t lds32(uint32_t a) { uint32_t v; asm volatile("ld.shared.u32 %0, [%1];" : "=r"(v) : "r"(a) : "memory"); return v; }
__device__ __forceinline__ void bulk_ld(uint32_t dst, const void* src, int bytes, uint32_t bar) {
  asm volatile("cp.async.bulk.shared::cluster.global.mbarrier::complete_tx::bytes [%0], [%1], %2, [%3];" ::"r"(dst), "l"(src), "r"(bytes), "r"(bar) : "memory");
}
__device__ __forceinline__ uint4 ldcg4(const void* p) {
  uint4 v; asm volatile("ld.global.cg.v4.u32 {%0,%1,%2,%3}, [%4];" : "=r"(v.x), "=r"(v.y), "=r"(v.z), "=r"(v.w) : "l"(p) : "memory"); return v;
}

__device__ __forceinline__ uint2 ldcg2(const void* p) {
  uint2 v; asm volatile("ld.global.cg.v2.u32 {%0,%1}, [%2];" : "=r"(v.x), "=r"(v.y) : "l"(p) : "memory"); return v;
}

__device__ __forceinline__ void mma_ss_184(float (&d)[92], uint64_t da, uint64_t db, int acc) {
  asm volatile("{.reg .pred p; setp.ne.b32 p, %94, 0;\n"
    "wgmma.mma_async.sync.aligned.m64n184k16.f32.bf16.bf16 {%0,%1,%2,%3,%4,%5,%6,%7,%8,%9,%10,%11,%12,%13,%14,%15,%16,%17,%18,%19,%20,%21,%22,%23,%24,%25,%26,%27,%28,%29,%30,%31,%32,%33,%34,%35,%36,%37,%38,%39,%40,%41,%42,%43,%44,%45,%46,%47,%48,%49,%50,%51,%52,%53,%54,%55,%56,%57,%58,%59,%60,%61,%62,%63,%64,%65,%66,%67,%68,%69,%70,%71,%72,%73,%74,%75,%76,%77,%78,%79,%80,%81,%82,%83,%84,%85,%86,%87,%88,%89,%90,%91}, %92, %93, p, 1, 1, 0, 1;}\n"
    : "+f"(d[0]),"+f"(d[1]),"+f"(d[2]),"+f"(d[3]),"+f"(d[4]),"+f"(d[5]),"+f"(d[6]),"+f"(d[7]),"+f"(d[8]),"+f"(d[9]),"+f"(d[10]),"+f"(d[11]),"+f"(d[12]),"+f"(d[13]),"+f"(d[14]),"+f"(d[15]),"+f"(d[16]),"+f"(d[17]),"+f"(d[18]),"+f"(d[19]),"+f"(d[20]),"+f"(d[21]),"+f"(d[22]),"+f"(d[23]),"+f"(d[24]),"+f"(d[25]),"+f"(d[26]),"+f"(d[27]),"+f"(d[28]),"+f"(d[29]),"+f"(d[30]),"+f"(d[31]),"+f"(d[32]),"+f"(d[33]),"+f"(d[34]),"+f"(d[35]),"+f"(d[36]),"+f"(d[37]),"+f"(d[38]),"+f"(d[39]),"+f"(d[40]),"+f"(d[41]),"+f"(d[42]),"+f"(d[43]),"+f"(d[44]),"+f"(d[45]),"+f"(d[46]),"+f"(d[47]),"+f"(d[48]),"+f"(d[49]),"+f"(d[50]),"+f"(d[51]),"+f"(d[52]),"+f"(d[53]),"+f"(d[54]),"+f"(d[55]),"+f"(d[56]),"+f"(d[57]),"+f"(d[58]),"+f"(d[59]),"+f"(d[60]),"+f"(d[61]),"+f"(d[62]),"+f"(d[63]),"+f"(d[64]),"+f"(d[65]),"+f"(d[66]),"+f"(d[67]),"+f"(d[68]),"+f"(d[69]),"+f"(d[70]),"+f"(d[71]),"+f"(d[72]),"+f"(d[73]),"+f"(d[74]),"+f"(d[75]),"+f"(d[76]),"+f"(d[77]),"+f"(d[78]),"+f"(d[79]),"+f"(d[80]),"+f"(d[81]),"+f"(d[82]),"+f"(d[83]),"+f"(d[84]),"+f"(d[85]),"+f"(d[86]),"+f"(d[87]),"+f"(d[88]),"+f"(d[89]),"+f"(d[90]),"+f"(d[91])
    : "l"(da), "l"(db), "r"(acc));
}
__device__ __forceinline__ void mma_ss_224(float (&d)[112], uint64_t da, uint64_t db, int acc) {
  asm volatile("{.reg .pred p; setp.ne.b32 p, %114, 0;\n"
    "wgmma.mma_async.sync.aligned.m64n224k16.f32.bf16.bf16 {%0,%1,%2,%3,%4,%5,%6,%7,%8,%9,%10,%11,%12,%13,%14,%15,%16,%17,%18,%19,%20,%21,%22,%23,%24,%25,%26,%27,%28,%29,%30,%31,%32,%33,%34,%35,%36,%37,%38,%39,%40,%41,%42,%43,%44,%45,%46,%47,%48,%49,%50,%51,%52,%53,%54,%55,%56,%57,%58,%59,%60,%61,%62,%63,%64,%65,%66,%67,%68,%69,%70,%71,%72,%73,%74,%75,%76,%77,%78,%79,%80,%81,%82,%83,%84,%85,%86,%87,%88,%89,%90,%91,%92,%93,%94,%95,%96,%97,%98,%99,%100,%101,%102,%103,%104,%105,%106,%107,%108,%109,%110,%111}, %112, %113, p, 1, 1, 0, 1;}\n"
    : "+f"(d[0]),"+f"(d[1]),"+f"(d[2]),"+f"(d[3]),"+f"(d[4]),"+f"(d[5]),"+f"(d[6]),"+f"(d[7]),"+f"(d[8]),"+f"(d[9]),"+f"(d[10]),"+f"(d[11]),"+f"(d[12]),"+f"(d[13]),"+f"(d[14]),"+f"(d[15]),"+f"(d[16]),"+f"(d[17]),"+f"(d[18]),"+f"(d[19]),"+f"(d[20]),"+f"(d[21]),"+f"(d[22]),"+f"(d[23]),"+f"(d[24]),"+f"(d[25]),"+f"(d[26]),"+f"(d[27]),"+f"(d[28]),"+f"(d[29]),"+f"(d[30]),"+f"(d[31]),"+f"(d[32]),"+f"(d[33]),"+f"(d[34]),"+f"(d[35]),"+f"(d[36]),"+f"(d[37]),"+f"(d[38]),"+f"(d[39]),"+f"(d[40]),"+f"(d[41]),"+f"(d[42]),"+f"(d[43]),"+f"(d[44]),"+f"(d[45]),"+f"(d[46]),"+f"(d[47]),"+f"(d[48]),"+f"(d[49]),"+f"(d[50]),"+f"(d[51]),"+f"(d[52]),"+f"(d[53]),"+f"(d[54]),"+f"(d[55]),"+f"(d[56]),"+f"(d[57]),"+f"(d[58]),"+f"(d[59]),"+f"(d[60]),"+f"(d[61]),"+f"(d[62]),"+f"(d[63]),"+f"(d[64]),"+f"(d[65]),"+f"(d[66]),"+f"(d[67]),"+f"(d[68]),"+f"(d[69]),"+f"(d[70]),"+f"(d[71]),"+f"(d[72]),"+f"(d[73]),"+f"(d[74]),"+f"(d[75]),"+f"(d[76]),"+f"(d[77]),"+f"(d[78]),"+f"(d[79]),"+f"(d[80]),"+f"(d[81]),"+f"(d[82]),"+f"(d[83]),"+f"(d[84]),"+f"(d[85]),"+f"(d[86]),"+f"(d[87]),"+f"(d[88]),"+f"(d[89]),"+f"(d[90]),"+f"(d[91]),"+f"(d[92]),"+f"(d[93]),"+f"(d[94]),"+f"(d[95]),"+f"(d[96]),"+f"(d[97]),"+f"(d[98]),"+f"(d[99]),"+f"(d[100]),"+f"(d[101]),"+f"(d[102]),"+f"(d[103]),"+f"(d[104]),"+f"(d[105]),"+f"(d[106]),"+f"(d[107]),"+f"(d[108]),"+f"(d[109]),"+f"(d[110]),"+f"(d[111])
    : "l"(da), "l"(db), "r"(acc));
}
__device__ __forceinline__ void mma_ss_56(float (&d)[28], uint64_t da, uint64_t db, int acc) {
  asm volatile("{.reg .pred p; setp.ne.b32 p, %30, 0;\n"
    "wgmma.mma_async.sync.aligned.m64n56k16.f32.bf16.bf16 {%0,%1,%2,%3,%4,%5,%6,%7,%8,%9,%10,%11,%12,%13,%14,%15,%16,%17,%18,%19,%20,%21,%22,%23,%24,%25,%26,%27}, %28, %29, p, 1, 1, 0, 1;}\n"
    : "+f"(d[0]),"+f"(d[1]),"+f"(d[2]),"+f"(d[3]),"+f"(d[4]),"+f"(d[5]),"+f"(d[6]),"+f"(d[7]),"+f"(d[8]),"+f"(d[9]),"+f"(d[10]),"+f"(d[11]),"+f"(d[12]),"+f"(d[13]),"+f"(d[14]),"+f"(d[15]),"+f"(d[16]),"+f"(d[17]),"+f"(d[18]),"+f"(d[19]),"+f"(d[20]),"+f"(d[21]),"+f"(d[22]),"+f"(d[23]),"+f"(d[24]),"+f"(d[25]),"+f"(d[26]),"+f"(d[27])
    : "l"(da), "l"(db), "r"(acc));
}
__device__ __forceinline__ void mma_rs_56(float (&d)[28], uint32_t a0, uint32_t a1, uint32_t a2, uint32_t a3, uint64_t db, int acc) {
  asm volatile("{.reg .pred p; setp.ne.b32 p, %33, 0;\n"
    "wgmma.mma_async.sync.aligned.m64n56k16.f32.bf16.bf16 {%0,%1,%2,%3,%4,%5,%6,%7,%8,%9,%10,%11,%12,%13,%14,%15,%16,%17,%18,%19,%20,%21,%22,%23,%24,%25,%26,%27}, {%28,%29,%30,%31}, %32, p, 1, 1, 1;}\n"
    : "+f"(d[0]),"+f"(d[1]),"+f"(d[2]),"+f"(d[3]),"+f"(d[4]),"+f"(d[5]),"+f"(d[6]),"+f"(d[7]),"+f"(d[8]),"+f"(d[9]),"+f"(d[10]),"+f"(d[11]),"+f"(d[12]),"+f"(d[13]),"+f"(d[14]),"+f"(d[15]),"+f"(d[16]),"+f"(d[17]),"+f"(d[18]),"+f"(d[19]),"+f"(d[20]),"+f"(d[21]),"+f"(d[22]),"+f"(d[23]),"+f"(d[24]),"+f"(d[25]),"+f"(d[26]),"+f"(d[27])
    : "r"(a0), "r"(a1), "r"(a2), "r"(a3), "l"(db), "r"(acc));
}
__device__ __forceinline__ void mma_ss_64t(float (&d)[32], uint64_t da, uint64_t db, int acc) {
  asm volatile("{.reg .pred p; setp.ne.b32 p, %34, 0;\n"
    "wgmma.mma_async.sync.aligned.m64n64k16.f32.bf16.bf16 {%0,%1,%2,%3,%4,%5,%6,%7,%8,%9,%10,%11,%12,%13,%14,%15,%16,%17,%18,%19,%20,%21,%22,%23,%24,%25,%26,%27,%28,%29,%30,%31}, %32, %33, p, 1, 1, 1, 1;}\n"
    : "+f"(d[0]),"+f"(d[1]),"+f"(d[2]),"+f"(d[3]),"+f"(d[4]),"+f"(d[5]),"+f"(d[6]),"+f"(d[7]),"+f"(d[8]),"+f"(d[9]),"+f"(d[10]),"+f"(d[11]),"+f"(d[12]),"+f"(d[13]),"+f"(d[14]),"+f"(d[15]),"+f"(d[16]),"+f"(d[17]),"+f"(d[18]),"+f"(d[19]),"+f"(d[20]),"+f"(d[21]),"+f"(d[22]),"+f"(d[23]),"+f"(d[24]),"+f"(d[25]),"+f"(d[26]),"+f"(d[27]),"+f"(d[28]),"+f"(d[29]),"+f"(d[30]),"+f"(d[31])
    : "l"(da), "l"(db), "r"(acc));
}
__device__ __forceinline__ void mma_rs_64(float (&d)[32], uint32_t a0, uint32_t a1, uint32_t a2, uint32_t a3, uint64_t db, int acc) {
  asm volatile("{.reg .pred p; setp.ne.b32 p, %37, 0;\n"
    "wgmma.mma_async.sync.aligned.m64n64k16.f32.bf16.bf16 {%0,%1,%2,%3,%4,%5,%6,%7,%8,%9,%10,%11,%12,%13,%14,%15,%16,%17,%18,%19,%20,%21,%22,%23,%24,%25,%26,%27,%28,%29,%30,%31}, {%32,%33,%34,%35}, %36, p, 1, 1, 1;}\n"
    : "+f"(d[0]),"+f"(d[1]),"+f"(d[2]),"+f"(d[3]),"+f"(d[4]),"+f"(d[5]),"+f"(d[6]),"+f"(d[7]),"+f"(d[8]),"+f"(d[9]),"+f"(d[10]),"+f"(d[11]),"+f"(d[12]),"+f"(d[13]),"+f"(d[14]),"+f"(d[15]),"+f"(d[16]),"+f"(d[17]),"+f"(d[18]),"+f"(d[19]),"+f"(d[20]),"+f"(d[21]),"+f"(d[22]),"+f"(d[23]),"+f"(d[24]),"+f"(d[25]),"+f"(d[26]),"+f"(d[27]),"+f"(d[28]),"+f"(d[29]),"+f"(d[30]),"+f"(d[31])
    : "r"(a0), "r"(a1), "r"(a2), "r"(a3), "l"(db), "r"(acc));
}

__device__ __forceinline__ void dual_softmax(const float (&p)[28], uint32_t (&phi)[4][7]) {
  constexpr float L2E = 1.4426950408889634f;
#pragma unroll
  for (int i = 0; i < 4; i++) {
    float mx = p[i], mn = p[i];
#pragma unroll
    for (int j = 1; j < 7; j++) { mx = fmaxf(mx, p[4 * j + i]); mn = fminf(mn, p[4 * j + i]); }
    mx = fmaxf(mx, __shfl_xor_sync(~0u, mx, 1)); mn = fminf(mn, __shfl_xor_sync(~0u, mn, 1));
    mx = fmaxf(mx, __shfl_xor_sync(~0u, mx, 2)); mn = fminf(mn, __shfl_xor_sync(~0u, mn, 2));
    float a[7], b[7], sa = 0.f, sb = 0.f;
    const float mxl = mx * L2E, mnl = mn * L2E;
#pragma unroll
    for (int j = 0; j < 7; j++) {
      a[j] = ex2(fmaf(p[4 * j + i], L2E, -mxl)); b[j] = ex2(fmaf(p[4 * j + i], -L2E, mnl));
      sa += a[j]; sb += b[j];
    }
    sa += __shfl_xor_sync(~0u, sa, 1); sb += __shfl_xor_sync(~0u, sb, 1);
    sa += __shfl_xor_sync(~0u, sa, 2); sb += __shfl_xor_sync(~0u, sb, 2);
    const float ra = __fdividef(1.f, sa), rb = __fdividef(1.f, sb);
#pragma unroll
    for (int j = 0; j < 7; j++) phi[i][j] = pack(a[j] * ra, b[j] * rb);
  }
}

struct Ring {
  uint32_t full, empty, base; int slot, par;
  __device__ __forceinline__ void uniform() { slot = __shfl_sync(~0u, slot, 0); par = __shfl_sync(~0u, par, 0); }
  __device__ __forceinline__ uint32_t acquire() { mbar_wait(full + slot * 8, par); return base + slot * SLOT; }
  __device__ __forceinline__ int advance() { int s = slot; if (++slot == NSLOT) { slot = 0; par ^= 1; } return s; }
  __device__ __forceinline__ void release(int s, bool elect) { if (elect) mbar_arrive(empty + s * 8); }
};
constexpr int UNR = 14;
constexpr int FL_KV = 448, FL_CS = FL_KV + 16, FL_DONE = FL_KV + 32;

__global__ void __launch_bounds__(384, 1)
fused_kernel(const __grid_constant__ CUtensorMap mQKV, const __grid_constant__ CUtensorMap mWO,
             const __grid_constant__ CUtensorMap mW1, const __grid_constant__ CUtensorMap mW2,
             const __grid_constant__ CUtensorMap mX, const __nv_bfloat16* __restrict__ wphi,
             const __nv_bfloat16* __restrict__ b1, const __nv_bfloat16* __restrict__ b2,
             const __nv_bfloat16* __restrict__ wqkv, const __nv_bfloat16* __restrict__ wo, const __nv_bfloat16* __restrict__ w1,
             const __nv_bfloat16* __restrict__ w2, __nv_bfloat16* __restrict__ out) {
  extern __shared__ unsigned char smem_raw[];
  const uint32_t sb = (smem_u32(smem_raw) + 1023) & ~1023u;
  unsigned char* sg = smem_raw + (sb - smem_u32(smem_raw));
  const int tid = threadIdx.x, lane = tid & 31;
  const int G = blockIdx.x >> 3, r = blockIdx.x & 7;
  const uint32_t barFull = sb + OFF_BAR, barEmpty = barFull + 56, barA = barEmpty + 56, barCS = barA + 112, barX = barCS + 16;
  const int warp = __shfl_sync(~0u, tid >> 5, 0);
  uint32_t wv[7], bv;
#pragma unroll
  for (int i = 0; i < 7; i++)
    wv[i] = __ldg(reinterpret_cast<const unsigned short*>(wphi) + (56 * r + i * 8 + (warp & 7)) * 28 + min(lane, 27));
  bv = __ldg(reinterpret_cast<const unsigned short*>(b1) + 224 * r + min(tid, 223));
  if (lane == 0) {
    if (warp >= 10) {
      const int cc = warp - 10;
      mbar_init(barX + cc * 8, 1);
      fence_async_smem();
      mbar_expect(barX + cc * 8, ABYTES);
#pragma unroll 1
      for (int k = 0; k < 7; k++) tma2(sb + cc * ABYTES + k * 8192, &mX, 64 * k, G * 128 + 64 * cc, barX + cc * 8);
    } else if (warp < 7) { mbar_init(barFull + warp * 8, 1); mbar_init(barEmpty + warp * 8, 2); mbar_init(barA + warp * 8, 1); mbar_init(barA + 56 + warp * 8, 1); }
    else if (warp < 9) { mbar_init(barCS + (warp - 7) * 8, 64); if (warp == 7) mbar_init(barX + 16, 1); }
    else
      asm volatile("cp.async.bulk.prefetch.L2.global [%0], %1;" ::"l"((const char*)wqkv + blockIdx.x * 9408), "r"(9408) : "memory");
    asm volatile("fence.mbarrier_init.release.cluster;" ::: "memory");
  }
  if (tid < 192) reinterpret_cast<float*>(sg + OFF_CS)[tid] = 0.f;
  __syncthreads();
  const int wgid = warp >> 2;
  if (wgid == 2) {
    asm volatile("setmaxnreg.dec.sync.aligned.u32 40;");
    if (warp == 8) {
      int slot = 0, par = 1;
#pragma unroll 1
      for (int it = 0; it < 2 * TILES_PER_LAYER; it++) {
        const int i = it >= TILES_PER_LAYER ? it - TILES_PER_LAYER : it;
        mbar_wait(barEmpty + slot * 8, par);
        const uint32_t dst = sb + OFF_RING + slot * SLOT, fb = barFull + slot * 8;
        if (elect_one()) {
          mbar_expect(fb, i < 14 ? 12288 : SLOT);
          if (i < 14) tma3(dst, &mQKV, 56 * r, 32 * i, 0, fb);
          else if (i < 18) tma2(dst, &mWO, 56 * r, 112 * (i - 14), fb);
          else if (i < 32) tma3(dst, &mW1, 0, 32 * (i - 18), 7 * r, fb);
          else tma2(dst, &mW2, 64 * ((i - 32) >> 1), 224 * r + 112 * (i & 1), fb);
        }
        if (++slot == NSLOT) { slot = 0; par ^= 1; }
      }
    } else if (warp == 11) {
      unsigned ep;
      asm volatile("ld.relaxed.gpu.global.u32 %0, [%1];" : "=r"(ep) : "l"(gFlag + FL_DONE * 32) : "memory");
#pragma unroll 1
      for (int layer = 0; layer < 2; layer++) {
        bar_sync<4, 288>();
        if (lane == 0) {
          flag_arrive(gFlag + (FL_KV + layer * 8 + r) * 32);
          flag_wait(gFlag + (FL_KV + layer * 8 + r) * 32, (ep / NCTA + 1) * 16);
          mbar_arrive(barX + 16);
        }
        __syncwarp();
      }
    } else {
      unsigned ep;
      asm volatile("ld.relaxed.gpu.global.u32 %0, [%1];" : "=r"(ep) : "l"(gFlag + FL_DONE * 32) : "memory");
      const int idx = tid - 288;
      ep = (ep / NCTA + 1) * 2;
      if (G == 0) {
#pragma unroll 1
        for (int i = idx; i < 2 * 1280; i += 64) gKV[((i >= 1280) * 7 + r) * 1280 + i] = make_float4(0.f, 0.f, 0.f, 0.f);
        __syncwarp();
        if (lane == 0) flag_arrive(gFlag + (FL_CS + r) * 32);
      }
      mbar_wait(barFull + 48, 0); mbar_wait(barFull + 48, 1);
      if (idx < 2) {
        const char* pf = idx ? (const char*)w2 + blockIdx.x * 12544 : (const char*)wo + blockIdx.x * 3136;
        asm volatile("cp.async.bulk.prefetch.L2.global [%0], %1;" ::"l"(pf), "r"(idx ? 12544 : 3136) : "memory");
      }
      if (lane == 0) flag_wait(gFlag + (FL_CS + r) * 32, ep);
      __syncwarp();
      mbar_arrive(barCS);
#pragma unroll 1
      for (int ps = 0; ps < 4; ps++) {
        const int ch = min(ps * 16 + (idx >> 2), 48), p = ch / 7, k0 = G * 28 + (idx & 3) * 7;
        const uint4* src = ch >= 21 ? reinterpret_cast<const uint4*>(w1 + (size_t)k0 * 1792 + 224 * r) + (ch - 21)
                                    : reinterpret_cast<const uint4*>(wqkv + (size_t)k0 * 1344 + p * 448 + 56 * r) + (ch - 7 * p);
        uint4 cu[7];
#pragma unroll
        for (int i = 0; i < 7; i++) cu[i] = __ldg(src + i * (ch >= 21 ? 224 : 168));
        float s[8] = {};
#pragma unroll
        for (int i = 0; i < 7; i++) { s[0] += lo(cu[i].x); s[1] += hi(cu[i].x); s[2] += lo(cu[i].y); s[3] += hi(cu[i].y); s[4] += lo(cu[i].z); s[5] += hi(cu[i].z); s[6] += lo(cu[i].w); s[7] += hi(cu[i].w); }
#pragma unroll
        for (int i = 0; i < 8; i++) { s[i] += __shfl_xor_sync(~0u, s[i], 1); s[i] += __shfl_xor_sync(~0u, s[i], 2); }
        if ((idx & 3) < 2) gCS[(r * 16 + G) * 104 + (ch + min(p, 3)) * 2 + (idx & 1)] = (idx & 1) ? make_float4(s[4], s[5], s[6], s[7]) : make_float4(s[0], s[1], s[2], s[3]);
      }
      __syncwarp();
      if (lane == 0) { flag_arrive(gFlag + (FL_CS + 8 + r) * 32); flag_wait(gFlag + (FL_CS + 8 + r) * 32, ep * 16); }
      __syncwarp();
#pragma unroll 1
      for (int j = idx; j < 208; j += 64) {
        float2 a = make_float2(0.f, 0.f);
#pragma unroll 8
        for (int i = 0; i < 16; i++) { const float2 v = __ldcg(reinterpret_cast<const float2*>(gCS + (r * 16 + i) * 104) + j); a.x += v.x; a.y += v.y; }
        reinterpret_cast<float2*>(sg + OFF_CS)[j] = a;
      }
      mbar_arrive(barCS + 8);
    }
  } else {
  asm volatile("setmaxnreg.inc.sync.aligned.u32 232;");
  const int c = wgid, w = warp & 3, g = lane >> 2, t = lane & 3;
  int elect_i = (tid & 127) == 0;
  asm volatile("" : "+r"(elect_i));
  const bool elect = elect_i;
  const uint32_t abuf = sb + c * ABYTES, barAc = barA + c * 56;
  const int row0 = G * 128 + c * 64;
  unsigned epoch;
  asm volatile("ld.relaxed.gpu.global.u32 %0, [%1];" : "=r"(epoch) : "l"(gFlag + FL_DONE * 32) : "memory");
  STAMP(24);
  float mean[2], rstd[2] = {0.f, 0.f};
  uint4 su[2] = {};
  uint32_t xs[7][2];
  {
#pragma unroll
    for (int i = 0; i < 8; i++) {
      const int k = i * 8 + (tid >> 5);
      *reinterpret_cast<uint32_t*>(sg + OFF_WPHI + k * 128 + ((g ^ (k & 7)) << 4) + t * 4) = (i < 7 && lane < 28) ? wv[i % 7] << (k >= 28 ? 16 : 0) : 0u;
    }
    if (tid < 224) reinterpret_cast<uint32_t*>(sg + OFF_B1)[tid] = bv << 16;
    mbar_wait(barX + c * 8, 0);
    STAMP(25);
#pragma unroll
    for (int j = 0; j < 7; j++) {
      const int ci = 7 * r + j;
      const uint32_t a = abuf + (ci >> 3) * 8192 + (w * 16 + g) * 128 + (((ci & 7) ^ g) << 4) + t * 4;
      xs[j][0] = lds32(a); xs[j][1] = lds32(a + 1024);
    }
    __syncwarp();
#pragma unroll 1
    for (int hh = 0; hh < 2; hh++) {
      uint4* p = reinterpret_cast<uint4*>(sg + c * ABYTES + (w * 16 + hh * 8 + g) * 128) + t;
      uint4 v[14];
#pragma unroll
      for (int k = 0; k < 14; k++) v[k] = p[(k >> 1) * 512 + ((k ^ g) & 1) * 4];
      float a8[8] = {};
#pragma unroll
      for (int k = 0; k < 14; k++) {
        const uint32_t e[4] = {v[k].x, v[k].y, v[k].z, v[k].w};
#pragma unroll
        for (int z = 0; z < 4; z++) { a8[2 * z] += lo(e[z]); a8[2 * z + 1] += hi(e[z]); }
      }
      float sm = ((a8[0] + a8[1]) + (a8[2] + a8[3])) + ((a8[4] + a8[5]) + (a8[6] + a8[7]));
      sm += __shfl_xor_sync(~0u, sm, 1); sm += __shfl_xor_sync(~0u, sm, 2);
      sm *= 1.f / DM;
#pragma unroll
      for (int k = 0; k < 14; k++) {
        uint32_t e[4] = {v[k].x, v[k].y, v[k].z, v[k].w};
#pragma unroll
        for (int z = 0; z < 4; z++) {
          const float a = lo(e[z]) - sm, b = hi(e[z]) - sm;
          a8[2 * z] = fmaf(a, a, k ? a8[2 * z] : 0.f); a8[2 * z + 1] = fmaf(b, b, k ? a8[2 * z + 1] : 0.f);
          e[z] = pack(a, b);
        }
        p[(k >> 1) * 512 + ((k ^ g) & 1) * 4] = make_uint4(e[0], e[1], e[2], e[3]);
      }
      float q = ((a8[0] + a8[1]) + (a8[2] + a8[3])) + ((a8[4] + a8[5]) + (a8[6] + a8[7]));
      q += __shfl_xor_sync(~0u, q, 1); q += __shfl_xor_sync(~0u, q, 2);
      rstd[1] = rsqrtf(q * (1.f / DM) + 1e-5f);
      if (hh == 0) rstd[0] = rstd[1];
    }
    fence_async_smem();
    bar_sync<3, 256>();
    epoch = epoch / NCTA + 1;
    mean[0] = mean[1] = 0.f;
  }
  STAMP(0);
  Ring ring{barFull, barEmpty, sb + OFF_RING, 0, 0};
  int apar = 1;
  const uint32_t stsm_off = (w * 16 + ((lane >> 3) & 1) * 8 + (lane & 7)) * 128;
  const uint32_t stsm_hi = lane >> 4;
  const uint64_t dA = mkdesc(abuf, 1024, 128, 0);

  auto gather = [&](unsigned* fl, const unsigned char* img) {
    bar_wg(c);
    if (w == 0) {
      if (elect_one()) {
        flag_arrive(fl);
        flag_wait(fl, epoch * 8);
        fence_async();
#pragma unroll
        for (int k = 0; k < 7; k++) { mbar_expect(barAc + k * 8, 8192); bulk_ld(abuf + k * 8192, img + k * 8192, 8192, barAc + k * 8); }
      }
      __syncwarp();
    }
    apar ^= 1;
  };
  auto slice_off = [&](int j, int hh) -> uint32_t {
    return (7 * r + j) * 1024 + (w * 2 + hh) * 128 + lane * 4;
  };
  auto load_stats = [&](const float2* st) {
    mbar_wait(barAc, apar);
#pragma unroll
    for (int hh = 0; hh < 2; hh++) su[hh] = ldcg4(st + (size_t)(row0 + w * 16 + hh * 8 + g) * 8 + 2 * t);
  };
  auto finish_stats = [&]() {
#pragma unroll
    for (int hh = 0; hh < 2; hh++) {
      const float m0 = __uint_as_float(su[hh].x), m1 = __uint_as_float(su[hh].z);
      float m = m0 + m1;
      m += __shfl_xor_sync(~0u, m, 1); m += __shfl_xor_sync(~0u, m, 2);
      m *= 0.125f;
      float q = __uint_as_float(su[hh].y) + __uint_as_float(su[hh].w) + 56.f * ((m0 - m) * (m0 - m) + (m1 - m) * (m1 - m));
      q += __shfl_xor_sync(~0u, q, 1); q += __shfl_xor_sync(~0u, q, 2);
      mean[hh] = m; rstd[hh] = rsqrtf(q * (1.f / DM) + 1e-5f);
    }
  };

#pragma unroll 1
  for (int lyr = 0; lyr < 2; lyr++) {
    const int layer = __shfl_sync(~0u, lyr, 0);
    unsigned* const fl = gFlag + (layer * 32 + G * 2 + c) * 7 * 32;
    uint32_t phiq[4][7];
    {
      float acc[92]; reg_def(acc);
      int prev = 0, prev2 = 0;
      ring.uniform();
      const uint64_t dQ = layer ? dA : mkdesc(abuf, 16, 1024, 1);
      const int kstep = layer ? 128 : 2;
      if (layer) load_stats(gStat + 2048 * 8);
#pragma unroll UNR
      for (int st = 0; st < 14; st++) {
        if (!(st & 1) && layer) mbar_wait(barAc + (st >> 1) * 8, apar);
        const uint64_t da = dQ + (st >> 1) * 512 + (st & 1) * 2 * kstep, db = mkdesc(ring.acquire(), 4096, 1024, 1);
        wg_fence();
        mma_ss_184(acc, da, db, 1);
        mma_ss_184(acc, da + kstep, db + 128, 1);
        wg_commit();
        if (st > 1) { wg_wait<2>(); ring.release(prev2, elect); }
        prev2 = prev; prev = ring.advance();
      }
      if (layer) {
        finish_stats();
#pragma unroll
        for (int j = 0; j < 7; j++) { xs[j][0] = lds32(abuf + slice_off(j, 0)); xs[j][1] = lds32(abuf + slice_off(j, 1)); }
      }
      wg_wait<0>(); reg_fence(acc);
      ring.release(prev2, elect); ring.release(prev, elect);
      STAMP(1 + layer * 12);
      uint32_t f[3][14];
      {
        const float2* cs = reinterpret_cast<const float2*>(sg + OFF_CS) + t;
        const float mr0 = -mean[0] * rstd[0], mr1 = -mean[1] * rstd[1];
#pragma unroll
        for (int p = 0; p < 3; p++)
#pragma unroll
          for (int j = 0; j < 7; j++) {
            const float2 s = cs[p * 32 + j * 4];
            const int b = p * 32 + j * 4;
            f[p][2 * j] = pack(fmaf(acc[b], rstd[0], s.x * mr0), fmaf(acc[b + 1], rstd[0], s.y * mr0));
            f[p][2 * j + 1] = pack(fmaf(acc[b + 2], rstd[1], s.x * mr1), fmaf(acc[b + 3], rstd[1], s.y * mr1));
          }
      }
      float pk[28], pq[28]; reg_def(pk); reg_def(pq);
      const uint64_t dW = mkdesc(sb + OFF_WPHI, 4096, 1024, 1);
      wg_fence();
#pragma unroll
      for (int s = 0; s < 4; s++) {
        mma_rs_56(pk, f[1][4 * s], f[1][4 * s + 1], s < 3 ? f[1][(4 * s + 2) % 14] : 0u, s < 3 ? f[1][(4 * s + 3) % 14] : 0u, dW + s * 128, s);
        mma_rs_56(pq, f[0][4 * s], f[0][4 * s + 1], s < 3 ? f[0][(4 * s + 2) % 14] : 0u, s < 3 ? f[0][(4 * s + 3) % 14] : 0u, dW + s * 128, s);
      }
      wg_commit();
      bar_wg(c);
      const uint32_t srow = abuf + stsm_off, ones = t == 0 ? 0x3F803F80u : 0u;
#pragma unroll
      for (int jp = 0; jp < 4; jp++)
        stsm4(srow + 16384 + (((2 * jp + stsm_hi) ^ (lane & 7)) << 4), f[2][4 * jp], f[2][4 * jp + 1],
              jp < 3 ? f[2][(4 * jp + 2) % 14] : ones, jp < 3 ? f[2][(4 * jp + 3) % 14] : ones);
      wg_wait<0>(); reg_fence(pk); reg_fence(pq);
#pragma unroll 1
      for (int pass = 0; pass < 2; pass++) {
        dual_softmax(pk, phiq);
        if (pass) break;
#pragma unroll
        for (int e = 0; e < 2; e++)
#pragma unroll
          for (int jp = 0; jp < 4; jp++)
            stsm4(srow + e * 8192 + (((2 * jp + stsm_hi) ^ (lane & 7)) << 4), phiq[e][2 * jp], phiq[2 + e][2 * jp],
                  jp < 3 ? phiq[e][(2 * jp + 1) % 7] : 0u, jp < 3 ? phiq[2 + e][(2 * jp + 1) % 7] : 0u);
        fence_async_smem();
        bar_sync<3, 256>();
        float kv[32], kw[32]; reg_def(kv); reg_def(kw);
        const uint64_t dP = mkdesc(sb + c * 8192, 4096, 1024, 1), dV = mkdesc(sb + 16384, 4096, 1024, 1);
        wg_fence();
#pragma unroll
        for (int s = 0; s < 4; s++) { mma_ss_64t(kv, dP + s * 128, dV + s * 128, s); mma_ss_64t(kw, dP + ABYTES / 16 + s * 128, dV + ABYTES / 16 + s * 128, s); }
        wg_commit();
        mbar_wait(barCS, 0);
        wg_wait<0>(); reg_fence(kv); reg_fence(kw);
#pragma unroll
        for (int i = 0; i < 32; i++) kv[i] += kw[i];
        float4* kvg = gKV + ((layer * 8 + r) * 2 + c) * 640 + (tid & 127);
#pragma unroll
        for (int i = 0; i < 5; i++) {
          float v0, v1, v2, v3;
          if (i == 4) { v0 = kv[28]; v1 = kv[29]; v2 = kv[30]; v3 = kv[31]; }
          else { v0 = c ? kv[12 + 4 * i] : kv[4 * i]; v1 = c ? kv[13 + 4 * i] : kv[1 + 4 * i]; v2 = c ? kv[14 + 4 * i] : kv[2 + 4 * i]; v3 = c ? kv[15 + 4 * i] : kv[3 + 4 * i]; }
          const bool use = i == 4 ? t == 0 : (i == 0 ? (c == 0 || t >= 2) : (i == 3 ? (c == 1 || t < 2) : true));
          if (use) asm volatile("red.relaxed.gpu.global.add.v4.f32 [%0], {%1,%2,%3,%4};" ::"l"(kvg + i * 128), "f"(v0), "f"(v1), "f"(v2), "f"(v3) : "memory");
        }
        asm volatile("bar.arrive 4, 288;" ::: "memory");
        STAMP(2 + layer * 12);
#pragma unroll
        for (int i = 0; i < 28; i++) pk[i] = pq[i];
      }
    }
    {
      mbar_wait(barX + 16, layer);
      STAMP(3 + layer * 12);
      const float4* kvg = gKV + (layer * 8 + r) * 1280 + c * 640 + (tid & 127);
      uint4 kk[5];
#pragma unroll
      for (int i = 0; i < 5; i++) kk[i] = ldcg4(kvg + i * 128);
      uint32_t f[5][2];
#pragma unroll
      for (int i = 0; i < 5; i++) { f[i][0] = pack(__uint_as_float(kk[i].x), __uint_as_float(kk[i].y)); f[i][1] = pack(__uint_as_float(kk[i].z), __uint_as_float(kk[i].w)); }
      const uint32_t zm = c ? 0xFFFF0000u : 0xFFFFu;
      const uint32_t srow = abuf + 24576 + stsm_off;
#pragma unroll
      for (int jp = 0; jp < 4; jp++) {
        uint32_t v[2][2];
#pragma unroll
        for (int u = 0; u < 2; u++) {
          const int j = 2 * jp + u;
#pragma unroll
          for (int hh = 0; hh < 2; hh++) v[u][hh] = j == 7 ? f[4][hh] & zm : (c ? (j >= 3 ? f[(j + 2) % 5][hh] : 0u) : (j < 4 ? f[j % 5][hh] : 0u));
        }
        stsm4(srow + (((2 * jp + stsm_hi) ^ (lane & 7)) << 4), v[0][0], v[0][1], v[1][0], v[1][1]);
      }
      fence_async_smem();
      bar_sync<3, 256>();
      float num[32], nub[32]; reg_def(num); reg_def(nub);
      const uint64_t dK = mkdesc(sb + 24576, 4096, 1024, 1);
      wg_fence();
#pragma unroll
      for (int s = 0; s < 4; s++) {
        mma_rs_64(num, phiq[0][2 * s], phiq[2][2 * s], s < 3 ? phiq[0][(2 * s + 1) % 7] : 0u, s < 3 ? phiq[2][(2 * s + 1) % 7] : 0u, dK + s * 128, s);
        mma_rs_64(nub, phiq[1][2 * s], phiq[3][2 * s], s < 3 ? phiq[1][(2 * s + 1) % 7] : 0u, s < 3 ? phiq[3][(2 * s + 1) % 7] : 0u, dK + ABYTES / 16 + s * 128, s);
      }
      wg_commit();
      wg_wait<0>(); reg_fence(num); reg_fence(nub);
      bar_sync<3, 256>();
#pragma unroll
      for (int i = 12; i < 32; i++) num[i] += nub[i];
      float rd[4];
#pragma unroll
      for (int i = 0; i < 4; i++) rd[i] = __fdividef(1.f, __shfl_sync(~0u, num[28 + i], lane & ~3) + 1e-6f);
      unsigned char* img = gImg + (size_t)(G * 2 + c) * ABYTES;
#pragma unroll
      for (int j = 0; j < 7; j++) {
        const bool hb = j > 3 || (j == 3 && t >= 2);
        const float r0 = hb ? rd[1] : rd[0], r1 = hb ? rd[3] : rd[2];
        *reinterpret_cast<uint32_t*>(img + slice_off(j, 0)) = pack(num[4 * j] * r0, num[4 * j + 1] * r0);
        *reinterpret_cast<uint32_t*>(img + slice_off(j, 1)) = pack(num[4 * j + 2] * r1, num[4 * j + 3] * r1);
      }
      STAMP(4 + layer * 12);
      gather(fl, img);
      STAMP(5 + layer * 12);
    }
    {
      float acc[28], acc2[28]; reg_def(acc); reg_def(acc2); reg_fence(acc); reg_fence(acc2);
      int sl[4];
      ring.uniform();
#pragma unroll
      for (int st = 0; st < 4; st++) {
        const uint64_t db = mkdesc(ring.acquire(), 4096, 1024, 1);
        sl[st] = ring.advance();
#pragma unroll
        for (int s = 0; s < 7; s++) {
          const int ks = st * 7 + s;
          if (!(ks & 3)) mbar_wait(barAc + (ks >> 2) * 8, apar);
          if (!(ks & 3) || !s) wg_fence();
          if (ks & 1) mma_ss_56(acc2, dA + ks * 128, db + s * 128, ks > 1); else mma_ss_56(acc, dA + ks * 128, db + s * 128, ks > 1);
        }
        wg_commit();
      }
      wg_wait<0>(); reg_fence(acc); reg_fence(acc2);
      unsigned char* img = gImg + (size_t)(32 + G * 2 + c) * ABYTES;
#pragma unroll
      for (int hh = 0; hh < 2; hh++) {
        float s = 0.f, q = 0.f;
#pragma unroll
        for (int j = 0; j < 7; j++) {
          xs[j][hh] = pack(lo(xs[j][hh]) + (acc[4 * j + 2 * hh] + acc2[4 * j + 2 * hh]), hi(xs[j][hh]) + (acc[4 * j + 2 * hh + 1] + acc2[4 * j + 2 * hh + 1]));
          *reinterpret_cast<uint32_t*>(img + slice_off(j, hh)) = xs[j][hh];
          s += lo(xs[j][hh]) + hi(xs[j][hh]);
        }
        s += __shfl_xor_sync(~0u, s, 1); s += __shfl_xor_sync(~0u, s, 2);
        s *= 1.f / 56.f;
#pragma unroll
        for (int j = 0; j < 7; j++) { const float a = lo(xs[j][hh]) - s, b = hi(xs[j][hh]) - s; q = fmaf(a, a, q); q = fmaf(b, b, q); }
        q += __shfl_xor_sync(~0u, q, 1); q += __shfl_xor_sync(~0u, q, 2);
        if (t == 0) gStat[(size_t)(row0 + w * 16 + hh * 8 + g) * 8 + r] = make_float2(s, q);
      }
#pragma unroll
      for (int j = 0; j < 7; j++) xs[j][0] = xs[j][1] = 0u;
      STAMP(6 + layer * 12);
      gather(fl + 32, img);
#pragma unroll
      for (int st = 0; st < 4; st++) ring.release(sl[st], elect);
      STAMP(7 + layer * 12);
    }
    {
      uint32_t hf[28][2];
      {
        float acc[112]; reg_def(acc);
        int prev = 0, prev2 = 0;
        load_stats(gStat);
        ring.uniform();
#pragma unroll UNR
        for (int st = 0; st < 14; st++) {
          if (!(st & 1)) mbar_wait(barAc + (st >> 1) * 8, apar);
          const uint64_t da = dA + st * 256, db = mkdesc(ring.acquire(), 2048, 512, 2);
          wg_fence();
          mma_ss_224(acc, da, db, 1);
          mma_ss_224(acc, da + 128, db + 64, 1);
          wg_commit();
          if (st > 1) { wg_wait<2>(); ring.release(prev2, elect); }
          prev2 = prev; prev = ring.advance();
        }
        finish_stats();
        mbar_wait(barCS + 8, 0);
        wg_wait<0>(); reg_fence(acc);
        ring.release(prev2, elect); ring.release(prev, elect);
        STAMP(8 + layer * 12);
        const float2* bs = reinterpret_cast<const float2*>(sg + OFF_B1) + t;
        const float2* cs = reinterpret_cast<const float2*>(sg + OFF_CS + 768) + t;
        const float mr0 = -mean[0] * rstd[0], mr1 = -mean[1] * rstd[1];
#pragma unroll
        for (int j = 0; j < 28; j++) {
          const float2 b = bs[4 * j], s = cs[4 * j];
          hf[j][0] = relu_sq(fmaf(acc[4 * j], rstd[0], fmaf(s.x, mr0, b.x)), fmaf(acc[4 * j + 1], rstd[0], fmaf(s.y, mr0, b.y)));
          hf[j][1] = relu_sq(fmaf(acc[4 * j + 2], rstd[1], fmaf(s.x, mr1, b.x)), fmaf(acc[4 * j + 3], rstd[1], fmaf(s.y, mr1, b.y)));
        }
      }
      unsigned char* pd[2]; int pstr[2];
#pragma unroll
      for (int hh = 0; hh < 2; hh++) {
        const bool own = 2 * w + hh == r;
        pd[hh] = own ? sg + c * ABYTES + (lane >> 4) * 1024 + (r ^ 1) * 128 + (lane & 15) * 8
                     : gP + (size_t)(((G * 2 + c) * 8 + 2 * w + hh) * 8 + r) * 7168 + lane * 8;
        pstr[hh] = own ? 2048 : 256;
      }
      uint2 pk[8] = {};
      ring.uniform();
#pragma unroll 1
      for (int ch = 0; ch < 7; ch++) {
        float acc[32], acc2[32]; reg_def(acc); reg_def(acc2);
        const uint64_t db0 = mkdesc(ring.acquire(), 4096, 1024, 1);
        const int sl0 = ring.advance();
        const uint64_t db1 = mkdesc(ring.acquire(), 4096, 1024, 1);
        const int sl1 = ring.advance();
        wg_fence();
#pragma unroll
        for (int s = 0; s < 7; s++) {
          mma_rs_64(acc, hf[2 * s][0], hf[2 * s][1], hf[2 * s + 1][0], hf[2 * s + 1][1], db0 + s * 128, s);
          mma_rs_64(acc2, hf[14 + 2 * s][0], hf[14 + 2 * s][1], hf[15 + 2 * s][0], hf[15 + 2 * s][1], db1 + s * 128, s);
        }
        wg_commit();
        if (ch > 0) {
#pragma unroll
          for (int i = 0; i < 8; i++) { *reinterpret_cast<uint2*>(pd[i & 1]) = pk[i]; pd[i & 1] += pstr[i & 1]; }
        }
        wg_wait<0>(); reg_fence(acc); reg_fence(acc2); ring.release(sl0, elect); ring.release(sl1, elect);
#pragma unroll
        for (int i = 0; i < 8; i++) {
          const int b = (i >> 1) * 8 + (i & 1) * 2;
          pk[i] = make_uint2((pack(acc[b] + acc2[b], acc[b + 1] + acc2[b + 1]) & ~1u) | (layer ^ 1), pack(acc[b + 4] + acc2[b + 4], acc[b + 5] + acc2[b + 5]));
        }
      }
#pragma unroll
      for (int i = 0; i < 8; i++) { *reinterpret_cast<uint2*>(pd[i & 1]) = pk[i]; pd[i & 1] += pstr[i & 1]; }
      STAMP(9 + layer * 12);
    }
    {
      uint32_t bx[14];
#pragma unroll
      for (int j = 0; j < 14; j++) bx[j] = __ldg(reinterpret_cast<const uint32_t*>(b2 + (j >> 1) * 64 + w * 16 + (j & 1) * 8 + 2 * t));
      const unsigned char* psrc = gP + (size_t)(((G * 2 + c) * 8 + r) * 8) * 7168 + w * 256 + lane * 8;
      unsigned char* img = gImg + (size_t)(64 + G * 2 + c) * ABYTES;
      uint2 pv[7][7];
      const unsigned char* ps[7];
#pragma unroll
      for (int s = 0; s < 7; s++) ps[s] = psrc + ((r + 1 + s) & 7) * 7168;
#pragma unroll
      for (int i = 0; i < 5; i++)
#pragma unroll
        for (int s = 0; s < 7; s++) pv[s][i] = ldcg2(ps[s] + i * 1024);
      bar_wg(c);
      const uint32_t off = w * 2048 + r * 128 + lane * 4;
      unsigned char* dst = layer ? reinterpret_cast<unsigned char*>(out + (size_t)(row0 + r * 8 + g) * DM + w * 16 + 4 * t) : img + off;
      float sm = 0.f, q = 0.f;
#pragma unroll
      for (int i = 0; i < 7; i++) {
        const uint2 own = *reinterpret_cast<const uint2*>(sg + c * ABYTES + i * 8192 + w * 2048 + (lane >> 4) * 1024 + (r ^ 1) * 128 + (lane & 15) * 8);
#pragma unroll 1
        for (int n = 0; n < (1 << 16); n++) {
          const uint32_t all = pv[0][i].x & pv[1][i].x & pv[2][i].x & pv[3][i].x & pv[4][i].x & pv[5][i].x & pv[6][i].x;
          const uint32_t any = pv[0][i].x | pv[1][i].x | pv[2][i].x | pv[3][i].x | pv[4][i].x | pv[5][i].x | pv[6][i].x;
          if (!__any_sync(~0u, (layer ? any : ~all) & 1u)) break;
#pragma unroll
          for (int s = 0; s < 7; s++) pv[s][i] = ldcg2(ps[s] + i * 1024);
        }
        if (i < 2) {
#pragma unroll
          for (int s = 0; s < 7; s++) pv[s][5 + (i & 1)] = ldcg2(ps[s] + (5 + i) * 1024);
        }
#pragma unroll
        for (int jj = 0; jj < 2; jj++) {
          const int j = 2 * i + jj;
          const uint32_t xo = lds32(abuf + off + i * 8192 + jj * 1024), uo = jj ? own.y : own.x;
          float y0 = lo(bx[j]) + lo(xo) + lo(uo), y1 = hi(bx[j]) + hi(xo) + hi(uo);
#pragma unroll
          for (int s = 0; s < 7; s++) { const uint32_t u = jj ? pv[s][i].y : pv[s][i].x; y0 += lo(u); y1 += hi(u); }
          bx[j] = pack(y0, y1);
          if (!layer) *reinterpret_cast<uint32_t*>(dst + (i * 8 + jj) * 1024) = bx[j];
          sm += lo(bx[j]) + hi(bx[j]);
        }
        if (layer) {
          const int sl = (lane & ~3) | ((t & 1) << 1);
          const uint32_t a0 = __shfl_sync(~0u, bx[2 * i], sl), a1 = __shfl_sync(~0u, bx[2 * i], sl + 1);
          const uint32_t b0 = __shfl_sync(~0u, bx[2 * i + 1], sl), b1v = __shfl_sync(~0u, bx[2 * i + 1], sl + 1);
          *reinterpret_cast<uint2*>(dst + i * 128) = t < 2 ? make_uint2(a0, a1) : make_uint2(b0, b1v);
        }
      }
      if (layer) break;
      sm += __shfl_xor_sync(~0u, sm, 1); sm += __shfl_xor_sync(~0u, sm, 2);
      sm *= 1.f / 112.f;
#pragma unroll
      for (int j = 0; j < 14; j++) { const float a = lo(bx[j]) - sm, b = hi(bx[j]) - sm; q = fmaf(a, a, q); q = fmaf(b, b, q); }
      q += __shfl_xor_sync(~0u, q, 1); q += __shfl_xor_sync(~0u, q, 2);
      if (t < 2) gStat[(size_t)(2048 + row0 + r * 8 + g) * 8 + 2 * w + t] = make_float2(sm, q * 0.5f);
      STAMP(11);
      gather(fl + 64, img);
      STAMP(12);
    }
  }
  STAMP(30);
  if (tid == 0) asm volatile("red.relaxed.gpu.global.add.u32 [%0], 1;" ::"l"(gFlag + FL_DONE * 32) : "memory");
  }
}

typedef CUresult (*EncFn)(CUtensorMap*, CUtensorMapDataType, cuuint32_t, void*, const cuuint64_t*, const cuuint64_t*,
                          const cuuint32_t*, const cuuint32_t*, CUtensorMapInterleave, CUtensorMapSwizzle,
                          CUtensorMapL2promotion, CUtensorMapFloatOOBfill);

void make_map(EncFn enc, CUtensorMap* m, void* p, int rank, uint64_t d0, uint64_t d1, uint64_t d2, uint64_t s1, uint64_t s2,
              uint32_t b0, uint32_t b1, uint32_t b2, CUtensorMapSwizzle sw) {
  cuuint64_t dims[3] = {d0, d1, d2}, strides[2] = {s1, s2};
  cuuint32_t box[3] = {b0, b1, b2}, es[3] = {1, 1, 1};
  enc(m, CU_TENSOR_MAP_DATA_TYPE_BFLOAT16, rank, p, dims, strides, box, es, CU_TENSOR_MAP_INTERLEAVE_NONE, sw,
      CU_TENSOR_MAP_L2_PROMOTION_L2_128B, CU_TENSOR_MAP_FLOAT_OOB_FILL_NONE);
}

}

extern "C" void kernel_launch(void* const* d_in, const int* in_sizes, int n_in, void* d_out, int out_size) {
  static EncFn enc = nullptr;
  if (!enc) {
    cudaDriverEntryPointQueryResult st;
    void* fn = nullptr;
    cudaGetDriverEntryPoint("cuTensorMapEncodeTiled", &fn, cudaEnableDefault, &st);
    enc = (EncFn)fn;
    cudaFuncSetAttribute(fused_kernel, cudaFuncAttributeMaxDynamicSharedMemorySize, SMEM_BYTES);
  }
  CUtensorMap mQKV, mWO, mW1, mW2, mX;
  make_map(enc, &mX, d_in[0], 2, 448, 2048, 1, 896, 0, 64, 64, 1, CU_TENSOR_MAP_SWIZZLE_128B);
  make_map(enc, &mQKV, d_in[1], 3, 448, 448, 3, 2688, 896, 64, 32, 3, CU_TENSOR_MAP_SWIZZLE_128B);
  make_map(enc, &mWO, d_in[3], 2, 448, 448, 1, 896, 0, 64, 112, 1, CU_TENSOR_MAP_SWIZZLE_128B);
  make_map(enc, &mW1, d_in[5], 3, 32, 448, 56, 3584, 64, 32, 32, 7, CU_TENSOR_MAP_SWIZZLE_64B);
  make_map(enc, &mW2, d_in[7], 2, 448, 1792, 1, 896, 0, 64, 112, 1, CU_TENSOR_MAP_SWIZZLE_128B);
  fused_kernel<<<NCTA, 384, SMEM_BYTES, cudaStreamPerThread>>>(
      mQKV, mWO, mW1, mW2, mX, (const __nv_bfloat16*)d_in[2], (const __nv_bfloat16*)d_in[6],
      (const __nv_bfloat16*)d_in[8], (const __nv_bfloat16*)d_in[1], (const __nv_bfloat16*)d_in[3], (const __nv_bfloat16*)d_in[5],
      (const __nv_bfloat16*)d_in[7], (__nv_bfloat16*)d_out);
}
```

```cpp
#include <cuda_runtime.h>
#include <cuda_bf16.h>
#include <cuda.h>
#include <stdint.h>

namespace {

constexpr int DM = 448, NCTA = 128;
constexpr int ABYTES = 57344;
constexpr int SLOT = 14336, NSLOT = 7;
constexpr int OFF_RING = 2 * ABYTES;
constexpr int OFF_WPHI = OFF_RING + NSLOT * SLOT;
constexpr int OFF_B1 = OFF_WPHI + 8192;
constexpr int OFF_CS = OFF_B1 + 896;
constexpr int OFF_BAR = OFF_CS + 1664;
constexpr int SMEM_BYTES = OFF_BAR + 272 + 1024;
constexpr int TILES_PER_LAYER = 46;

__device__ __align__(1024) unsigned char gP[16 * 2 * 8 * 8 * 7168];
__device__ __align__(1024) unsigned char gImg[3 * 32 * ABYTES];
__device__ __align__(1024) float2 gStat[2 * 2048 * 8];
__device__ __align__(1024) float4 gKV[2 * 8 * 2 * 5 * 128];
__device__ __align__(1024) float4 gCS[8 * 16 * 104];
__device__ __align__(128) unsigned gFlag[(2 * 32 * 7 + 32 + 1 + 16) * 32];
#define STAMP(i)

__device__ __forceinline__ uint32_t smem_u32(const void* p) { return (uint32_t)__cvta_generic_to_shared(p); }
__device__ __forceinline__ void mbar_init(uint32_t b, int c) { asm volatile("mbarrier.init.shared::cta.b64 [%0], %1;" ::"r"(b), "r"(c)); }
__device__ __forceinline__ void mbar_expect(uint32_t b, int bytes) { asm volatile("mbarrier.arrive.expect_tx.shared::cta.b64 _, [%0], %1;" ::"r"(b), "r"(bytes) : "memory"); }
__device__ __forceinline__ void mbar_arrive(uint32_t b) { asm volatile("mbarrier.arrive.shared::cta.b64 _, [%0];" ::"r"(b) : "memory"); }
__device__ __forceinline__ void mbar_wait(uint32_t b, int par) {
  uint32_t ok; int n = 0;
#pragma unroll 1
  while (true) {
    asm volatile("{.reg .pred p; mbarrier.try_wait.parity.shared::cta.b64 p, [%1], %2; selp.u32 %0,1,0,p;}" : "=r"(ok) : "r"(b), "r"(par) : "memory");
    if (ok) break;
    if (++n > (1 << 22)) break;
  }
}
__device__ __forceinline__ void flag_wait(const unsigned* f, unsigned target) {
  unsigned v; int n = 0;
#pragma unroll 1
  while (true) {
    asm volatile("ld.acquire.gpu.global.u32 %0, [%1];" : "=r"(v) : "l"(f) : "memory");
    if ((int)(v - target) >= 0) break;
    if (++n > (1 << 21)) break;
  }
}
__device__ __forceinline__ void flag_arrive(unsigned* f) { asm volatile("red.release.gpu.global.add.u32 [%0], 1;" ::"l"(f) : "memory"); }
__device__ __forceinline__ bool elect_one() {
  uint32_t p; asm volatile("{.reg .pred P; elect.sync _|P, 0xffffffff; selp.u32 %0, 1, 0, P;}" : "=r"(p)); return p;
}
__device__ __forceinline__ void fence_async() { asm volatile("fence.proxy.async.global;" ::: "memory"); }
__device__ __forceinline__ void fence_async_smem() { asm volatile("fence.proxy.async.shared::cta;" ::: "memory"); }
template <int ID, int N> __device__ __forceinline__ void bar_sync() { asm volatile("bar.sync %0, %1;" ::"n"(ID), "n"(N) : "memory"); }
__device__ __forceinline__ void bar_wg(int c) { if (c) bar_sync<2, 128>(); else bar_sync<1, 128>(); }
__device__ __forceinline__ void wg_fence() { asm volatile("wgmma.fence.sync.aligned;" ::: "memory"); }
__device__ __forceinline__ void wg_commit() { asm volatile("wgmma.commit_group.sync.aligned;" ::: "memory"); }
template <int N> __device__ __forceinline__ void wg_wait() { asm volatile("wgmma.wait_group.sync.aligned %0;" ::"n"(N) : "memory"); }
template <int N> __device__ __forceinline__ void reg_fence(float (&d)[N]) {
#pragma unroll
  for (int i = 0; i < N; i++) asm volatile("" : "+f"(d[i])::"memory");
}
template <int N> __device__ __forceinline__ void reg_def(float (&d)[N]) {
#pragma unroll
  for (int i = 0; i < N; i++) d[i] = 0.f;
}
__device__ __forceinline__ uint64_t mkdesc(uint32_t addr, uint32_t lbo, uint32_t sbo, uint64_t swz) {
  return (uint64_t)((addr & 0x3FFFF) >> 4) | ((uint64_t)(lbo >> 4) << 16) | ((uint64_t)(sbo >> 4) << 32) | (swz << 62);
}
__device__ __forceinline__ uint32_t pack(float a, float b) {
  uint32_t r; asm("cvt.rn.bf16x2.f32 %0, %1, %2;" : "=r"(r) : "f"(b), "f"(a)); return r;
}
__device__ __forceinline__ uint32_t relu_sq(float a, float b) {
  uint32_t r; asm("{.reg .b32 v; cvt.rn.relu.bf16x2.f32 v, %1, %2; mul.rn.bf16x2 %0, v, v;}" : "=r"(r) : "f"(b), "f"(a)); return r;
}
__device__ __forceinline__ float lo(uint32_t u) { return __uint_as_float(u << 16); }
__device__ __forceinline__ float hi(uint32_t u) { return __uint_as_float(u & 0xFFFF0000u); }
__device__ __forceinline__ float ex2(float x) { float y; asm("ex2.approx.ftz.f32 %0, %1;" : "=f"(y) : "f"(x)); return y; }
__device__ __forceinline__ void stsm4(uint32_t a, uint32_t r0, uint32_t r1, uint32_t r2, uint32_t r3) {
  asm volatile("stmatrix.sync.aligned.m8n8.x4.shared.b16 [%0], {%1,%2,%3,%4};" ::"r"(a), "r"(r0), "r"(r1), "r"(r2), "r"(r3) : "memory");
}
__device__ __forceinline__ void tma3(uint32_t dst, const CUtensorMap* m, int c0, int c1, int c2, uint32_t bar) {
  asm volatile("cp.async.bulk.tensor.3d.shared::cluster.global.mbarrier::complete_tx::bytes [%0], [%1, {%3,%4,%5}], [%2];"
               ::"r"(dst), "l"(m), "r"(bar), "r"(c0), "r"(c1), "r"(c2) : "memory");
}
__device__ __forceinline__ void tma2(uint32_t dst, const CUtensorMap* m, int c0, int c1, uint32_t bar) {
  asm volatile("cp.async.bulk.tensor.2d.shared::cluster.global.mbarrier::complete_tx::bytes [%0], [%1, {%3,%4}], [%2];"
               ::"r"(dst), "l"(m), "r"(bar), "r"(c0), "r"(c1) : "memory");
}
__device__ __forceinline__ uint32_t lds32(uint32_t a) { uint32_t v; asm volatile("ld.shared.u32 %0, [%1];" : "=r"(v) : "r"(a) : "memory"); return v; }
__device__ __forceinline__ void bulk_ld(uint32_t dst, const void* src, int bytes, uint32_t bar) {
  asm volatile("cp.async.bulk.shared::cluster.global.mbarrier::complete_tx::bytes [%0], [%1], %2, [%3];" ::"r"(dst), "l"(src), "r"(bytes), "r"(bar) : "memory");
}
__device__ __forceinline__ uint4 ldcg4(const void* p) {
  uint4 v; asm volatile("ld.global.cg.v4.u32 {%0,%1,%2,%3}, [%4];" : "=r"(v.x), "=r"(v.y), "=r"(v.z), "=r"(v.w) : "l"(p) : "memory"); return v;
}

__device__ __forceinline__ uint2 ldcg2(const void* p) {
  uint2 v; asm volatile("ld.global.cg.v2.u32 {%0,%1}, [%2];" : "=r"(v.x), "=r"(v.y) : "l"(p) : "memory"); return v;
}

__device__ __forceinline__ void mma_ss_184(float (&d)[92], uint64_t da, uint64_t db, int acc) {
  asm volatile("{.reg .pred p; setp.ne.b32 p, %94, 0;\n"
    "wgmma.mma_async.sync.aligned.m64n184k16.f32.bf16.bf16 {%0,%1,%2,%3,%4,%5,%6,%7,%8,%9,%10,%11,%12,%13,%14,%15,%16,%17,%18,%19,%20,%21,%22,%23,%24,%25,%26,%27,%28,%29,%30,%31,%32,%33,%34,%35,%36,%37,%38,%39,%40,%41,%42,%43,%44,%45,%46,%47,%48,%49,%50,%51,%52,%53,%54,%55,%56,%57,%58,%59,%60,%61,%62,%63,%64,%65,%66,%67,%68,%69,%70,%71,%72,%73,%74,%75,%76,%77,%78,%79,%80,%81,%82,%83,%84,%85,%86,%87,%88,%89,%90,%91}, %92, %93, p, 1, 1, 0, 1;}\n"
    : "+f"(d[0]),"+f"(d[1]),"+f"(d[2]),"+f"(d[3]),"+f"(d[4]),"+f"(d[5]),"+f"(d[6]),"+f"(d[7]),"+f"(d[8]),"+f"(d[9]),"+f"(d[10]),"+f"(d[11]),"+f"(d[12]),"+f"(d[13]),"+f"(d[14]),"+f"(d[15]),"+f"(d[16]),"+f"(d[17]),"+f"(d[18]),"+f"(d[19]),"+f"(d[20]),"+f"(d[21]),"+f"(d[22]),"+f"(d[23]),"+f"(d[24]),"+f"(d[25]),"+f"(d[26]),"+f"(d[27]),"+f"(d[28]),"+f"(d[29]),"+f"(d[30]),"+f"(d[31]),"+f"(d[32]),"+f"(d[33]),"+f"(d[34]),"+f"(d[35]),"+f"(d[36]),"+f"(d[37]),"+f"(d[38]),"+f"(d[39]),"+f"(d[40]),"+f"(d[41]),"+f"(d[42]),"+f"(d[43]),"+f"(d[44]),"+f"(d[45]),"+f"(d[46]),"+f"(d[47]),"+f"(d[48]),"+f"(d[49]),"+f"(d[50]),"+f"(d[51]),"+f"(d[52]),"+f"(d[53]),"+f"(d[54]),"+f"(d[55]),"+f"(d[56]),"+f"(d[57]),"+f"(d[58]),"+f"(d[59]),"+f"(d[60]),"+f"(d[61]),"+f"(d[62]),"+f"(d[63]),"+f"(d[64]),"+f"(d[65]),"+f"(d[66]),"+f"(d[67]),"+f"(d[68]),"+f"(d[69]),"+f"(d[70]),"+f"(d[71]),"+f"(d[72]),"+f"(d[73]),"+f"(d[74]),"+f"(d[75]),"+f"(d[76]),"+f"(d[77]),"+f"(d[78]),"+f"(d[79]),"+f"(d[80]),"+f"(d[81]),"+f"(d[82]),"+f"(d[83]),"+f"(d[84]),"+f"(d[85]),"+f"(d[86]),"+f"(d[87]),"+f"(d[88]),"+f"(d[89]),"+f"(d[90]),"+f"(d[91])
    : "l"(da), "l"(db), "r"(acc));
}
__device__ __forceinline__ void mma_ss_224(float (&d)[112], uint64_t da, uint64_t db, int acc) {
  asm volatile("{.reg .pred p; setp.ne.b32 p, %114, 0;\n"
    "wgmma.mma_async.sync.aligned.m64n224k16.f32.bf16.bf16 {%0,%1,%2,%3,%4,%5,%6,%7,%8,%9,%10,%11,%12,%13,%14,%15,%16,%17,%18,%19,%20,%21,%22,%23,%24,%25,%26,%27,%28,%29,%30,%31,%32,%33,%34,%35,%36,%37,%38,%39,%40,%41,%42,%43,%44,%45,%46,%47,%48,%49,%50,%51,%52,%53,%54,%55,%56,%57,%58,%59,%60,%61,%62,%63,%64,%65,%66,%67,%68,%69,%70,%71,%72,%73,%74,%75,%76,%77,%78,%79,%80,%81,%82,%83,%84,%85,%86,%87,%88,%89,%90,%91,%92,%93,%94,%95,%96,%97,%98,%99,%100,%101,%102,%103,%104,%105,%106,%107,%108,%109,%110,%111}, %112, %113, p, 1, 1, 0, 1;}\n"
    : "+f"(d[0]),"+f"(d[1]),"+f"(d[2]),"+f"(d[3]),"+f"(d[4]),"+f"(d[5]),"+f"(d[6]),"+f"(d[7]),"+f"(d[8]),"+f"(d[9]),"+f"(d[10]),"+f"(d[11]),"+f"(d[12]),"+f"(d[13]),"+f"(d[14]),"+f"(d[15]),"+f"(d[16]),"+f"(d[17]),"+f"(d[18]),"+f"(d[19]),"+f"(d[20]),"+f"(d[21]),"+f"(d[22]),"+f"(d[23]),"+f"(d[24]),"+f"(d[25]),"+f"(d[26]),"+f"(d[27]),"+f"(d[28]),"+f"(d[29]),"+f"(d[30]),"+f"(d[31]),"+f"(d[32]),"+f"(d[33]),"+f"(d[34]),"+f"(d[35]),"+f"(d[36]),"+f"(d[37]),"+f"(d[38]),"+f"(d[39]),"+f"(d[40]),"+f"(d[41]),"+f"(d[42]),"+f"(d[43]),"+f"(d[44]),"+f"(d[45]),"+f"(d[46]),"+f"(d[47]),"+f"(d[48]),"+f"(d[49]),"+f"(d[50]),"+f"(d[51]),"+f"(d[52]),"+f"(d[53]),"+f"(d[54]),"+f"(d[55]),"+f"(d[56]),"+f"(d[57]),"+f"(d[58]),"+f"(d[59]),"+f"(d[60]),"+f"(d[61]),"+f"(d[62]),"+f"(d[63]),"+f"(d[64]),"+f"(d[65]),"+f"(d[66]),"+f"(d[67]),"+f"(d[68]),"+f"(d[69]),"+f"(d[70]),"+f"(d[71]),"+f"(d[72]),"+f"(d[73]),"+f"(d[74]),"+f"(d[75]),"+f"(d[76]),"+f"(d[77]),"+f"(d[78]),"+f"(d[79]),"+f"(d[80]),"+f"(d[81]),"+f"(d[82]),"+f"(d[83]),"+f"(d[84]),"+f"(d[85]),"+f"(d[86]),"+f"(d[87]),"+f"(d[88]),"+f"(d[89]),"+f"(d[90]),"+f"(d[91]),"+f"(d[92]),"+f"(d[93]),"+f"(d[94]),"+f"(d[95]),"+f"(d[96]),"+f"(d[97]),"+f"(d[98]),"+f"(d[99]),"+f"(d[100]),"+f"(d[101]),"+f"(d[102]),"+f"(d[103]),"+f"(d[104]),"+f"(d[105]),"+f"(d[106]),"+f"(d[107]),"+f"(d[108]),"+f"(d[109]),"+f"(d[110]),"+f"(d[111])
    : "l"(da), "l"(db), "r"(acc));
}
__device__ __forceinline__ void mma_ss_56(float (&d)[28], uint64_t da, uint64_t db, int acc) {
  asm volatile("{.reg .pred p; setp.ne.b32 p, %30, 0;\n"
    "wgmma.mma_async.sync.aligned.m64n56k16.f32.bf16.bf16 {%0,%1,%2,%3,%4,%5,%6,%7,%8,%9,%10,%11,%12,%13,%14,%15,%16,%17,%18,%19,%20,%21,%22,%23,%24,%25,%26,%27}, %28, %29, p, 1, 1, 0, 1;}\n"
    : "+f"(d[0]),"+f"(d[1]),"+f"(d[2]),"+f"(d[3]),"+f"(d[4]),"+f"(d[5]),"+f"(d[6]),"+f"(d[7]),"+f"(d[8]),"+f"(d[9]),"+f"(d[10]),"+f"(d[11]),"+f"(d[12]),"+f"(d[13]),"+f"(d[14]),"+f"(d[15]),"+f"(d[16]),"+f"(d[17]),"+f"(d[18]),"+f"(d[19]),"+f"(d[20]),"+f"(d[21]),"+f"(d[22]),"+f"(d[23]),"+f"(d[24]),"+f"(d[25]),"+f"(d[26]),"+f"(d[27])
    : "l"(da), "l"(db), "r"(acc));
}
__device__ __forceinline__ void mma_rs_56(float (&d)[28], uint32_t a0, uint32_t a1, uint32_t a2, uint32_t a3, uint64_t db, int acc) {
  asm volatile("{.reg .pred p; setp.ne.b32 p, %33, 0;\n"
    "wgmma.mma_async.sync.aligned.m64n56k16.f32.bf16.bf16 {%0,%1,%2,%3,%4,%5,%6,%7,%8,%9,%10,%11,%12,%13,%14,%15,%16,%17,%18,%19,%20,%21,%22,%23,%24,%25,%26,%27}, {%28,%29,%30,%31}, %32, p, 1, 1, 1;}\n"
    : "+f"(d[0]),"+f"(d[1]),"+f"(d[2]),"+f"(d[3]),"+f"(d[4]),"+f"(d[5]),"+f"(d[6]),"+f"(d[7]),"+f"(d[8]),"+f"(d[9]),"+f"(d[10]),"+f"(d[11]),"+f"(d[12]),"+f"(d[13]),"+f"(d[14]),"+f"(d[15]),"+f"(d[16]),"+f"(d[17]),"+f"(d[18]),"+f"(d[19]),"+f"(d[20]),"+f"(d[21]),"+f"(d[22]),"+f"(d[23]),"+f"(d[24]),"+f"(d[25]),"+f"(d[26]),"+f"(d[27])
    : "r"(a0), "r"(a1), "r"(a2), "r"(a3), "l"(db), "r"(acc));
}
__device__ __forceinline__ void mma_ss_64t(float (&d)[32], uint64_t da, uint64_t db, int acc) {
  asm volatile("{.reg .pred p; setp.ne.b32 p, %34, 0;\n"
    "wgmma.mma_async.sync.aligned.m64n64k16.f32.bf16.bf16 {%0,%1,%2,%3,%4,%5,%6,%7,%8,%9,%10,%11,%12,%13,%14,%15,%16,%17,%18,%19,%20,%21,%22,%23,%24,%25,%26,%27,%28,%29,%30,%31}, %32, %33, p, 1, 1, 1, 1;}\n"
    : "+f"(d[0]),"+f"(d[1]),"+f"(d[2]),"+f"(d[3]),"+f"(d[4]),"+f"(d[5]),"+f"(d[6]),"+f"(d[7]),"+f"(d[8]),"+f"(d[9]),"+f"(d[10]),"+f"(d[11]),"+f"(d[12]),"+f"(d[13]),"+f"(d[14]),"+f"(d[15]),"+f"(d[16]),"+f"(d[17]),"+f"(d[18]),"+f"(d[19]),"+f"(d[20]),"+f"(d[21]),"+f"(d[22]),"+f"(d[23]),"+f"(d[24]),"+f"(d[25]),"+f"(d[26]),"+f"(d[27]),"+f"(d[28]),"+f"(d[29]),"+f"(d[30]),"+f"(d[31])
    : "l"(da), "l"(db), "r"(acc));
}
__device__ __forceinline__ void mma_rs_64(float (&d)[32], uint32_t a0, uint32_t a1, uint32_t a2, uint32_t a3, uint64_t db, int acc) {
  asm volatile("{.reg .pred p; setp.ne.b32 p, %37, 0;\n"
    "wgmma.mma_async.sync.aligned.m64n64k16.f32.bf16.bf16 {%0,%1,%2,%3,%4,%5,%6,%7,%8,%9,%10,%11,%12,%13,%14,%15,%16,%17,%18,%19,%20,%21,%22,%23,%24,%25,%26,%27,%28,%29,%30,%31}, {%32,%33,%34,%35}, %36, p, 1, 1, 1;}\n"
    : "+f"(d[0]),"+f"(d[1]),"+f"(d[2]),"+f"(d[3]),"+f"(d[4]),"+f"(d[5]),"+f"(d[6]),"+f"(d[7]),"+f"(d[8]),"+f"(d[9]),"+f"(d[10]),"+f"(d[11]),"+f"(d[12]),"+f"(d[13]),"+f"(d[14]),"+f"(d[15]),"+f"(d[16]),"+f"(d[17]),"+f"(d[18]),"+f"(d[19]),"+f"(d[20]),"+f"(d[21]),"+f"(d[22]),"+f"(d[23]),"+f"(d[24]),"+f"(d[25]),"+f"(d[26]),"+f"(d[27]),"+f"(d[28]),"+f"(d[29]),"+f"(d[30]),"+f"(d[31])
    : "r"(a0), "r"(a1), "r"(a2), "r"(a3), "l"(db), "r"(acc));
}

__device__ __forceinline__ void dual_softmax(const float (&p)[28], uint32_t (&phi)[4][7]) {
  constexpr float L2E = 1.4426950408889634f;
#pragma unroll
  for (int i = 0; i < 4; i++) {
    float mx = p[i], mn = p[i];
#pragma unroll
    for (int j = 1; j < 7; j++) { mx = fmaxf(mx, p[4 * j + i]); mn = fminf(mn, p[4 * j + i]); }
    mx = fmaxf(mx, __shfl_xor_sync(~0u, mx, 1)); mn = fminf(mn, __shfl_xor_sync(~0u, mn, 1));
    mx = fmaxf(mx, __shfl_xor_sync(~0u, mx, 2)); mn = fminf(mn, __shfl_xor_sync(~0u, mn, 2));
    float a[7], b[7], sa = 0.f, sb = 0.f;
    const float mxl = mx * L2E, mnl = mn * L2E;
#pragma unroll
    for (int j = 0; j < 7; j++) {
      a[j] = ex2(fmaf(p[4 * j + i], L2E, -mxl)); b[j] = ex2(fmaf(p[4 * j + i], -L2E, mnl));
      sa += a[j]; sb += b[j];
    }
    sa += __shfl_xor_sync(~0u, sa, 1); sb += __shfl_xor_sync(~0u, sb, 1);
    sa += __shfl_xor_sync(~0u, sa, 2); sb += __shfl_xor_sync(~0u, sb, 2);
    const float ra = __fdividef(1.f, sa), rb = __fdividef(1.f, sb);
#pragma unroll
    for (int j = 0; j < 7; j++) phi[i][j] = pack(a[j] * ra, b[j] * rb);
  }
}

struct Ring {
  uint32_t full, empty, base; int slot, par;
  __device__ __forceinline__ void uniform() { slot = __shfl_sync(~0u, slot, 0); par = __shfl_sync(~0u, par, 0); }
  __device__ __forceinline__ uint32_t acquire() { mbar_wait(full + slot * 8, par); return base + slot * SLOT; }
  __device__ __forceinline__ int advance() { int s = slot; if (++slot == NSLOT) { slot = 0; par ^= 1; } return s; }
  __device__ __forceinline__ void release(int s, bool elect) { if (elect) mbar_arrive(empty + s * 8); }
};
constexpr int UNR = 14;
constexpr int FL_KV = 448, FL_CS = FL_KV + 16, FL_DONE = FL_KV + 32;

__global__ void __launch_bounds__(384, 1)
fused_kernel(const __grid_constant__ CUtensorMap mQKV, const __grid_constant__ CUtensorMap mWO,
             const __grid_constant__ CUtensorMap mW1, const __grid_constant__ CUtensorMap mW2,
             const __grid_constant__ CUtensorMap mX, const __nv_bfloat16* __restrict__ wphi,
             const __nv_bfloat16* __restrict__ b1, const __nv_bfloat16* __restrict__ b2,
             const __nv_bfloat16* __restrict__ wqkv, const __nv_bfloat16* __restrict__ wo, const __nv_bfloat16* __restrict__ w1,
             const __nv_bfloat16* __restrict__ w2, __nv_bfloat16* __restrict__ out) {
  extern __shared__ unsigned char smem_raw[];
  const uint32_t sb = (smem_u32(smem_raw) + 1023) & ~1023u;
  unsigned char* sg = smem_raw + (sb - smem_u32(smem_raw));
  const int tid = threadIdx.x, lane = tid & 31;
  const int G = blockIdx.x >> 3, r = blockIdx.x & 7;
  const uint32_t barFull = sb + OFF_BAR, barEmpty = barFull + 56, barA = barEmpty + 56, barCS = barA + 112, barX = barCS + 16;
  const int warp = __shfl_sync(~0u, tid >> 5, 0);
  uint32_t wv[7] = {}, bv = 0;
  if (warp < 8) {
#pragma unroll
    for (int i = 0; i < 7; i++)
      wv[i] = __ldg(reinterpret_cast<const unsigned short*>(wphi) + (56 * r + i * 8 + warp) * 28 + min(lane, 27));
    bv = __ldg(reinterpret_cast<const unsigned short*>(b1) + 224 * r + min(tid, 223));
  }
  if (lane == 0) {
    if (warp >= 10) {
      const int cc = warp - 10;
      mbar_init(barX + cc * 8, 1);
      fence_async_smem();
      mbar_expect(barX + cc * 8, ABYTES);
#pragma unroll 1
      for (int k = 0; k < 7; k++) tma2(sb + cc * ABYTES + k * 8192, &mX, 64 * k, G * 128 + 64 * cc, barX + cc * 8);
    } else if (warp < 7) { mbar_init(barFull + warp * 8, 1); mbar_init(barEmpty + warp * 8, 2); mbar_init(barA + warp * 8, 1); mbar_init(barA + 56 + warp * 8, 1); }
    else if (warp < 9) { mbar_init(barCS + (warp - 7) * 8, 64); if (warp == 7) mbar_init(barX + 16, 1); }
    else
      asm volatile("cp.async.bulk.prefetch.L2.global [%0], %1;" ::"l"((const char*)wqkv + blockIdx.x * 9408), "r"(9408) : "memory");
    asm volatile("fence.mbarrier_init.release.cluster;" ::: "memory");
  }
  if (tid < 192) reinterpret_cast<float*>(sg + OFF_CS)[tid] = 0.f;
  __syncthreads();
  const int wgid = warp >> 2;
  if (wgid == 2) {
    asm volatile("setmaxnreg.dec.sync.aligned.u32 40;");
    if (warp == 8) {
      int slot = 0, par = 1;
#pragma unroll 1
      for (int it = 0; it < 2 * TILES_PER_LAYER; it++) {
        const int i = it >= TILES_PER_LAYER ? it - TILES_PER_LAYER : it;
        mbar_wait(barEmpty + slot * 8, par);
        const uint32_t dst = sb + OFF_RING + slot * SLOT, fb = barFull + slot * 8;
        if (elect_one()) {
          mbar_expect(fb, i < 14 ? 12288 : SLOT);
          if (i < 14) tma3(dst, &mQKV, 56 * r, 32 * i, 0, fb);
          else if (i < 18) tma2(dst, &mWO, 56 * r, 112 * (i - 14), fb);
          else if (i < 32) tma3(dst, &mW1, 0, 32 * (i - 18), 7 * r, fb);
          else tma2(dst, &mW2, 64 * ((i - 32) >> 1), 224 * r + 112 * (i & 1), fb);
        }
        if (++slot == NSLOT) { slot = 0; par ^= 1; }
      }
    } else if (warp == 11) {
      unsigned ep;
      asm volatile("ld.relaxed.gpu.global.u32 %0, [%1];" : "=r"(ep) : "l"(gFlag + FL_DONE * 32) : "memory");
#pragma unroll 1
      for (int layer = 0; layer < 2; layer++) {
        bar_sync<4, 288>();
        if (lane == 0) {
          flag_arrive(gFlag + (FL_KV + layer * 8 + r) * 32);
          flag_wait(gFlag + (FL_KV + layer * 8 + r) * 32, (ep / NCTA + 1) * 16);
          mbar_arrive(barX + 16);
        }
        __syncwarp();
      }
    } else {
      unsigned ep;
      asm volatile("ld.relaxed.gpu.global.u32 %0, [%1];" : "=r"(ep) : "l"(gFlag + FL_DONE * 32) : "memory");
      const int idx = tid - 288;
      ep = (ep / NCTA + 1) * 2;
      if (G == 0) {
#pragma unroll 1
        for (int i = idx; i < 2 * 1280; i += 64) gKV[((i >= 1280) * 7 + r) * 1280 + i] = make_float4(0.f, 0.f, 0.f, 0.f);
        __syncwarp();
        if (lane == 0) flag_arrive(gFlag + (FL_CS + r) * 32);
      }
      mbar_wait(barFull + 48, 0); mbar_wait(barFull + 48, 1);
      if (idx < 2) {
        const char* pf = idx ? (const char*)w2 + blockIdx.x * 12544 : (const char*)wo + blockIdx.x * 3136;
        asm volatile("cp.async.bulk.prefetch.L2.global [%0], %1;" ::"l"(pf), "r"(idx ? 12544 : 3136) : "memory");
      }
      if (lane == 0) flag_wait(gFlag + (FL_CS + r) * 32, ep);
      __syncwarp();
      mbar_arrive(barCS);
#pragma unroll 1
      for (int ps = 0; ps < 4; ps++) {
        const int ch = min(ps * 16 + (idx >> 2), 48), p = ch / 7, k0 = G * 28 + (idx & 3) * 7;
        const uint4* src = ch >= 21 ? reinterpret_cast<const uint4*>(w1 + (size_t)k0 * 1792 + 224 * r) + (ch - 21)
                                    : reinterpret_cast<const uint4*>(wqkv + (size_t)k0 * 1344 + p * 448 + 56 * r) + (ch - 7 * p);
        uint4 cu[7];
#pragma unroll
        for (int i = 0; i < 7; i++) cu[i] = __ldg(src + i * (ch >= 21 ? 224 : 168));
        float s[8] = {};
#pragma unroll
        for (int i = 0; i < 7; i++) { s[0] += lo(cu[i].x); s[1] += hi(cu[i].x); s[2] += lo(cu[i].y); s[3] += hi(cu[i].y); s[4] += lo(cu[i].z); s[5] += hi(cu[i].z); s[6] += lo(cu[i].w); s[7] += hi(cu[i].w); }
#pragma unroll
        for (int i = 0; i < 8; i++) { s[i] += __shfl_xor_sync(~0u, s[i], 1); s[i] += __shfl_xor_sync(~0u, s[i], 2); }
        if ((idx & 3) < 2) gCS[(r * 16 + G) * 104 + (ch + min(p, 3)) * 2 + (idx & 1)] = (idx & 1) ? make_float4(s[4], s[5], s[6], s[7]) : make_float4(s[0], s[1], s[2], s[3]);
      }
      __syncwarp();
      if (lane == 0) { flag_arrive(gFlag + (FL_CS + 8 + r) * 32); flag_wait(gFlag + (FL_CS + 8 + r) * 32, ep * 16); }
      __syncwarp();
#pragma unroll 1
      for (int j = idx; j < 208; j += 64) {
        float2 a = make_float2(0.f, 0.f);
#pragma unroll 8
        for (int i = 0; i < 16; i++) { const float2 v = __ldcg(reinterpret_cast<const float2*>(gCS + (r * 16 + i) * 104) + j); a.x += v.x; a.y += v.y; }
        reinterpret_cast<float2*>(sg + OFF_CS)[j] = a;
      }
      mbar_arrive(barCS + 8);
    }
  } else {
  asm volatile("setmaxnreg.inc.sync.aligned.u32 232;");
  const int c = wgid, w = warp & 3, g = lane >> 2, t = lane & 3;
  int elect_i = (tid & 127) == 0;
  asm volatile("" : "+r"(elect_i));
  const bool elect = elect_i;
  const uint32_t abuf = sb + c * ABYTES, barAc = barA + c * 56;
  const int row0 = G * 128 + c * 64;
  unsigned epoch;
  asm volatile("ld.relaxed.gpu.global.u32 %0, [%1];" : "=r"(epoch) : "l"(gFlag + FL_DONE * 32) : "memory");
  STAMP(24);
  float mean[2], rstd[2] = {0.f, 0.f};
  uint4 su[2] = {};
  uint32_t xs[7][2];
  {
#pragma unroll
    for (int i = 0; i < 8; i++) {
      const int k = i * 8 + (tid >> 5);
      *reinterpret_cast<uint32_t*>(sg + OFF_WPHI + k * 128 + ((g ^ (k & 7)) << 4) + t * 4) = (i < 7 && lane < 28) ? wv[i % 7] << (k >= 28 ? 16 : 0) : 0u;
    }
    if (tid < 224) reinterpret_cast<uint32_t*>(sg + OFF_B1)[tid] = bv << 16;
    mbar_wait(barX + c * 8, 0);
    STAMP(25);
#pragma unroll
    for (int j = 0; j < 7; j++) {
      const int ci = 7 * r + j;
      const uint32_t a = abuf + (ci >> 3) * 8192 + (w * 16 + g) * 128 + (((ci & 7) ^ g) << 4) + t * 4;
      xs[j][0] = lds32(a); xs[j][1] = lds32(a + 1024);
    }
    __syncwarp();
#pragma unroll 1
    for (int hh = 0; hh < 2; hh++) {
      uint4* p = reinterpret_cast<uint4*>(sg + c * ABYTES + (w * 16 + hh * 8 + g) * 128) + t;
      uint4 v[14];
#pragma unroll
      for (int k = 0; k < 14; k++) v[k] = p[(k >> 1) * 512 + ((k ^ g) & 1) * 4];
      float a8[8] = {};
#pragma unroll
      for (int k = 0; k < 14; k++) {
        const uint32_t e[4] = {v[k].x, v[k].y, v[k].z, v[k].w};
#pragma unroll
        for (int z = 0; z < 4; z++) { a8[2 * z] += lo(e[z]); a8[2 * z + 1] += hi(e[z]); }
      }
      float sm = ((a8[0] + a8[1]) + (a8[2] + a8[3])) + ((a8[4] + a8[5]) + (a8[6] + a8[7]));
      sm += __shfl_xor_sync(~0u, sm, 1); sm += __shfl_xor_sync(~0u, sm, 2);
      sm *= 1.f / DM;
#pragma unroll
      for (int k = 0; k < 14; k++) {
        uint32_t e[4] = {v[k].x, v[k].y, v[k].z, v[k].w};
#pragma unroll
        for (int z = 0; z < 4; z++) {
          const float a = lo(e[z]) - sm, b = hi(e[z]) - sm;
          a8[2 * z] = fmaf(a, a, k ? a8[2 * z] : 0.f); a8[2 * z + 1] = fmaf(b, b, k ? a8[2 * z + 1] : 0.f);
          e[z] = pack(a, b);
        }
        p[(k >> 1) * 512 + ((k ^ g) & 1) * 4] = make_uint4(e[0], e[1], e[2], e[3]);
      }
      float q = ((a8[0] + a8[1]) + (a8[2] + a8[3])) + ((a8[4] + a8[5]) + (a8[6] + a8[7]));
      q += __shfl_xor_sync(~0u, q, 1); q += __shfl_xor_sync(~0u, q, 2);
      rstd[1] = rsqrtf(q * (1.f / DM) + 1e-5f);
      if (hh == 0) rstd[0] = rstd[1];
    }
    fence_async_smem();
    bar_sync<3, 256>();
    epoch = epoch / NCTA + 1;
    mean[0] = mean[1] = 0.f;
  }
  STAMP(0);
  Ring ring{barFull, barEmpty, sb + OFF_RING, 0, 0};
  int apar = 1;
  const uint32_t stsm_off = (w * 16 + ((lane >> 3) & 1) * 8 + (lane & 7)) * 128;
  const uint32_t stsm_hi = lane >> 4;
  const uint64_t dA = mkdesc(abuf, 1024, 128, 0);

  auto gather = [&](unsigned* fl, const unsigned char* img) {
    bar_wg(c);
    if (w == 0) {
      if (elect_one()) {
        flag_arrive(fl);
        flag_wait(fl, epoch * 8);
        fence_async();
#pragma unroll
        for (int k = 0; k < 7; k++) { mbar_expect(barAc + k * 8, 8192); bulk_ld(abuf + k * 8192, img + k * 8192, 8192, barAc + k * 8); }
      }
      __syncwarp();
    }
    apar ^= 1;
  };
  auto slice_off = [&](int j, int hh) -> uint32_t {
    return (7 * r + j) * 1024 + (w * 2 + hh) * 128 + lane * 4;
  };
  auto load_stats = [&](const float2* st) {
    mbar_wait(barAc, apar);
#pragma unroll
    for (int hh = 0; hh < 2; hh++) su[hh] = ldcg4(st + (size_t)(row0 + w * 16 + hh * 8 + g) * 8 + 2 * t);
  };
  auto finish_stats = [&]() {
#pragma unroll
    for (int hh = 0; hh < 2; hh++) {
      const float m0 = __uint_as_float(su[hh].x), m1 = __uint_as_float(su[hh].z);
      float m = m0 + m1;
      m += __shfl_xor_sync(~0u, m, 1); m += __shfl_xor_sync(~0u, m, 2);
      m *= 0.125f;
      float q = __uint_as_float(su[hh].y) + __uint_as_float(su[hh].w) + 56.f * ((m0 - m) * (m0 - m) + (m1 - m) * (m1 - m));
      q += __shfl_xor_sync(~0u, q, 1); q += __shfl_xor_sync(~0u, q, 2);
      mean[hh] = m; rstd[hh] = rsqrtf(q * (1.f / DM) + 1e-5f);
    }
  };

#pragma unroll 1
  for (int lyr = 0; lyr < 2; lyr++) {
    const int layer = __shfl_sync(~0u, lyr, 0);
    unsigned* const fl = gFlag + (layer * 32 + G * 2 + c) * 7 * 32;
    uint32_t phiq[4][7];
    {
      float acc[92]; reg_def(acc);
      int prev = 0, prev2 = 0;
      ring.uniform();
      const uint64_t dQ = layer ? dA : mkdesc(abuf, 16, 1024, 1);
      const int kstep = layer ? 128 : 2;
      if (layer) load_stats(gStat + 2048 * 8);
#pragma unroll UNR
      for (int st = 0; st < 14; st++) {
        if (!(st & 1) && layer) mbar_wait(barAc + (st >> 1) * 8, apar);
        const uint64_t da = dQ + (st >> 1) * 512 + (st & 1) * 2 * kstep, db = mkdesc(ring.acquire(), 4096, 1024, 1);
        wg_fence();
        mma_ss_184(acc, da, db, 1);
        mma_ss_184(acc, da + kstep, db + 128, 1);
        wg_commit();
        if (st > 1) { wg_wait<2>(); ring.release(prev2, elect); }
        prev2 = prev; prev = ring.advance();
      }
      if (layer) {
        finish_stats();
#pragma unroll
        for (int j = 0; j < 7; j++) { xs[j][0] = lds32(abuf + slice_off(j, 0)); xs[j][1] = lds32(abuf + slice_off(j, 1)); }
      }
      wg_wait<0>(); reg_fence(acc);
      ring.release(prev2, elect); ring.release(prev, elect);
      STAMP(1 + layer * 12);
      uint32_t f[3][14];
      auto frags = [&](const int p0, const int p1) {
        const float2* cs = reinterpret_cast<const float2*>(sg + OFF_CS) + t;
        const float mr0 = -mean[0] * rstd[0], mr1 = -mean[1] * rstd[1];
#pragma unroll
        for (int p = p0; p < p1; p++)
#pragma unroll
          for (int j = 0; j < 7; j++) {
            const float2 s = cs[p * 32 + j * 4];
            const int b = p * 32 + j * 4;
            f[p][2 * j] = pack(fmaf(acc[b], rstd[0], s.x * mr0), fmaf(acc[b + 1], rstd[0], s.y * mr0));
            f[p][2 * j + 1] = pack(fmaf(acc[b + 2], rstd[1], s.x * mr1), fmaf(acc[b + 3], rstd[1], s.y * mr1));
          }
      };
      frags(1, 2);
      float pk[28]; reg_def(pk);
      const uint64_t dW = mkdesc(sb + OFF_WPHI, 4096, 1024, 1);
      wg_fence();
#pragma unroll
      for (int s = 0; s < 4; s++) {
        mma_rs_56(pk, f[1][4 * s], f[1][4 * s + 1], s < 3 ? f[1][(4 * s + 2) % 14] : 0u, s < 3 ? f[1][(4 * s + 3) % 14] : 0u, dW + s * 128, s);
      }
      wg_commit();
      frags(2, 3);
      bar_wg(c);
      const uint32_t srow = abuf + stsm_off, ones = t == 0 ? 0x3F803F80u : 0u;
#pragma unroll
      for (int jp = 0; jp < 4; jp++)
        stsm4(srow + 16384 + (((2 * jp + stsm_hi) ^ (lane & 7)) << 4), f[2][4 * jp], f[2][4 * jp + 1],
              jp < 3 ? f[2][(4 * jp + 2) % 14] : ones, jp < 3 ? f[2][(4 * jp + 3) % 14] : ones);
      wg_wait<0>(); reg_fence(pk);
      {
        dual_softmax(pk, phiq);
#pragma unroll
        for (int e = 0; e < 2; e++)
#pragma unroll
          for (int jp = 0; jp < 4; jp++)
            stsm4(srow + e * 8192 + (((2 * jp + stsm_hi) ^ (lane & 7)) << 4), phiq[e][2 * jp], phiq[2 + e][2 * jp],
                  jp < 3 ? phiq[e][(2 * jp + 1) % 7] : 0u, jp < 3 ? phiq[2 + e][(2 * jp + 1) % 7] : 0u);
        fence_async_smem();
        bar_sync<3, 256>();
        float kv[32], kw[32]; reg_def(kv); reg_def(kw);
        const uint64_t dP = mkdesc(sb + c * 8192, 4096, 1024, 1), dV = mkdesc(sb + 16384, 4096, 1024, 1);
        wg_fence();
#pragma unroll
        for (int s = 0; s < 4; s++) { mma_ss_64t(kv, dP + s * 128, dV + s * 128, s); mma_ss_64t(kw, dP + ABYTES / 16 + s * 128, dV + ABYTES / 16 + s * 128, s); }
        wg_commit();
        mbar_wait(barCS, 0);
        wg_wait<0>(); reg_fence(kv); reg_fence(kw);
#pragma unroll
        for (int i = 0; i < 32; i++) kv[i] += kw[i];
        float4* kvg = gKV + ((layer * 8 + r) * 2 + c) * 640 + (tid & 127);
#pragma unroll
        for (int i = 0; i < 5; i++) {
          float v0, v1, v2, v3;
          if (i == 4) { v0 = kv[28]; v1 = kv[29]; v2 = kv[30]; v3 = kv[31]; }
          else { v0 = c ? kv[12 + 4 * i] : kv[4 * i]; v1 = c ? kv[13 + 4 * i] : kv[1 + 4 * i]; v2 = c ? kv[14 + 4 * i] : kv[2 + 4 * i]; v3 = c ? kv[15 + 4 * i] : kv[3 + 4 * i]; }
          const bool use = i == 4 ? t == 0 : (i == 0 ? (c == 0 || t >= 2) : (i == 3 ? (c == 1 || t < 2) : true));
          if (use) asm volatile("red.relaxed.gpu.global.add.v4.f32 [%0], {%1,%2,%3,%4};" ::"l"(kvg + i * 128), "f"(v0), "f"(v1), "f"(v2), "f"(v3) : "memory");
        }
        asm volatile("bar.arrive 4, 288;" ::: "memory");
        STAMP(2 + layer * 12);
      }
      frags(0, 1);
      float pq[28]; reg_def(pq);
      wg_fence();
#pragma unroll
      for (int s = 0; s < 4; s++)
        mma_rs_56(pq, f[0][4 * s], f[0][4 * s + 1], s < 3 ? f[0][(4 * s + 2) % 14] : 0u, s < 3 ? f[0][(4 * s + 3) % 14] : 0u, dW + s * 128, s);
      wg_commit();
      wg_wait<0>(); reg_fence(pq);
      dual_softmax(pq, phiq);
    }
    {
      mbar_wait(barX + 16, layer);
      STAMP(3 + layer * 12);
      const float4* kvg = gKV + (layer * 8 + r) * 1280 + c * 640 + (tid & 127);
      uint4 kk[5];
#pragma unroll
      for (int i = 0; i < 5; i++) kk[i] = ldcg4(kvg + i * 128);
      uint32_t f[5][2];
#pragma unroll
      for (int i = 0; i < 5; i++) { f[i][0] = pack(__uint_as_float(kk[i].x), __uint_as_float(kk[i].y)); f[i][1] = pack(__uint_as_float(kk[i].z), __uint_as_float(kk[i].w)); }
      const uint32_t zm = c ? 0xFFFF0000u : 0xFFFFu;
      const uint32_t srow = abuf + 24576 + stsm_off;
#pragma unroll
      for (int jp = 0; jp < 4; jp++) {
        uint32_t v[2][2];
#pragma unroll
        for (int u = 0; u < 2; u++) {
          const int j = 2 * jp + u;
#pragma unroll
          for (int hh = 0; hh < 2; hh++) v[u][hh] = j == 7 ? f[4][hh] & zm : (c ? (j >= 3 ? f[(j + 2) % 5][hh] : 0u) : (j < 4 ? f[j % 5][hh] : 0u));
        }
        stsm4(srow + (((2 * jp + stsm_hi) ^ (lane & 7)) << 4), v[0][0], v[0][1], v[1][0], v[1][1]);
      }
      fence_async_smem();
      bar_sync<3, 256>();
      float num[32], nub[32]; reg_def(num); reg_def(nub);
      const uint64_t dK = mkdesc(sb + 24576, 4096, 1024, 1);
      wg_fence();
#pragma unroll
      for (int s = 0; s < 4; s++) {
        mma_rs_64(num, phiq[0][2 * s], phiq[2][2 * s], s < 3 ? phiq[0][(2 * s + 1) % 7] : 0u, s < 3 ? phiq[2][(2 * s + 1) % 7] : 0u, dK + s * 128, s);
        mma_rs_64(nub, phiq[1][2 * s], phiq[3][2 * s], s < 3 ? phiq[1][(2 * s + 1) % 7] : 0u, s < 3 ? phiq[3][(2 * s + 1) % 7] : 0u, dK + ABYTES / 16 + s * 128, s);
      }
      wg_commit();
      wg_wait<0>(); reg_fence(num); reg_fence(nub);
      bar_sync<3, 256>();
#pragma unroll
      for (int i = 12; i < 32; i++) num[i] += nub[i];
      float rd[4];
#pragma unroll
      for (int i = 0; i < 4; i++) rd[i] = __fdividef(1.f, __shfl_sync(~0u, num[28 + i], lane & ~3) + 1e-6f);
      unsigned char* img = gImg + (size_t)(G * 2 + c) * ABYTES;
#pragma unroll
      for (int j = 0; j < 7; j++) {
        const bool hb = j > 3 || (j == 3 && t >= 2);
        const float r0 = hb ? rd[1] : rd[0], r1 = hb ? rd[3] : rd[2];
        *reinterpret_cast<uint32_t*>(img + slice_off(j, 0)) = pack(num[4 * j] * r0, num[4 * j + 1] * r0);
        *reinterpret_cast<uint32_t*>(img + slice_off(j, 1)) = pack(num[4 * j + 2] * r1, num[4 * j + 3] * r1);
      }
      STAMP(4 + layer * 12);
      gather(fl, img);
      STAMP(5 + layer * 12);
    }
    {
      float acc[28], acc2[28]; reg_def(acc); reg_def(acc2); reg_fence(acc); reg_fence(acc2);
      int sl[4];
      ring.uniform();
#pragma unroll
      for (int st = 0; st < 4; st++) {
        const uint64_t db = mkdesc(ring.acquire(), 4096, 1024, 1);
        sl[st] = ring.advance();
#pragma unroll
        for (int s = 0; s < 7; s++) {
          const int ks = st * 7 + s;
          if (!(ks & 3)) mbar_wait(barAc + (ks >> 2) * 8, apar);
          if (!(ks & 3) || !s) wg_fence();
          if (ks & 1) mma_ss_56(acc2, dA + ks * 128, db + s * 128, ks > 1); else mma_ss_56(acc, dA + ks * 128, db + s * 128, ks > 1);
        }
        wg_commit();
      }
      wg_wait<0>(); reg_fence(acc); reg_fence(acc2);
      unsigned char* img = gImg + (size_t)(32 + G * 2 + c) * ABYTES;
#pragma unroll
      for (int hh = 0; hh < 2; hh++) {
        float s = 0.f, q = 0.f;
#pragma unroll
        for (int j = 0; j < 7; j++) {
          xs[j][hh] = pack(lo(xs[j][hh]) + (acc[4 * j + 2 * hh] + acc2[4 * j + 2 * hh]), hi(xs[j][hh]) + (acc[4 * j + 2 * hh + 1] + acc2[4 * j + 2 * hh + 1]));
          *reinterpret_cast<uint32_t*>(img + slice_off(j, hh)) = xs[j][hh];
          s += lo(xs[j][hh]) + hi(xs[j][hh]);
        }
        s += __shfl_xor_sync(~0u, s, 1); s += __shfl_xor_sync(~0u, s, 2);
        s *= 1.f / 56.f;
#pragma unroll
        for (int j = 0; j < 7; j++) { const float a = lo(xs[j][hh]) - s, b = hi(xs[j][hh]) - s; q = fmaf(a, a, q); q = fmaf(b, b, q); }
        q += __shfl_xor_sync(~0u, q, 1); q += __shfl_xor_sync(~0u, q, 2);
        if (t == 0) gStat[(size_t)(row0 + w * 16 + hh * 8 + g) * 8 + r] = make_float2(s, q);
      }
#pragma unroll
      for (int j = 0; j < 7; j++) xs[j][0] = xs[j][1] = 0u;
      STAMP(6 + layer * 12);
      gather(fl + 32, img);
#pragma unroll
      for (int st = 0; st < 4; st++) ring.release(sl[st], elect);
      STAMP(7 + layer * 12);
    }
    {
      uint32_t hf[28][2];
      {
        float acc[112]; reg_def(acc);
        int prev = 0, prev2 = 0;
        load_stats(gStat);
        ring.uniform();
#pragma unroll UNR
        for (int st = 0; st < 14; st++) {
          if (!(st & 1)) mbar_wait(barAc + (st >> 1) * 8, apar);
          const uint64_t da = dA + st * 256, db = mkdesc(ring.acquire(), 2048, 512, 2);
          wg_fence();
          mma_ss_224(acc, da, db, 1);
          mma_ss_224(acc, da + 128, db + 64, 1);
          wg_commit();
          if (st > 1) { wg_wait<2>(); ring.release(prev2, elect); }
          prev2 = prev; prev = ring.advance();
        }
        finish_stats();
        mbar_wait(barCS + 8, 0);
        wg_wait<0>(); reg_fence(acc);
        ring.release(prev2, elect); ring.release(prev, elect);
        STAMP(8 + layer * 12);
        const float2* bs = reinterpret_cast<const float2*>(sg + OFF_B1) + t;
        const float2* cs = reinterpret_cast<const float2*>(sg + OFF_CS + 768) + t;
        const float mr0 = -mean[0] * rstd[0], mr1 = -mean[1] * rstd[1];
#pragma unroll
        for (int j = 0; j < 28; j++) {
          const float2 b = bs[4 * j], s = cs[4 * j];
          hf[j][0] = relu_sq(fmaf(acc[4 * j], rstd[0], fmaf(s.x, mr0, b.x)), fmaf(acc[4 * j + 1], rstd[0], fmaf(s.y, mr0, b.y)));
          hf[j][1] = relu_sq(fmaf(acc[4 * j + 2], rstd[1], fmaf(s.x, mr1, b.x)), fmaf(acc[4 * j + 3], rstd[1], fmaf(s.y, mr1, b.y)));
        }
      }
      unsigned char* pd[2]; int pstr[2];
#pragma unroll
      for (int hh = 0; hh < 2; hh++) {
        const bool own = 2 * w + hh == r;
        pd[hh] = own ? sg + c * ABYTES + (lane >> 4) * 1024 + (r ^ 1) * 128 + (lane & 15) * 8
                     : gP + (size_t)(((G * 2 + c) * 8 + 2 * w + hh) * 8 + r) * 7168 + lane * 8;
        pstr[hh] = own ? 2048 : 256;
      }
      uint2 pk[8] = {};
      ring.uniform();
#pragma unroll 1
      for (int ch = 0; ch < 7; ch++) {
        float acc[32], acc2[32]; reg_def(acc); reg_def(acc2);
        const uint64_t db0 = mkdesc(ring.acquire(), 4096, 1024, 1);
        const int sl0 = ring.advance();
        const uint64_t db1 = mkdesc(ring.acquire(), 4096, 1024, 1);
        const int sl1 = ring.advance();
        wg_fence();
#pragma unroll
        for (int s = 0; s < 7; s++) {
          mma_rs_64(acc, hf[2 * s][0], hf[2 * s][1], hf[2 * s + 1][0], hf[2 * s + 1][1], db0 + s * 128, s);
          mma_rs_64(acc2, hf[14 + 2 * s][0], hf[14 + 2 * s][1], hf[15 + 2 * s][0], hf[15 + 2 * s][1], db1 + s * 128, s);
        }
        wg_commit();
        if (ch > 0) {
#pragma unroll
          for (int i = 0; i < 8; i++) { *reinterpret_cast<uint2*>(pd[i & 1]) = pk[i]; pd[i & 1] += pstr[i & 1]; }
        }
        wg_wait<0>(); reg_fence(acc); reg_fence(acc2); ring.release(sl0, elect && ch < 5); ring.release(sl1, elect && ch < 5);
#pragma unroll
        for (int i = 0; i < 8; i++) {
          const int b = (i >> 1) * 8 + (i & 1) * 2;
          pk[i] = make_uint2((pack(acc[b] + acc2[b], acc[b + 1] + acc2[b + 1]) & ~1u) | (layer ^ 1), pack(acc[b + 4] + acc2[b + 4], acc[b + 5] + acc2[b + 5]));
        }
      }
#pragma unroll
      for (int i = 0; i < 8; i++) { *reinterpret_cast<uint2*>(pd[i & 1]) = pk[i]; pd[i & 1] += pstr[i & 1]; }
      STAMP(9 + layer * 12);
    }
    {
      uint32_t bx[14];
#pragma unroll
      for (int j = 0; j < 14; j++) bx[j] = __ldg(reinterpret_cast<const uint32_t*>(b2 + (j >> 1) * 64 + w * 16 + (j & 1) * 8 + 2 * t));
      const unsigned char* psrc = gP + (size_t)(((G * 2 + c) * 8 + r) * 8) * 7168 + w * 256 + lane * 8;
      unsigned char* img = gImg + (size_t)(64 + G * 2 + c) * ABYTES;
      uint2 pv[7][7];
      const unsigned char* ps[7];
#pragma unroll
      for (int s = 0; s < 7; s++) ps[s] = psrc + ((r + 1 + s) & 7) * 7168;
#pragma unroll
      for (int i = 0; i < 5; i++)
#pragma unroll
        for (int s = 0; s < 7; s++) pv[s][i] = ldcg2(ps[s] + i * 1024);
      bar_wg(c);
      const uint32_t off = w * 2048 + r * 128 + lane * 4;
      unsigned char* dst = layer ? reinterpret_cast<unsigned char*>(out + (size_t)(row0 + r * 8 + g) * DM + w * 16 + 4 * t) : img + off;
      float sm = 0.f, q = 0.f;
#pragma unroll
      for (int i = 0; i < 7; i++) {
        const uint2 own = *reinterpret_cast<const uint2*>(sg + c * ABYTES + i * 8192 + w * 2048 + (lane >> 4) * 1024 + (r ^ 1) * 128 + (lane & 15) * 8);
#pragma unroll 1
        for (int n = 0; n < (1 << 16); n++) {
          const uint32_t all = pv[0][i].x & pv[1][i].x & pv[2][i].x & pv[3][i].x & pv[4][i].x & pv[5][i].x & pv[6][i].x;
          const uint32_t any = pv[0][i].x | pv[1][i].x | pv[2][i].x | pv[3][i].x | pv[4][i].x | pv[5][i].x | pv[6][i].x;
          if (!__any_sync(~0u, (layer ? any : ~all) & 1u)) break;
#pragma unroll
          for (int s = 0; s < 7; s++) pv[s][i] = ldcg2(ps[s] + i * 1024);
        }
        if (i < 2) {
#pragma unroll
          for (int s = 0; s < 7; s++) pv[s][5 + (i & 1)] = ldcg2(ps[s] + (5 + i) * 1024);
        }
#pragma unroll
        for (int jj = 0; jj < 2; jj++) {
          const int j = 2 * i + jj;
          const uint32_t xo = lds32(abuf + off + i * 8192 + jj * 1024), uo = jj ? own.y : own.x;
          float y0 = lo(bx[j]) + lo(xo) + lo(uo), y1 = hi(bx[j]) + hi(xo) + hi(uo);
#pragma unroll
          for (int s = 0; s < 7; s++) { const uint32_t u = jj ? pv[s][i].y : pv[s][i].x; y0 += lo(u); y1 += hi(u); }
          bx[j] = pack(y0, y1);
          if (!layer) *reinterpret_cast<uint32_t*>(dst + (i * 8 + jj) * 1024) = bx[j];
          sm += lo(bx[j]) + hi(bx[j]);
        }
        if (layer) {
          const int sl = (lane & ~3) | ((t & 1) << 1);
          const uint32_t a0 = __shfl_sync(~0u, bx[2 * i], sl), a1 = __shfl_sync(~0u, bx[2 * i], sl + 1);
          const uint32_t b0 = __shfl_sync(~0u, bx[2 * i + 1], sl), b1v = __shfl_sync(~0u, bx[2 * i + 1], sl + 1);
          *reinterpret_cast<uint2*>(dst + i * 128) = t < 2 ? make_uint2(a0, a1) : make_uint2(b0, b1v);
        }
      }
      if (layer) break;
      sm += __shfl_xor_sync(~0u, sm, 1); sm += __shfl_xor_sync(~0u, sm, 2);
      sm *= 1.f / 112.f;
#pragma unroll
      for (int j = 0; j < 14; j++) { const float a = lo(bx[j]) - sm, b = hi(bx[j]) - sm; q = fmaf(a, a, q); q = fmaf(b, b, q); }
      q += __shfl_xor_sync(~0u, q, 1); q += __shfl_xor_sync(~0u, q, 2);
      if (t < 2) gStat[(size_t)(2048 + row0 + r * 8 + g) * 8 + 2 * w + t] = make_float2(sm, q * 0.5f);
      STAMP(11);
      gather(fl + 64, img);
#pragma unroll
      for (int i = 3; i < 7; i++) ring.release((ring.slot + i) % NSLOT, elect);
      STAMP(12);
    }
  }
  STAMP(30);
  if (tid == 0) asm volatile("red.relaxed.gpu.global.add.u32 [%0], 1;" ::"l"(gFlag + FL_DONE * 32) : "memory");
  }
}

typedef CUresult (*EncFn)(CUtensorMap*, CUtensorMapDataType, cuuint32_t, void*, const cuuint64_t*, const cuuint64_t*,
                          const cuuint32_t*, const cuuint32_t*, CUtensorMapInterleave, CUtensorMapSwizzle,
                          CUtensorMapL2promotion, CUtensorMapFloatOOBfill);

void make_map(EncFn enc, CUtensorMap* m, void* p, int rank, uint64_t d0, uint64_t d1, uint64_t d2, uint64_t s1, uint64_t s2,
              uint32_t b0, uint32_t b1, uint32_t b2, CUtensorMapSwizzle sw) {
  cuuint64_t dims[3] = {d0, d1, d2}, strides[2] = {s1, s2};
  cuuint32_t box[3] = {b0, b1, b2}, es[3] = {1, 1, 1};
  enc(m, CU_TENSOR_MAP_DATA_TYPE_BFLOAT16, rank, p, dims, strides, box, es, CU_TENSOR_MAP_INTERLEAVE_NONE, sw,
      CU_TENSOR_MAP_L2_PROMOTION_L2_128B, CU_TENSOR_MAP_FLOAT_OOB_FILL_NONE);
}

}

extern "C" void kernel_launch(void* const* d_in, const int* in_sizes, int n_in, void* d_out, int out_size) {
  static EncFn enc = nullptr;
  if (!enc) {
    cudaDriverEntryPointQueryResult st;
    void* fn = nullptr;
    cudaGetDriverEntryPoint("cuTensorMapEncodeTiled", &fn, cudaEnableDefault, &st);
    enc = (EncFn)fn;
    cudaFuncSetAttribute(fused_kernel, cudaFuncAttributeMaxDynamicSharedMemorySize, SMEM_BYTES);
  }
  CUtensorMap mQKV, mWO, mW1, mW2, mX;
  make_map(enc, &mX, d_in[0], 2, 448, 2048, 1, 896, 0, 64, 64, 1, CU_TENSOR_MAP_SWIZZLE_128B);
  make_map(enc, &mQKV, d_in[1], 3, 448, 448, 3, 2688, 896, 64, 32, 3, CU_TENSOR_MAP_SWIZZLE_128B);
  make_map(enc, &mWO, d_in[3], 2, 448, 448, 1, 896, 0, 64, 112, 1, CU_TENSOR_MAP_SWIZZLE_128B);
  make_map(enc, &mW1, d_in[5], 3, 32, 448, 56, 3584, 64, 32, 32, 7, CU_TENSOR_MAP_SWIZZLE_64B);
  make_map(enc, &mW2, d_in[7], 2, 448, 1792, 1, 896, 0, 64, 112, 1, CU_TENSOR_MAP_SWIZZLE_128B);
  fused_kernel<<<NCTA, 384, SMEM_BYTES, cudaStreamPerThread>>>(
      mQKV, mWO, mW1, mW2, mX, (const __nv_bfloat16*)d_in[2], (const __nv_bfloat16*)d_in[6],
      (const __nv_bfloat16*)d_in[8], (const __nv_bfloat16*)d_in[1], (const __nv_bfloat16*)d_in[3], (const __nv_bfloat16*)d_in[5],
      (const __nv_bfloat16*)d_in[7], (__nv_bfloat16*)d_out);
}
```

```cpp
#include <cuda_runtime.h>
#include <cuda_bf16.h>
#include <cuda.h>
#include <stdint.h>

namespace {

constexpr int DM = 448, NCTA = 128;
constexpr int ABYTES = 57344;
constexpr int SLOT = 14336, NSLOT = 7;
constexpr int OFF_RING = 2 * ABYTES;
constexpr int OFF_WPHI = OFF_RING + NSLOT * SLOT;
constexpr int OFF_B1 = OFF_WPHI + 8192;
constexpr int OFF_CS = OFF_B1 + 896;
constexpr int OFF_BAR = OFF_CS + 1664;
constexpr int SMEM_BYTES = OFF_BAR + 272 + 1024;
constexpr int TILES_PER_LAYER = 46;

__device__ __align__(1024) unsigned char gP[16 * 2 * 8 * 8 * 7168];
__device__ __align__(1024) unsigned char gImg[3 * 32 * ABYTES];
__device__ __align__(1024) float2 gStat[2 * 2048 * 8];
__device__ __align__(1024) float4 gKV[2 * 8 * 2 * 5 * 128];
__device__ __align__(1024) float4 gCS[8 * 16 * 104];
__device__ __align__(128) unsigned gFlag[(2 * 32 * 7 + 32 + 1 + 16) * 32];
#define STAMP(i)

__device__ __forceinline__ uint32_t smem_u32(const void* p) { return (uint32_t)__cvta_generic_to_shared(p); }
__device__ __forceinline__ void mbar_init(uint32_t b, int c) { asm volatile("mbarrier.init.shared::cta.b64 [%0], %1;" ::"r"(b), "r"(c)); }
__device__ __forceinline__ void mbar_expect(uint32_t b, int bytes) { asm volatile("mbarrier.arrive.expect_tx.shared::cta.b64 _, [%0], %1;" ::"r"(b), "r"(bytes) : "memory"); }
__device__ __forceinline__ void mbar_arrive(uint32_t b) { asm volatile("mbarrier.arrive.shared::cta.b64 _, [%0];" ::"r"(b) : "memory"); }
__device__ __forceinline__ void mbar_wait(uint32_t b, int par) {
  uint32_t ok; int n = 0;
#pragma unroll 1
  while (true) {
    asm volatile("{.reg .pred p; mbarrier.try_wait.parity.shared::cta.b64 p, [%1], %2; selp.u32 %0,1,0,p;}" : "=r"(ok) : "r"(b), "r"(par) : "memory");
    if (ok) break;
    if (++n > (1 << 22)) break;
  }
}
__device__ __forceinline__ void flag_wait(const unsigned* f, unsigned target) {
  unsigned v; int n = 0;
#pragma unroll 1
  while (true) {
    asm volatile("ld.acquire.gpu.global.u32 %0, [%1];" : "=r"(v) : "l"(f) : "memory");
    if ((int)(v - target) >= 0) break;
    if (++n > (1 << 21)) break;
  }
}
__device__ __forceinline__ void flag_arrive(unsigned* f) { asm volatile("red.release.gpu.global.add.u32 [%0], 1;" ::"l"(f) : "memory"); }
__device__ __forceinline__ bool elect_one() {
  uint32_t p; asm volatile("{.reg .pred P; elect.sync _|P, 0xffffffff; selp.u32 %0, 1, 0, P;}" : "=r"(p)); return p;
}
__device__ __forceinline__ void fence_async() { asm volatile("fence.proxy.async.global;" ::: "memory"); }
__device__ __forceinline__ void fence_async_smem() { asm volatile("fence.proxy.async.shared::cta;" ::: "memory"); }
template <int ID, int N> __device__ __forceinline__ void bar_sync() { asm volatile("bar.sync %0, %1;" ::"n"(ID), "n"(N) : "memory"); }
__device__ __forceinline__ void bar_wg(int c) { if (c) bar_sync<2, 128>(); else bar_sync<1, 128>(); }
__device__ __forceinline__ void wg_fence() { asm volatile("wgmma.fence.sync.aligned;" ::: "memory"); }
__device__ __forceinline__ void wg_commit() { asm volatile("wgmma.commit_group.sync.aligned;" ::: "memory"); }
template <int N> __device__ __forceinline__ void wg_wait() { asm volatile("wgmma.wait_group.sync.aligned %0;" ::"n"(N) : "memory"); }
template <int N> __device__ __forceinline__ void reg_fence(float (&d)[N]) {
#pragma unroll
  for (int i = 0; i < N; i++) asm volatile("" : "+f"(d[i])::"memory");
}
template <int N> __device__ __forceinline__ void reg_def(float (&d)[N]) {
#pragma unroll
  for (int i = 0; i < N; i++) d[i] = 0.f;
}
__device__ __forceinline__ uint64_t mkdesc(uint32_t addr, uint32_t lbo, uint32_t sbo, uint64_t swz) {
  return (uint64_t)((addr & 0x3FFFF) >> 4) | ((uint64_t)(lbo >> 4) << 16) | ((uint64_t)(sbo >> 4) << 32) | (swz << 62);
}
__device__ __forceinline__ uint32_t pack(float a, float b) {
  uint32_t r; asm("cvt.rn.bf16x2.f32 %0, %1, %2;" : "=r"(r) : "f"(b), "f"(a)); return r;
}
__device__ __forceinline__ uint32_t relu_sq(float a, float b) {
  uint32_t r; asm("{.reg .b32 v; cvt.rn.relu.bf16x2.f32 v, %1, %2; mul.rn.bf16x2 %0, v, v;}" : "=r"(r) : "f"(b), "f"(a)); return r;
}
__device__ __forceinline__ float lo(uint32_t u) { return __uint_as_float(u << 16); }
__device__ __forceinline__ float hi(uint32_t u) { return __uint_as_float(u & 0xFFFF0000u); }
__device__ __forceinline__ float ex2(float x) { float y; asm("ex2.approx.ftz.f32 %0, %1;" : "=f"(y) : "f"(x)); return y; }
__device__ __forceinline__ void stsm4(uint32_t a, uint32_t r0, uint32_t r1, uint32_t r2, uint32_t r3) {
  asm volatile("stmatrix.sync.aligned.m8n8.x4.shared.b16 [%0], {%1,%2,%3,%4};" ::"r"(a), "r"(r0), "r"(r1), "r"(r2), "r"(r3) : "memory");
}
__device__ __forceinline__ void tma3(uint32_t dst, const CUtensorMap* m, int c0, int c1, int c2, uint32_t bar) {
  asm volatile("cp.async.bulk.tensor.3d.shared::cluster.global.mbarrier::complete_tx::bytes [%0], [%1, {%3,%4,%5}], [%2];"
               ::"r"(dst), "l"(m), "r"(bar), "r"(c0), "r"(c1), "r"(c2) : "memory");
}
__device__ __forceinline__ void tma2(uint32_t dst, const CUtensorMap* m, int c0, int c1, uint32_t bar) {
  asm volatile("cp.async.bulk.tensor.2d.shared::cluster.global.mbarrier::complete_tx::bytes [%0], [%1, {%3,%4}], [%2];"
               ::"r"(dst), "l"(m), "r"(bar), "r"(c0), "r"(c1) : "memory");
}
__device__ __forceinline__ uint32_t lds32(uint32_t a) { uint32_t v; asm volatile("ld.shared.u32 %0, [%1];" : "=r"(v) : "r"(a) : "memory"); return v; }
__device__ __forceinline__ void bulk_ld(uint32_t dst, const void* src, int bytes, uint32_t bar) {
  asm volatile("cp.async.bulk.shared::cluster.global.mbarrier::complete_tx::bytes [%0], [%1], %2, [%3];" ::"r"(dst), "l"(src), "r"(bytes), "r"(bar) : "memory");
}
__device__ __forceinline__ uint4 ldcg4(const void* p) {
  uint4 v; asm volatile("ld.global.cg.v4.u32 {%0,%1,%2,%3}, [%4];" : "=r"(v.x), "=r"(v.y), "=r"(v.z), "=r"(v.w) : "l"(p) : "memory"); return v;
}

__device__ __forceinline__ uint2 ldcg2(const void* p) {
  uint2 v; asm volatile("ld.global.cg.v2.u32 {%0,%1}, [%2];" : "=r"(v.x), "=r"(v.y) : "l"(p) : "memory"); return v;
}

__device__ __forceinline__ void mma_ss_184(float (&d)[92], uint64_t da, uint64_t db, int acc) {
  asm volatile("{.reg .pred p; setp.ne.b32 p, %94, 0;\n"
    "wgmma.mma_async.sync.aligned.m64n184k16.f32.bf16.bf16 {%0,%1,%2,%3,%4,%5,%6,%7,%8,%9,%10,%11,%12,%13,%14,%15,%16,%17,%18,%19,%20,%21,%22,%23,%24,%25,%26,%27,%28,%29,%30,%31,%32,%33,%34,%35,%36,%37,%38,%39,%40,%41,%42,%43,%44,%45,%46,%47,%48,%49,%50,%51,%52,%53,%54,%55,%56,%57,%58,%59,%60,%61,%62,%63,%64,%65,%66,%67,%68,%69,%70,%71,%72,%73,%74,%75,%76,%77,%78,%79,%80,%81,%82,%83,%84,%85,%86,%87,%88,%89,%90,%91}, %92, %93, p, 1, 1, 0, 1;}\n"
    : "+f"(d[0]),"+f"(d[1]),"+f"(d[2]),"+f"(d[3]),"+f"(d[4]),"+f"(d[5]),"+f"(d[6]),"+f"(d[7]),"+f"(d[8]),"+f"(d[9]),"+f"(d[10]),"+f"(d[11]),"+f"(d[12]),"+f"(d[13]),"+f"(d[14]),"+f"(d[15]),"+f"(d[16]),"+f"(d[17]),"+f"(d[18]),"+f"(d[19]),"+f"(d[20]),"+f"(d[21]),"+f"(d[22]),"+f"(d[23]),"+f"(d[24]),"+f"(d[25]),"+f"(d[26]),"+f"(d[27]),"+f"(d[28]),"+f"(d[29]),"+f"(d[30]),"+f"(d[31]),"+f"(d[32]),"+f"(d[33]),"+f"(d[34]),"+f"(d[35]),"+f"(d[36]),"+f"(d[37]),"+f"(d[38]),"+f"(d[39]),"+f"(d[40]),"+f"(d[41]),"+f"(d[42]),"+f"(d[43]),"+f"(d[44]),"+f"(d[45]),"+f"(d[46]),"+f"(d[47]),"+f"(d[48]),"+f"(d[49]),"+f"(d[50]),"+f"(d[51]),"+f"(d[52]),"+f"(d[53]),"+f"(d[54]),"+f"(d[55]),"+f"(d[56]),"+f"(d[57]),"+f"(d[58]),"+f"(d[59]),"+f"(d[60]),"+f"(d[61]),"+f"(d[62]),"+f"(d[63]),"+f"(d[64]),"+f"(d[65]),"+f"(d[66]),"+f"(d[67]),"+f"(d[68]),"+f"(d[69]),"+f"(d[70]),"+f"(d[71]),"+f"(d[72]),"+f"(d[73]),"+f"(d[74]),"+f"(d[75]),"+f"(d[76]),"+f"(d[77]),"+f"(d[78]),"+f"(d[79]),"+f"(d[80]),"+f"(d[81]),"+f"(d[82]),"+f"(d[83]),"+f"(d[84]),"+f"(d[85]),"+f"(d[86]),"+f"(d[87]),"+f"(d[88]),"+f"(d[89]),"+f"(d[90]),"+f"(d[91])
    : "l"(da), "l"(db), "r"(acc));
}
__device__ __forceinline__ void mma_ss_224(float (&d)[112], uint64_t da, uint64_t db, int acc) {
  asm volatile("{.reg .pred p; setp.ne.b32 p, %114, 0;\n"
    "wgmma.mma_async.sync.aligned.m64n224k16.f32.bf16.bf16 {%0,%1,%2,%3,%4,%5,%6,%7,%8,%9,%10,%11,%12,%13,%14,%15,%16,%17,%18,%19,%20,%21,%22,%23,%24,%25,%26,%27,%28,%29,%30,%31,%32,%33,%34,%35,%36,%37,%38,%39,%40,%41,%42,%43,%44,%45,%46,%47,%48,%49,%50,%51,%52,%53,%54,%55,%56,%57,%58,%59,%60,%61,%62,%63,%64,%65,%66,%67,%68,%69,%70,%71,%72,%73,%74,%75,%76,%77,%78,%79,%80,%81,%82,%83,%84,%85,%86,%87,%88,%89,%90,%91,%92,%93,%94,%95,%96,%97,%98,%99,%100,%101,%102,%103,%104,%105,%106,%107,%108,%109,%110,%111}, %112, %113, p, 1, 1, 0, 1;}\n"
    : "+f"(d[0]),"+f"(d[1]),"+f"(d[2]),"+f"(d[3]),"+f"(d[4]),"+f"(d[5]),"+f"(d[6]),"+f"(d[7]),"+f"(d[8]),"+f"(d[9]),"+f"(d[10]),"+f"(d[11]),"+f"(d[12]),"+f"(d[13]),"+f"(d[14]),"+f"(d[15]),"+f"(d[16]),"+f"(d[17]),"+f"(d[18]),"+f"(d[19]),"+f"(d[20]),"+f"(d[21]),"+f"(d[22]),"+f"(d[23]),"+f"(d[24]),"+f"(d[25]),"+f"(d[26]),"+f"(d[27]),"+f"(d[28]),"+f"(d[29]),"+f"(d[30]),"+f"(d[31]),"+f"(d[32]),"+f"(d[33]),"+f"(d[34]),"+f"(d[35]),"+f"(d[36]),"+f"(d[37]),"+f"(d[38]),"+f"(d[39]),"+f"(d[40]),"+f"(d[41]),"+f"(d[42]),"+f"(d[43]),"+f"(d[44]),"+f"(d[45]),"+f"(d[46]),"+f"(d[47]),"+f"(d[48]),"+f"(d[49]),"+f"(d[50]),"+f"(d[51]),"+f"(d[52]),"+f"(d[53]),"+f"(d[54]),"+f"(d[55]),"+f"(d[56]),"+f"(d[57]),"+f"(d[58]),"+f"(d[59]),"+f"(d[60]),"+f"(d[61]),"+f"(d[62]),"+f"(d[63]),"+f"(d[64]),"+f"(d[65]),"+f"(d[66]),"+f"(d[67]),"+f"(d[68]),"+f"(d[69]),"+f"(d[70]),"+f"(d[71]),"+f"(d[72]),"+f"(d[73]),"+f"(d[74]),"+f"(d[75]),"+f"(d[76]),"+f"(d[77]),"+f"(d[78]),"+f"(d[79]),"+f"(d[80]),"+f"(d[81]),"+f"(d[82]),"+f"(d[83]),"+f"(d[84]),"+f"(d[85]),"+f"(d[86]),"+f"(d[87]),"+f"(d[88]),"+f"(d[89]),"+f"(d[90]),"+f"(d[91]),"+f"(d[92]),"+f"(d[93]),"+f"(d[94]),"+f"(d[95]),"+f"(d[96]),"+f"(d[97]),"+f"(d[98]),"+f"(d[99]),"+f"(d[100]),"+f"(d[101]),"+f"(d[102]),"+f"(d[103]),"+f"(d[104]),"+f"(d[105]),"+f"(d[106]),"+f"(d[107]),"+f"(d[108]),"+f"(d[109]),"+f"(d[110]),"+f"(d[111])
    : "l"(da), "l"(db), "r"(acc));
}
__device__ __forceinline__ void mma_ss_56(float (&d)[28], uint64_t da, uint64_t db, int acc) {
  asm volatile("{.reg .pred p; setp.ne.b32 p, %30, 0;\n"
    "wgmma.mma_async.sync.aligned.m64n56k16.f32.bf16.bf16 {%0,%1,%2,%3,%4,%5,%6,%7,%8,%9,%10,%11,%12,%13,%14,%15,%16,%17,%18,%19,%20,%21,%22,%23,%24,%25,%26,%27}, %28, %29, p, 1, 1, 0, 1;}\n"
    : "+f"(d[0]),"+f"(d[1]),"+f"(d[2]),"+f"(d[3]),"+f"(d[4]),"+f"(d[5]),"+f"(d[6]),"+f"(d[7]),"+f"(d[8]),"+f"(d[9]),"+f"(d[10]),"+f"(d[11]),"+f"(d[12]),"+f"(d[13]),"+f"(d[14]),"+f"(d[15]),"+f"(d[16]),"+f"(d[17]),"+f"(d[18]),"+f"(d[19]),"+f"(d[20]),"+f"(d[21]),"+f"(d[22]),"+f"(d[23]),"+f"(d[24]),"+f"(d[25]),"+f"(d[26]),"+f"(d[27])
    : "l"(da), "l"(db), "r"(acc));
}
__device__ __forceinline__ void mma_rs_56(float (&d)[28], uint32_t a0, uint32_t a1, uint32_t a2, uint32_t a3, uint64_t db, int acc) {
  asm volatile("{.reg .pred p; setp.ne.b32 p, %33, 0;\n"
    "wgmma.mma_async.sync.aligned.m64n56k16.f32.bf16.bf16 {%0,%1,%2,%3,%4,%5,%6,%7,%8,%9,%10,%11,%12,%13,%14,%15,%16,%17,%18,%19,%20,%21,%22,%23,%24,%25,%26,%27}, {%28,%29,%30,%31}, %32, p, 1, 1, 1;}\n"
    : "+f"(d[0]),"+f"(d[1]),"+f"(d[2]),"+f"(d[3]),"+f"(d[4]),"+f"(d[5]),"+f"(d[6]),"+f"(d[7]),"+f"(d[8]),"+f"(d[9]),"+f"(d[10]),"+f"(d[11]),"+f"(d[12]),"+f"(d[13]),"+f"(d[14]),"+f"(d[15]),"+f"(d[16]),"+f"(d[17]),"+f"(d[18]),"+f"(d[19]),"+f"(d[20]),"+f"(d[21]),"+f"(d[22]),"+f"(d[23]),"+f"(d[24]),"+f"(d[25]),"+f"(d[26]),"+f"(d[27])
    : "r"(a0), "r"(a1), "r"(a2), "r"(a3), "l"(db), "r"(acc));
}
__device__ __forceinline__ void mma_ss_64t(float (&d)[32], uint64_t da, uint64_t db, int acc) {
  asm volatile("{.reg .pred p; setp.ne.b32 p, %34, 0;\n"
    "wgmma.mma_async.sync.aligned.m64n64k16.f32.bf16.bf16 {%0,%1,%2,%3,%4,%5,%6,%7,%8,%9,%10,%11,%12,%13,%14,%15,%16,%17,%18,%19,%20,%21,%22,%23,%24,%25,%26,%27,%28,%29,%30,%31}, %32, %33, p, 1, 1, 1, 1;}\n"
    : "+f"(d[0]),"+f"(d[1]),"+f"(d[2]),"+f"(d[3]),"+f"(d[4]),"+f"(d[5]),"+f"(d[6]),"+f"(d[7]),"+f"(d[8]),"+f"(d[9]),"+f"(d[10]),"+f"(d[11]),"+f"(d[12]),"+f"(d[13]),"+f"(d[14]),"+f"(d[15]),"+f"(d[16]),"+f"(d[17]),"+f"(d[18]),"+f"(d[19]),"+f"(d[20]),"+f"(d[21]),"+f"(d[22]),"+f"(d[23]),"+f"(d[24]),"+f"(d[25]),"+f"(d[26]),"+f"(d[27]),"+f"(d[28]),"+f"(d[29]),"+f"(d[30]),"+f"(d[31])
    : "l"(da), "l"(db), "r"(acc));
}
__device__ __forceinline__ void mma_rs_64(float (&d)[32], uint32_t a0, uint32_t a1, uint32_t a2, uint32_t a3, uint64_t db, int acc) {
  asm volatile("{.reg .pred p; setp.ne.b32 p, %37, 0;\n"
    "wgmma.mma_async.sync.aligned.m64n64k16.f32.bf16.bf16 {%0,%1,%2,%3,%4,%5,%6,%7,%8,%9,%10,%11,%12,%13,%14,%15,%16,%17,%18,%19,%20,%21,%22,%23,%24,%25,%26,%27,%28,%29,%30,%31}, {%32,%33,%34,%35}, %36, p, 1, 1, 1;}\n"
    : "+f"(d[0]),"+f"(d[1]),"+f"(d[2]),"+f"(d[3]),"+f"(d[4]),"+f"(d[5]),"+f"(d[6]),"+f"(d[7]),"+f"(d[8]),"+f"(d[9]),"+f"(d[10]),"+f"(d[11]),"+f"(d[12]),"+f"(d[13]),"+f"(d[14]),"+f"(d[15]),"+f"(d[16]),"+f"(d[17]),"+f"(d[18]),"+f"(d[19]),"+f"(d[20]),"+f"(d[21]),"+f"(d[22]),"+f"(d[23]),"+f"(d[24]),"+f"(d[25]),"+f"(d[26]),"+f"(d[27]),"+f"(d[28]),"+f"(d[29]),"+f"(d[30]),"+f"(d[31])
    : "r"(a0), "r"(a1), "r"(a2), "r"(a3), "l"(db), "r"(acc));
}

__device__ __forceinline__ void dual_softmax(const float (&p)[28], uint32_t (&phi)[4][7]) {
  constexpr float L2E = 1.4426950408889634f;
#pragma unroll
  for (int i = 0; i < 4; i++) {
    float mx = p[i], mn = p[i];
#pragma unroll
    for (int j = 1; j < 7; j++) { mx = fmaxf(mx, p[4 * j + i]); mn = fminf(mn, p[4 * j + i]); }
    mx = fmaxf(mx, __shfl_xor_sync(~0u, mx, 1)); mn = fminf(mn, __shfl_xor_sync(~0u, mn, 1));
    mx = fmaxf(mx, __shfl_xor_sync(~0u, mx, 2)); mn = fminf(mn, __shfl_xor_sync(~0u, mn, 2));
    float a[7], b[7], sa = 0.f, sb = 0.f;
    const float mxl = mx * L2E, mnl = mn * L2E;
#pragma unroll
    for (int j = 0; j < 7; j++) {
      a[j] = ex2(fmaf(p[4 * j + i], L2E, -mxl)); b[j] = ex2(fmaf(p[4 * j + i], -L2E, mnl));
      sa += a[j]; sb += b[j];
    }
    sa += __shfl_xor_sync(~0u, sa, 1); sb += __shfl_xor_sync(~0u, sb, 1);
    sa += __shfl_xor_sync(~0u, sa, 2); sb += __shfl_xor_sync(~0u, sb, 2);
    const float ra = __fdividef(1.f, sa), rb = __fdividef(1.f, sb);
#pragma unroll
    for (int j = 0; j < 7; j++) phi[i][j] = pack(a[j] * ra, b[j] * rb);
  }
}

struct Ring {
  uint32_t full, empty, base; int slot, par;
  __device__ __forceinline__ void uniform() { slot = __shfl_sync(~0u, slot, 0); par = __shfl_sync(~0u, par, 0); }
  __device__ __forceinline__ uint32_t acquire() { mbar_wait(full + slot * 8, par); return base + slot * SLOT; }
  __device__ __forceinline__ int advance() { int s = slot; if (++slot == NSLOT) { slot = 0; par ^= 1; } return s; }
  __device__ __forceinline__ void release(int s, bool elect) { if (elect) mbar_arrive(empty + s * 8); }
};
constexpr int NPRE = 3, PRECH = 5, UNR = 14;
constexpr int FL_KV = 448, FL_CS = FL_KV + 16, FL_DONE = FL_KV + 32;

__global__ void __launch_bounds__(384, 1)
fused_kernel(const __grid_constant__ CUtensorMap mQKV, const __grid_constant__ CUtensorMap mWO,
             const __grid_constant__ CUtensorMap mW1, const __grid_constant__ CUtensorMap mW2,
             const __grid_constant__ CUtensorMap mX, const __nv_bfloat16* __restrict__ wphi,
             const __nv_bfloat16* __restrict__ b1, const __nv_bfloat16* __restrict__ b2,
             const __nv_bfloat16* __restrict__ wqkv, const __nv_bfloat16* __restrict__ wo, const __nv_bfloat16* __restrict__ w1,
             const __nv_bfloat16* __restrict__ w2, __nv_bfloat16* __restrict__ out) {
  extern __shared__ unsigned char smem_raw[];
  const uint32_t sb = (smem_u32(smem_raw) + 1023) & ~1023u;
  unsigned char* sg = smem_raw + (sb - smem_u32(smem_raw));
  const int tid = threadIdx.x, lane = tid & 31;
  const int G = blockIdx.x >> 3, r = blockIdx.x & 7;
  const uint32_t barFull = sb + OFF_BAR, barEmpty = barFull + 56, barA = barEmpty + 56, barCS = barA + 112, barX = barCS + 16;
  const int warp = __shfl_sync(~0u, tid >> 5, 0);
  uint32_t wv[7] = {}, bv = 0;
  if (warp < 8) {
#pragma unroll
    for (int i = 0; i < 7; i++)
      wv[i] = __ldg(reinterpret_cast<const unsigned short*>(wphi) + (56 * r + i * 8 + warp) * 28 + min(lane, 27));
    bv = __ldg(reinterpret_cast<const unsigned short*>(b1) + 224 * r + min(tid, 223));
  }
  if (lane == 0) {
    if (warp >= 10) {
      const int cc = warp - 10;
      mbar_init(barX + cc * 8, 1);
      fence_async_smem();
      mbar_expect(barX + cc * 8, ABYTES);
#pragma unroll 1
      for (int k = 0; k < 7; k++) tma2(sb + cc * ABYTES + k * 8192, &mX, 64 * k, G * 128 + 64 * cc, barX + cc * 8);
    } else if (warp < 7) { mbar_init(barFull + warp * 8, 1); mbar_init(barEmpty + warp * 8, 2); mbar_init(barA + warp * 8, 1); mbar_init(barA + 56 + warp * 8, 1); }
    else if (warp < 9) { mbar_init(barCS + (warp - 7) * 8, 64); if (warp == 7) mbar_init(barX + 16, 1); }
    else
      asm volatile("cp.async.bulk.prefetch.L2.global [%0], %1;" ::"l"((const char*)wqkv + blockIdx.x * 9408), "r"(9408) : "memory");
    asm volatile("fence.mbarrier_init.release.cluster;" ::: "memory");
  }
  if (tid < 192) reinterpret_cast<float*>(sg + OFF_CS)[tid] = 0.f;
  __syncthreads();
  const int wgid = warp >> 2;
  if (wgid == 2) {
    asm volatile("setmaxnreg.dec.sync.aligned.u32 40;");
    if (warp == 8) {
      int slot = 0, par = 1;
#pragma unroll 1
      for (int it = 0; it < 2 * TILES_PER_LAYER; it++) {
        const int i = it >= TILES_PER_LAYER ? it - TILES_PER_LAYER : it;
        mbar_wait(barEmpty + slot * 8, par);
        const uint32_t dst = sb + OFF_RING + slot * SLOT, fb = barFull + slot * 8;
        if (elect_one()) {
          mbar_expect(fb, i < 14 ? 12288 : SLOT);
          if (i < 14) tma3(dst, &mQKV, 56 * r, 32 * i, 0, fb);
          else if (i < 18) tma2(dst, &mWO, 56 * r, 112 * (i - 14), fb);
          else if (i < 32) tma3(dst, &mW1, 0, 32 * (i - 18), 7 * r, fb);
          else tma2(dst, &mW2, 64 * ((i - 32) >> 1), 224 * r + 112 * (i & 1), fb);
        }
        if (++slot == NSLOT) { slot = 0; par ^= 1; }
      }
    } else if (warp == 11) {
      unsigned ep;
      asm volatile("ld.relaxed.gpu.global.u32 %0, [%1];" : "=r"(ep) : "l"(gFlag + FL_DONE * 32) : "memory");
#pragma unroll 1
      for (int layer = 0; layer < 2; layer++) {
        bar_sync<4, 288>();
        if (lane == 0) {
          flag_arrive(gFlag + (FL_KV + layer * 8 + r) * 32);
          flag_wait(gFlag + (FL_KV + layer * 8 + r) * 32, (ep / NCTA + 1) * 16);
          mbar_arrive(barX + 16);
        }
        __syncwarp();
      }
    } else {
      unsigned ep;
      asm volatile("ld.relaxed.gpu.global.u32 %0, [%1];" : "=r"(ep) : "l"(gFlag + FL_DONE * 32) : "memory");
      const int idx = tid - 288;
      ep = (ep / NCTA + 1) * 2;
      if (G == 0) {
#pragma unroll 1
        for (int i = idx; i < 2 * 1280; i += 64) gKV[((i >= 1280) * 7 + r) * 1280 + i] = make_float4(0.f, 0.f, 0.f, 0.f);
        __syncwarp();
        if (lane == 0) flag_arrive(gFlag + (FL_CS + r) * 32);
      }
      mbar_wait(barFull + 48, 0); mbar_wait(barFull + 48, 1);
      if (idx < 2) {
        const char* pf = idx ? (const char*)w2 + blockIdx.x * 12544 : (const char*)wo + blockIdx.x * 3136;
        asm volatile("cp.async.bulk.prefetch.L2.global [%0], %1;" ::"l"(pf), "r"(idx ? 12544 : 3136) : "memory");
      }
      if (lane == 0) flag_wait(gFlag + (FL_CS + r) * 32, ep);
      __syncwarp();
      mbar_arrive(barCS);
#pragma unroll 1
      for (int ps = 0; ps < 4; ps++) {
        const int ch = min(ps * 16 + (idx >> 2), 48), p = ch / 7, k0 = G * 28 + (idx & 3) * 7;
        const uint4* src = ch >= 21 ? reinterpret_cast<const uint4*>(w1 + (size_t)k0 * 1792 + 224 * r) + (ch - 21)
                                    : reinterpret_cast<const uint4*>(wqkv + (size_t)k0 * 1344 + p * 448 + 56 * r) + (ch - 7 * p);
        uint4 cu[7];
#pragma unroll
        for (int i = 0; i < 7; i++) cu[i] = __ldg(src + i * (ch >= 21 ? 224 : 168));
        float s[8] = {};
#pragma unroll
        for (int i = 0; i < 7; i++) { s[0] += lo(cu[i].x); s[1] += hi(cu[i].x); s[2] += lo(cu[i].y); s[3] += hi(cu[i].y); s[4] += lo(cu[i].z); s[5] += hi(cu[i].z); s[6] += lo(cu[i].w); s[7] += hi(cu[i].w); }
#pragma unroll
        for (int i = 0; i < 8; i++) { s[i] += __shfl_xor_sync(~0u, s[i], 1); s[i] += __shfl_xor_sync(~0u, s[i], 2); }
        if ((idx & 3) < 2) gCS[(r * 16 + G) * 104 + (ch + min(p, 3)) * 2 + (idx & 1)] = (idx & 1) ? make_float4(s[4], s[5], s[6], s[7]) : make_float4(s[0], s[1], s[2], s[3]);
      }
      __syncwarp();
      if (lane == 0) { flag_arrive(gFlag + (FL_CS + 8 + r) * 32); flag_wait(gFlag + (FL_CS + 8 + r) * 32, ep * 16); }
      __syncwarp();
#pragma unroll 1
      for (int j = idx; j < 208; j += 64) {
        float2 a = make_float2(0.f, 0.f);
#pragma unroll 8
        for (int i = 0; i < 16; i++) { const float2 v = __ldcg(reinterpret_cast<const float2*>(gCS + (r * 16 + i) * 104) + j); a.x += v.x; a.y += v.y; }
        reinterpret_cast<float2*>(sg + OFF_CS)[j] = a;
      }
      mbar_arrive(barCS + 8);
    }
  } else {
  asm volatile("setmaxnreg.inc.sync.aligned.u32 232;");
  const int c = wgid, w = warp & 3, g = lane >> 2, t = lane & 3;
  int elect_i = (tid & 127) == 0;
  asm volatile("" : "+r"(elect_i));
  const bool elect = elect_i;
  const uint32_t abuf = sb + c * ABYTES, barAc = barA + c * 56;
  const int row0 = G * 128 + c * 64;
  unsigned epoch;
  asm volatile("ld.relaxed.gpu.global.u32 %0, [%1];" : "=r"(epoch) : "l"(gFlag + FL_DONE * 32) : "memory");
  STAMP(24);
  float mean[2], rstd[2] = {0.f, 0.f};
  uint4 su[2] = {};
  uint32_t xs[7][2];
  {
#pragma unroll
    for (int i = 0; i < 8; i++) {
      const int k = i * 8 + (tid >> 5);
      *reinterpret_cast<uint32_t*>(sg + OFF_WPHI + k * 128 + ((g ^ (k & 7)) << 4) + t * 4) = (i < 7 && lane < 28) ? wv[i % 7] << (k >= 28 ? 16 : 0) : 0u;
    }
    if (tid < 224) reinterpret_cast<uint32_t*>(sg + OFF_B1)[tid] = bv << 16;
    mbar_wait(barX + c * 8, 0);
    STAMP(25);
#pragma unroll
    for (int j = 0; j < 7; j++) {
      const int ci = 7 * r + j;
      const uint32_t a = abuf + (ci >> 3) * 8192 + (w * 16 + g) * 128 + (((ci & 7) ^ g) << 4) + t * 4;
      xs[j][0] = lds32(a); xs[j][1] = lds32(a + 1024);
    }
    __syncwarp();
#pragma unroll 1
    for (int hh = 0; hh < 2; hh++) {
      uint4* p = reinterpret_cast<uint4*>(sg + c * ABYTES + (w * 16 + hh * 8 + g) * 128) + t;
      uint4 v[14];
#pragma unroll
      for (int k = 0; k < 14; k++) v[k] = p[(k >> 1) * 512 + ((k ^ g) & 1) * 4];
      float a8[8] = {};
#pragma unroll
      for (int k = 0; k < 14; k++) {
        const uint32_t e[4] = {v[k].x, v[k].y, v[k].z, v[k].w};
#pragma unroll
        for (int z = 0; z < 4; z++) { a8[2 * z] += lo(e[z]); a8[2 * z + 1] += hi(e[z]); }
      }
      float sm = ((a8[0] + a8[1]) + (a8[2] + a8[3])) + ((a8[4] + a8[5]) + (a8[6] + a8[7]));
      sm += __shfl_xor_sync(~0u, sm, 1); sm += __shfl_xor_sync(~0u, sm, 2);
      sm *= 1.f / DM;
#pragma unroll
      for (int k = 0; k < 14; k++) {
        uint32_t e[4] = {v[k].x, v[k].y, v[k].z, v[k].w};
#pragma unroll
        for (int z = 0; z < 4; z++) {
          const float a = lo(e[z]) - sm, b = hi(e[z]) - sm;
          a8[2 * z] = fmaf(a, a, k ? a8[2 * z] : 0.f); a8[2 * z + 1] = fmaf(b, b, k ? a8[2 * z + 1] : 0.f);
          e[z] = pack(a, b);
        }
        p[(k >> 1) * 512 + ((k ^ g) & 1) * 4] = make_uint4(e[0], e[1], e[2], e[3]);
      }
      float q = ((a8[0] + a8[1]) + (a8[2] + a8[3])) + ((a8[4] + a8[5]) + (a8[6] + a8[7]));
      q += __shfl_xor_sync(~0u, q, 1); q += __shfl_xor_sync(~0u, q, 2);
      rstd[1] = rsqrtf(q * (1.f / DM) + 1e-5f);
      if (hh == 0) rstd[0] = rstd[1];
    }
    fence_async_smem();
    bar_sync<3, 256>();
    epoch = epoch / NCTA + 1;
    mean[0] = mean[1] = 0.f;
  }
  STAMP(0);
  Ring ring{barFull, barEmpty, sb + OFF_RING, 0, 0};
  int apar = 1;
  const uint32_t stsm_off = (w * 16 + ((lane >> 3) & 1) * 8 + (lane & 7)) * 128;
  const uint32_t stsm_hi = lane >> 4;
  const uint64_t dA = mkdesc(abuf, 1024, 128, 0);

  auto gather = [&](unsigned* fl, const unsigned char* img) {
    bar_wg(c);
    if (w == 0) {
      if (elect_one()) {
        flag_arrive(fl);
        flag_wait(fl, epoch * 8);
        fence_async();
#pragma unroll
        for (int k = 0; k < 7; k++) { mbar_expect(barAc + k * 8, 8192); bulk_ld(abuf + k * 8192, img + k * 8192, 8192, barAc + k * 8); }
      }
      __syncwarp();
    }
    apar ^= 1;
  };
  auto slice_off = [&](int j, int hh) -> uint32_t {
    return (7 * r + j) * 1024 + (w * 2 + hh) * 128 + lane * 4;
  };
  auto load_stats = [&](const float2* st) {
    mbar_wait(barAc, apar);
#pragma unroll
    for (int hh = 0; hh < 2; hh++) su[hh] = ldcg4(st + (size_t)(row0 + w * 16 + hh * 8 + g) * 8 + 2 * t);
  };
  auto finish_stats = [&]() {
#pragma unroll
    for (int hh = 0; hh < 2; hh++) {
      const float m0 = __uint_as_float(su[hh].x), m1 = __uint_as_float(su[hh].z);
      float m = m0 + m1;
      m += __shfl_xor_sync(~0u, m, 1); m += __shfl_xor_sync(~0u, m, 2);
      m *= 0.125f;
      float q = __uint_as_float(su[hh].y) + __uint_as_float(su[hh].w) + 56.f * ((m0 - m) * (m0 - m) + (m1 - m) * (m1 - m));
      q += __shfl_xor_sync(~0u, q, 1); q += __shfl_xor_sync(~0u, q, 2);
      mean[hh] = m; rstd[hh] = rsqrtf(q * (1.f / DM) + 1e-5f);
    }
  };

#pragma unroll 1
  for (int lyr = 0; lyr < 2; lyr++) {
    const int layer = __shfl_sync(~0u, lyr, 0);
    unsigned* const fl = gFlag + (layer * 32 + G * 2 + c) * 7 * 32;
    uint32_t phiq[4][7];
    {
      float acc[92]; reg_def(acc);
      int prev = 0, prev2 = 0;
      ring.uniform();
      const uint64_t dQ = layer ? dA : mkdesc(abuf, 16, 1024, 1);
      const int kstep = layer ? 128 : 2;
      if (layer) load_stats(gStat + 2048 * 8);
#pragma unroll UNR
      for (int st = 0; st < 14; st++) {
        if (!(st & 1) && layer) mbar_wait(barAc + (st >> 1) * 8, apar);
        const uint64_t da = dQ + (st >> 1) * 512 + (st & 1) * 2 * kstep, db = mkdesc(ring.acquire(), 4096, 1024, 1);
        wg_fence();
        mma_ss_184(acc, da, db, 1);
        mma_ss_184(acc, da + kstep, db + 128, 1);
        wg_commit();
        if (st > 1) { wg_wait<2>(); ring.release(prev2, elect); }
        prev2 = prev; prev = ring.advance();
      }
      if (layer) {
        finish_stats();
#pragma unroll
        for (int j = 0; j < 7; j++) { xs[j][0] = lds32(abuf + slice_off(j, 0)); xs[j][1] = lds32(abuf + slice_off(j, 1)); }
      }
      wg_wait<0>(); reg_fence(acc);
      ring.release(prev2, elect); ring.release(prev, elect);
      STAMP(1 + layer * 12);
      uint32_t f[3][14];
      auto frags = [&](const int p0, const int p1) {
        const float2* cs = reinterpret_cast<const float2*>(sg + OFF_CS) + t;
        const float mr0 = -mean[0] * rstd[0], mr1 = -mean[1] * rstd[1];
#pragma unroll
        for (int p = p0; p < p1; p++)
#pragma unroll
          for (int j = 0; j < 7; j++) {
            const float2 s = cs[p * 32 + j * 4];
            const int b = p * 32 + j * 4;
            f[p][2 * j] = pack(fmaf(acc[b], rstd[0], s.x * mr0), fmaf(acc[b + 1], rstd[0], s.y * mr0));
            f[p][2 * j + 1] = pack(fmaf(acc[b + 2], rstd[1], s.x * mr1), fmaf(acc[b + 3], rstd[1], s.y * mr1));
          }
      };
      frags(1, 2);
      float pk[28]; reg_def(pk);
      const uint64_t dW = mkdesc(sb + OFF_WPHI, 4096, 1024, 1);
      wg_fence();
#pragma unroll
      for (int s = 0; s < 4; s++) {
        mma_rs_56(pk, f[1][4 * s], f[1][4 * s + 1], s < 3 ? f[1][(4 * s + 2) % 14] : 0u, s < 3 ? f[1][(4 * s + 3) % 14] : 0u, dW + s * 128, s);
      }
      wg_commit();
      frags(2, 3);
      bar_wg(c);
      const uint32_t srow = abuf + stsm_off, ones = t == 0 ? 0x3F803F80u : 0u;
#pragma unroll
      for (int jp = 0; jp < 4; jp++)
        stsm4(srow + 16384 + (((2 * jp + stsm_hi) ^ (lane & 7)) << 4), f[2][4 * jp], f[2][4 * jp + 1],
              jp < 3 ? f[2][(4 * jp + 2) % 14] : ones, jp < 3 ? f[2][(4 * jp + 3) % 14] : ones);
      wg_wait<0>(); reg_fence(pk);
      {
        dual_softmax(pk, phiq);
#pragma unroll
        for (int e = 0; e < 2; e++)
#pragma unroll
          for (int jp = 0; jp < 4; jp++)
            stsm4(srow + e * 8192 + (((2 * jp + stsm_hi) ^ (lane & 7)) << 4), phiq[e][2 * jp], phiq[2 + e][2 * jp],
                  jp < 3 ? phiq[e][(2 * jp + 1) % 7] : 0u, jp < 3 ? phiq[2 + e][(2 * jp + 1) % 7] : 0u);
        fence_async_smem();
        bar_sync<3, 256>();
        float kv[32], kw[32]; reg_def(kv); reg_def(kw);
        const uint64_t dP = mkdesc(sb + c * 8192, 4096, 1024, 1), dV = mkdesc(sb + 16384, 4096, 1024, 1);
        wg_fence();
#pragma unroll
        for (int s = 0; s < 4; s++) { mma_ss_64t(kv, dP + s * 128, dV + s * 128, s); mma_ss_64t(kw, dP + ABYTES / 16 + s * 128, dV + ABYTES / 16 + s * 128, s); }
        wg_commit();
        mbar_wait(barCS, 0);
        wg_wait<0>(); reg_fence(kv); reg_fence(kw);
#pragma unroll
        for (int i = 0; i < 32; i++) kv[i] += kw[i];
        float4* kvg = gKV + ((layer * 8 + r) * 2 + c) * 640 + (tid & 127);
#pragma unroll
        for (int i = 0; i < 5; i++) {
          float v0, v1, v2, v3;
          if (i == 4) { v0 = kv[28]; v1 = kv[29]; v2 = kv[30]; v3 = kv[31]; }
          else { v0 = c ? kv[12 + 4 * i] : kv[4 * i]; v1 = c ? kv[13 + 4 * i] : kv[1 + 4 * i]; v2 = c ? kv[14 + 4 * i] : kv[2 + 4 * i]; v3 = c ? kv[15 + 4 * i] : kv[3 + 4 * i]; }
          const bool use = i == 4 ? t == 0 : (i == 0 ? (c == 0 || t >= 2) : (i == 3 ? (c == 1 || t < 2) : true));
          if (use) asm volatile("red.relaxed.gpu.global.add.v4.f32 [%0], {%1,%2,%3,%4};" ::"l"(kvg + i * 128), "f"(v0), "f"(v1), "f"(v2), "f"(v3) : "memory");
        }
        asm volatile("bar.arrive 4, 288;" ::: "memory");
        STAMP(2 + layer * 12);
      }
      frags(0, 1);
      float pq[28]; reg_def(pq);
      wg_fence();
#pragma unroll
      for (int s = 0; s < 4; s++)
        mma_rs_56(pq, f[0][4 * s], f[0][4 * s + 1], s < 3 ? f[0][(4 * s + 2) % 14] : 0u, s < 3 ? f[0][(4 * s + 3) % 14] : 0u, dW + s * 128, s);
      wg_commit();
      wg_wait<0>(); reg_fence(pq);
      dual_softmax(pq, phiq);
    }
    {
      mbar_wait(barX + 16, layer);
      STAMP(3 + layer * 12);
      const float4* kvg = gKV + (layer * 8 + r) * 1280 + c * 640 + (tid & 127);
      uint4 kk[5];
#pragma unroll
      for (int i = 0; i < 5; i++) kk[i] = ldcg4(kvg + i * 128);
      uint32_t f[5][2];
#pragma unroll
      for (int i = 0; i < 5; i++) { f[i][0] = pack(__uint_as_float(kk[i].x), __uint_as_float(kk[i].y)); f[i][1] = pack(__uint_as_float(kk[i].z), __uint_as_float(kk[i].w)); }
      const uint32_t zm = c ? 0xFFFF0000u : 0xFFFFu;
      const uint32_t srow = abuf + 24576 + stsm_off;
#pragma unroll
      for (int jp = 0; jp < 4; jp++) {
        uint32_t v[2][2];
#pragma unroll
        for (int u = 0; u < 2; u++) {
          const int j = 2 * jp + u;
#pragma unroll
          for (int hh = 0; hh < 2; hh++) v[u][hh] = j == 7 ? f[4][hh] & zm : (c ? (j >= 3 ? f[(j + 2) % 5][hh] : 0u) : (j < 4 ? f[j % 5][hh] : 0u));
        }
        stsm4(srow + (((2 * jp + stsm_hi) ^ (lane & 7)) << 4), v[0][0], v[0][1], v[1][0], v[1][1]);
      }
      fence_async_smem();
      bar_sync<3, 256>();
      float num[32], nub[32]; reg_def(num); reg_def(nub);
      const uint64_t dK = mkdesc(sb + 24576, 4096, 1024, 1);
      wg_fence();
#pragma unroll
      for (int s = 0; s < 4; s++) {
        mma_rs_64(num, phiq[0][2 * s], phiq[2][2 * s], s < 3 ? phiq[0][(2 * s + 1) % 7] : 0u, s < 3 ? phiq[2][(2 * s + 1) % 7] : 0u, dK + s * 128, s);
        mma_rs_64(nub, phiq[1][2 * s], phiq[3][2 * s], s < 3 ? phiq[1][(2 * s + 1) % 7] : 0u, s < 3 ? phiq[3][(2 * s + 1) % 7] : 0u, dK + ABYTES / 16 + s * 128, s);
      }
      wg_commit();
      wg_wait<0>(); reg_fence(num); reg_fence(nub);
      bar_sync<3, 256>();
#pragma unroll
      for (int i = 12; i < 32; i++) num[i] += nub[i];
      float rd[4];
#pragma unroll
      for (int i = 0; i < 4; i++) rd[i] = __fdividef(1.f, __shfl_sync(~0u, num[28 + i], lane & ~3) + 1e-6f);
      unsigned char* img = gImg + (size_t)(G * 2 + c) * ABYTES;
#pragma unroll
      for (int j = 0; j < 7; j++) {
        const bool hb = j > 3 || (j == 3 && t >= 2);
        const float r0 = hb ? rd[1] : rd[0], r1 = hb ? rd[3] : rd[2];
        *reinterpret_cast<uint32_t*>(img + slice_off(j, 0)) = pack(num[4 * j] * r0, num[4 * j + 1] * r0);
        *reinterpret_cast<uint32_t*>(img + slice_off(j, 1)) = pack(num[4 * j + 2] * r1, num[4 * j + 3] * r1);
      }
      STAMP(4 + layer * 12);
      gather(fl, img);
      STAMP(5 + layer * 12);
    }
    {
      float acc[28], acc2[28]; reg_def(acc); reg_def(acc2); reg_fence(acc); reg_fence(acc2);
      int sl[4];
      ring.uniform();
#pragma unroll
      for (int st = 0; st < 4; st++) {
        const uint64_t db = mkdesc(ring.acquire(), 4096, 1024, 1);
        sl[st] = ring.advance();
#pragma unroll
        for (int s = 0; s < 7; s++) {
          const int ks = st * 7 + s;
          if (!(ks & 3)) mbar_wait(barAc + (ks >> 2) * 8, apar);
          if (!(ks & 3) || !s) wg_fence();
          if (ks & 1) mma_ss_56(acc2, dA + ks * 128, db + s * 128, ks > 1); else mma_ss_56(acc, dA + ks * 128, db + s * 128, ks > 1);
        }
        wg_commit();
      }
      wg_wait<0>(); reg_fence(acc); reg_fence(acc2);
      unsigned char* img = gImg + (size_t)(32 + G * 2 + c) * ABYTES;
#pragma unroll
      for (int hh = 0; hh < 2; hh++) {
        float s = 0.f, q = 0.f;
#pragma unroll
        for (int j = 0; j < 7; j++) {
          xs[j][hh] = pack(lo(xs[j][hh]) + (acc[4 * j + 2 * hh] + acc2[4 * j + 2 * hh]), hi(xs[j][hh]) + (acc[4 * j + 2 * hh + 1] + acc2[4 * j + 2 * hh + 1]));
          *reinterpret_cast<uint32_t*>(img + slice_off(j, hh)) = xs[j][hh];
          s += lo(xs[j][hh]) + hi(xs[j][hh]);
        }
        s += __shfl_xor_sync(~0u, s, 1); s += __shfl_xor_sync(~0u, s, 2);
        s *= 1.f / 56.f;
#pragma unroll
        for (int j = 0; j < 7; j++) { const float a = lo(xs[j][hh]) - s, b = hi(xs[j][hh]) - s; q = fmaf(a, a, q); q = fmaf(b, b, q); }
        q += __shfl_xor_sync(~0u, q, 1); q += __shfl_xor_sync(~0u, q, 2);
        if (t == 0) gStat[(size_t)(row0 + w * 16 + hh * 8 + g) * 8 + r] = make_float2(s, q);
      }
#pragma unroll
      for (int j = 0; j < 7; j++) xs[j][0] = xs[j][1] = 0u;
      STAMP(6 + layer * 12);
      gather(fl + 32, img);
#pragma unroll
      for (int st = 0; st < 4; st++) ring.release(sl[st], elect);
      STAMP(7 + layer * 12);
    }
    uint2 pv[7][7];
    const unsigned char* psrc = gP + (size_t)(((G * 2 + c) * 8 + r) * 8) * 7168 + w * 256 + lane * 8;
    {
      uint32_t hf[28][2];
      {
        float acc[112]; reg_def(acc);
        int prev = 0, prev2 = 0;
        load_stats(gStat);
        ring.uniform();
#pragma unroll UNR
        for (int st = 0; st < 14; st++) {
          if (!(st & 1)) mbar_wait(barAc + (st >> 1) * 8, apar);
          const uint64_t da = dA + st * 256, db = mkdesc(ring.acquire(), 2048, 512, 2);
          wg_fence();
          mma_ss_224(acc, da, db, 1);
          mma_ss_224(acc, da + 128, db + 64, 1);
          wg_commit();
          if (st > 1) { wg_wait<2>(); ring.release(prev2, elect); }
          prev2 = prev; prev = ring.advance();
        }
        finish_stats();
        mbar_wait(barCS + 8, 0);
        wg_wait<0>(); reg_fence(acc);
        ring.release(prev2, elect); ring.release(prev, elect);
        STAMP(8 + layer * 12);
        const float2* bs = reinterpret_cast<const float2*>(sg + OFF_B1) + t;
        const float2* cs = reinterpret_cast<const float2*>(sg + OFF_CS + 768) + t;
        const float mr0 = -mean[0] * rstd[0], mr1 = -mean[1] * rstd[1];
#pragma unroll
        for (int j = 0; j < 28; j++) {
          const float2 b = bs[4 * j], s = cs[4 * j];
          hf[j][0] = relu_sq(fmaf(acc[4 * j], rstd[0], fmaf(s.x, mr0, b.x)), fmaf(acc[4 * j + 1], rstd[0], fmaf(s.y, mr0, b.y)));
          hf[j][1] = relu_sq(fmaf(acc[4 * j + 2], rstd[1], fmaf(s.x, mr1, b.x)), fmaf(acc[4 * j + 3], rstd[1], fmaf(s.y, mr1, b.y)));
        }
      }
      unsigned char* pd[2]; int pstr[2];
#pragma unroll
      for (int hh = 0; hh < 2; hh++) {
        const bool own = 2 * w + hh == r;
        pd[hh] = own ? sg + c * ABYTES + (lane >> 4) * 1024 + (r ^ 1) * 128 + (lane & 15) * 8
                     : gP + (size_t)(((G * 2 + c) * 8 + 2 * w + hh) * 8 + r) * 7168 + lane * 8;
        pstr[hh] = own ? 2048 : 256;
      }
      uint2 pk[8] = {};
#pragma unroll
      for (int i = 0; i < 7 * NPRE; i++) pv[i % 7][i / 7] = make_uint2(0u, 0u);
      ring.uniform();
#pragma unroll 1
      for (int ch = 0; ch < 7; ch++) {
        float acc[32], acc2[32]; reg_def(acc); reg_def(acc2);
        const uint64_t db0 = mkdesc(ring.acquire(), 4096, 1024, 1);
        const int sl0 = ring.advance();
        const uint64_t db1 = mkdesc(ring.acquire(), 4096, 1024, 1);
        const int sl1 = ring.advance();
        wg_fence();
#pragma unroll
        for (int s = 0; s < 7; s++) {
          mma_rs_64(acc, hf[2 * s][0], hf[2 * s][1], hf[2 * s + 1][0], hf[2 * s + 1][1], db0 + s * 128, s);
          mma_rs_64(acc2, hf[14 + 2 * s][0], hf[14 + 2 * s][1], hf[15 + 2 * s][0], hf[15 + 2 * s][1], db1 + s * 128, s);
        }
        wg_commit();
        if (ch > 0) {
#pragma unroll
          for (int i = 0; i < 8; i++) { *reinterpret_cast<uint2*>(pd[i & 1]) = pk[i]; pd[i & 1] += pstr[i & 1]; }
        }
        if (ch == PRECH) {
#pragma unroll
          for (int i = 0; i < 7 * NPRE; i++) pv[i % 7][i / 7] = ldcg2(psrc + ((r + 1 + i % 7) & 7) * 7168 + (i / 7) * 1024);
        }
        wg_wait<0>(); reg_fence(acc); reg_fence(acc2); ring.release(sl0, elect && ch < 5); ring.release(sl1, elect && ch < 5);
#pragma unroll
        for (int i = 0; i < 8; i++) {
          const int b = (i >> 1) * 8 + (i & 1) * 2;
          pk[i] = make_uint2((pack(acc[b] + acc2[b], acc[b + 1] + acc2[b + 1]) & ~1u) | (layer ^ 1), pack(acc[b + 4] + acc2[b + 4], acc[b + 5] + acc2[b + 5]));
        }
      }
#pragma unroll
      for (int i = 0; i < 8; i++) { *reinterpret_cast<uint2*>(pd[i & 1]) = pk[i]; pd[i & 1] += pstr[i & 1]; }
      STAMP(9 + layer * 12);
    }
    {
      uint32_t bx[14];
#pragma unroll
      for (int j = 0; j < 14; j++) bx[j] = __ldg(reinterpret_cast<const uint32_t*>(b2 + (j >> 1) * 64 + w * 16 + (j & 1) * 8 + 2 * t));
      unsigned char* img = gImg + (size_t)(64 + G * 2 + c) * ABYTES;
      const unsigned char* ps[7];
#pragma unroll
      for (int s = 0; s < 7; s++) ps[s] = psrc + ((r + 1 + s) & 7) * 7168;
#pragma unroll
      for (int i = NPRE; i < 5; i++)
#pragma unroll
        for (int s = 0; s < 7; s++) pv[s][i] = ldcg2(ps[s] + i * 1024);
      bar_wg(c);
      const uint32_t off = w * 2048 + r * 128 + lane * 4;
      unsigned char* dst = layer ? reinterpret_cast<unsigned char*>(out + (size_t)(row0 + r * 8 + g) * DM + w * 16 + 4 * t) : img + off;
      float sm = 0.f, q = 0.f;
#pragma unroll
      for (int i = 0; i < 7; i++) {
        const uint2 own = *reinterpret_cast<const uint2*>(sg + c * ABYTES + i * 8192 + w * 2048 + (lane >> 4) * 1024 + (r ^ 1) * 128 + (lane & 15) * 8);
#pragma unroll 1
        for (int n = 0; n < (1 << 16); n++) {
          const uint32_t all = pv[0][i].x & pv[1][i].x & pv[2][i].x & pv[3][i].x & pv[4][i].x & pv[5][i].x & pv[6][i].x;
          const uint32_t any = pv[0][i].x | pv[1][i].x | pv[2][i].x | pv[3][i].x | pv[4][i].x | pv[5][i].x | pv[6][i].x;
          if (!__any_sync(~0u, (layer ? any : ~all) & 1u)) break;
#pragma unroll
          for (int s = 0; s < 7; s++) pv[s][i] = ldcg2(ps[s] + i * 1024);
        }
        if (i < 2) {
#pragma unroll
          for (int s = 0; s < 7; s++) pv[s][5 + (i & 1)] = ldcg2(ps[s] + (5 + i) * 1024);
        }
#pragma unroll
        for (int jj = 0; jj < 2; jj++) {
          const int j = 2 * i + jj;
          const uint32_t xo = lds32(abuf + off + i * 8192 + jj * 1024), uo = jj ? own.y : own.x;
          float y0 = lo(bx[j]) + lo(xo) + lo(uo), y1 = hi(bx[j]) + hi(xo) + hi(uo);
#pragma unroll
          for (int s = 0; s < 7; s++) { const uint32_t u = jj ? pv[s][i].y : pv[s][i].x; y0 += lo(u); y1 += hi(u); }
          bx[j] = pack(y0, y1);
          if (!layer) *reinterpret_cast<uint32_t*>(dst + (i * 8 + jj) * 1024) = bx[j];
          sm += lo(bx[j]) + hi(bx[j]);
        }
        if (layer) {
          const int sl = (lane & ~3) | ((t & 1) << 1);
          const uint32_t a0 = __shfl_sync(~0u, bx[2 * i], sl), a1 = __shfl_sync(~0u, bx[2 * i], sl + 1);
          const uint32_t b0 = __shfl_sync(~0u, bx[2 * i + 1], sl), b1v = __shfl_sync(~0u, bx[2 * i + 1], sl + 1);
          *reinterpret_cast<uint2*>(dst + i * 128) = t < 2 ? make_uint2(a0, a1) : make_uint2(b0, b1v);
        }
      }
      if (layer) break;
      sm += __shfl_xor_sync(~0u, sm, 1); sm += __shfl_xor_sync(~0u, sm, 2);
      sm *= 1.f / 112.f;
#pragma unroll
      for (int j = 0; j < 14; j++) { const float a = lo(bx[j]) - sm, b = hi(bx[j]) - sm; q = fmaf(a, a, q); q = fmaf(b, b, q); }
      q += __shfl_xor_sync(~0u, q, 1); q += __shfl_xor_sync(~0u, q, 2);
      if (t < 2) gStat[(size_t)(2048 + row0 + r * 8 + g) * 8 + 2 * w + t] = make_float2(sm, q * 0.5f);
      STAMP(11);
      gather(fl + 64, img);
#pragma unroll
      for (int i = 3; i < 7; i++) ring.release((ring.slot + i) % NSLOT, elect);
      STAMP(12);
    }
  }
  STAMP(30);
  if (tid == 0) asm volatile("red.relaxed.gpu.global.add.u32 [%0], 1;" ::"l"(gFlag + FL_DONE * 32) : "memory");
  }
}

typedef CUresult (*EncFn)(CUtensorMap*, CUtensorMapDataType, cuuint32_t, void*, const cuuint64_t*, const cuuint64_t*,
                          const cuuint32_t*, const cuuint32_t*, CUtensorMapInterleave, CUtensorMapSwizzle,
                          CUtensorMapL2promotion, CUtensorMapFloatOOBfill);

void make_map(EncFn enc, CUtensorMap* m, void* p, int rank, uint64_t d0, uint64_t d1, uint64_t d2, uint64_t s1, uint64_t s2,
              uint32_t b0, uint32_t b1, uint32_t b2, CUtensorMapSwizzle sw) {
  cuuint64_t dims[3] = {d0, d1, d2}, strides[2] = {s1, s2};
  cuuint32_t box[3] = {b0, b1, b2}, es[3] = {1, 1, 1};
  enc(m, CU_TENSOR_MAP_DATA_TYPE_BFLOAT16, rank, p, dims, strides, box, es, CU_TENSOR_MAP_INTERLEAVE_NONE, sw,
      CU_TENSOR_MAP_L2_PROMOTION_L2_128B, CU_TENSOR_MAP_FLOAT_OOB_FILL_NONE);
}

}

extern "C" void kernel_launch(void* const* d_in, const int* in_sizes, int n_in, void* d_out, int out_size) {
  static EncFn enc = nullptr;
  if (!enc) {
    cudaDriverEntryPointQueryResult st;
    void* fn = nullptr;
    cudaGetDriverEntryPoint("cuTensorMapEncodeTiled", &fn, cudaEnableDefault, &st);
    enc = (EncFn)fn;
    cudaFuncSetAttribute(fused_kernel, cudaFuncAttributeMaxDynamicSharedMemorySize, SMEM_BYTES);
  }
  CUtensorMap mQKV, mWO, mW1, mW2, mX;
  make_map(enc, &mX, d_in[0], 2, 448, 2048, 1, 896, 0, 64, 64, 1, CU_TENSOR_MAP_SWIZZLE_128B);
  make_map(enc, &mQKV, d_in[1], 3, 448, 448, 3, 2688, 896, 64, 32, 3, CU_TENSOR_MAP_SWIZZLE_128B);
  make_map(enc, &mWO, d_in[3], 2, 448, 448, 1, 896, 0, 64, 112, 1, CU_TENSOR_MAP_SWIZZLE_128B);
  make_map(enc, &mW1, d_in[5], 3, 32, 448, 56, 3584, 64, 32, 32, 7, CU_TENSOR_MAP_SWIZZLE_64B);
  make_map(enc, &mW2, d_in[7], 2, 448, 1792, 1, 896, 0, 64, 112, 1, CU_TENSOR_MAP_SWIZZLE_128B);
  fused_kernel<<<NCTA, 384, SMEM_BYTES, cudaStreamPerThread>>>(
      mQKV, mWO, mW1, mW2, mX, (const __nv_bfloat16*)d_in[2], (const __nv_bfloat16*)d_in[6],
      (const __nv_bfloat16*)d_in[8], (const __nv_bfloat16*)d_in[1], (const __nv_bfloat16*)d_in[3], (const __nv_bfloat16*)d_in[5],
      (const __nv_bfloat16*)d_in[7], (__nv_bfloat16*)d_out);
}
```

```cpp
#include <cuda_runtime.h>
#include <cuda_bf16.h>
#include <cuda.h>
#include <stdint.h>

namespace {

constexpr int DM = 448, NCTA = 128;
constexpr int ABYTES = 57344;
constexpr int SLOT = 14336, NSLOT = 7;
constexpr int OFF_RING = 2 * ABYTES;
constexpr int OFF_WPHI = OFF_RING + NSLOT * SLOT;
constexpr int OFF_B1 = OFF_WPHI + 8192;
constexpr int OFF_CS = OFF_B1 + 896;
constexpr int OFF_BAR = OFF_CS + 1664;
constexpr int SMEM_BYTES = OFF_BAR + 272 + 1024;
constexpr int TILES_PER_LAYER = 46;

__device__ __align__(1024) unsigned char gP[16 * 2 * 8 * 8 * 7168];
__device__ __align__(1024) unsigned char gImg[3 * 32 * ABYTES];
__device__ __align__(1024) float2 gStat[2 * 2048 * 8];
__device__ __align__(1024) float4 gKV[2 * 8 * 2 * 5 * 128];
__device__ __align__(1024) float4 gCS[8 * 16 * 104];
__device__ __align__(128) unsigned gFlag[(2 * 32 * 7 + 32 + 1 + 16) * 32];
#define STAMP(i)

__device__ __forceinline__ uint32_t smem_u32(const void* p) { return (uint32_t)__cvta_generic_to_shared(p); }
__device__ __forceinline__ void mbar_init(uint32_t b, int c) { asm volatile("mbarrier.init.shared::cta.b64 [%0], %1;" ::"r"(b), "r"(c)); }
__device__ __forceinline__ void mbar_expect(uint32_t b, int bytes) { asm volatile("mbarrier.arrive.expect_tx.shared::cta.b64 _, [%0], %1;" ::"r"(b), "r"(bytes) : "memory"); }
__device__ __forceinline__ void mbar_arrive(uint32_t b) { asm volatile("mbarrier.arrive.shared::cta.b64 _, [%0];" ::"r"(b) : "memory"); }
__device__ __forceinline__ void mbar_wait(uint32_t b, int par) {
  uint32_t ok; int n = 0;
#pragma unroll 1
  while (true) {
    asm volatile("{.reg .pred p; mbarrier.try_wait.parity.shared::cta.b64 p, [%1], %2; selp.u32 %0,1,0,p;}" : "=r"(ok) : "r"(b), "r"(par) : "memory");
    if (ok) break;
    if (++n > (1 << 20)) break;
  }
}
__device__ __forceinline__ void flag_wait(const unsigned* f, unsigned target) {
  unsigned v; int n = 0;
#pragma unroll 1
  while (true) {
    asm volatile("ld.acquire.gpu.global.u32 %0, [%1];" : "=r"(v) : "l"(f) : "memory");
    if ((int)(v - target) >= 0) break;
    if (++n > (1 << 18)) break;
  }
}
__device__ __forceinline__ void flag_arrive(unsigned* f) { asm volatile("red.release.gpu.global.add.u32 [%0], 1;" ::"l"(f) : "memory"); }
__device__ __forceinline__ bool elect_one() {
  uint32_t p; asm volatile("{.reg .pred P; elect.sync _|P, 0xffffffff; selp.u32 %0, 1, 0, P;}" : "=r"(p)); return p;
}
__device__ __forceinline__ void fence_async() { asm volatile("fence.proxy.async.global;" ::: "memory"); }
__device__ __forceinline__ void fence_async_smem() { asm volatile("fence.proxy.async.shared::cta;" ::: "memory"); }
template <int ID, int N> __device__ __forceinline__ void bar_sync() { asm volatile("bar.sync %0, %1;" ::"n"(ID), "n"(N) : "memory"); }
__device__ __forceinline__ void bar_wg(int c) { if (c) bar_sync<2, 128>(); else bar_sync<1, 128>(); }
__device__ __forceinline__ void wg_fence() { asm volatile("wgmma.fence.sync.aligned;" ::: "memory"); }
__device__ __forceinline__ void wg_commit() { asm volatile("wgmma.commit_group.sync.aligned;" ::: "memory"); }
template <int N> __device__ __forceinline__ void wg_wait() { asm volatile("wgmma.wait_group.sync.aligned %0;" ::"n"(N) : "memory"); }
template <int N> __device__ __forceinline__ void reg_fence(float (&d)[N]) {
#pragma unroll
  for (int i = 0; i < N; i++) asm volatile("" : "+f"(d[i])::"memory");
}
template <int N> __device__ __forceinline__ void reg_def(float (&d)[N]) {
#pragma unroll
  for (int i = 0; i < N; i++) d[i] = 0.f;
}
__device__ __forceinline__ uint64_t mkdesc(uint32_t addr, uint32_t lbo, uint32_t sbo, uint64_t swz) {
  return (uint64_t)((addr & 0x3FFFF) >> 4) | ((uint64_t)(lbo >> 4) << 16) | ((uint64_t)(sbo >> 4) << 32) | (swz << 62);
}
__device__ __forceinline__ uint32_t pack(float a, float b) {
  uint32_t r; asm("cvt.rn.bf16x2.f32 %0, %1, %2;" : "=r"(r) : "f"(b), "f"(a)); return r;
}
__device__ __forceinline__ uint32_t relu_sq(float a, float b) {
  uint32_t r; asm("{.reg .b32 v; cvt.rn.relu.bf16x2.f32 v, %1, %2; mul.rn.bf16x2 %0, v, v;}" : "=r"(r) : "f"(b), "f"(a)); return r;
}
__device__ __forceinline__ float lo(uint32_t u) { return __uint_as_float(u << 16); }
__device__ __forceinline__ float hi(uint32_t u) { return __uint_as_float(u & 0xFFFF0000u); }
__device__ __forceinline__ float ex2(float x) { float y; asm("ex2.approx.ftz.f32 %0, %1;" : "=f"(y) : "f"(x)); return y; }
__device__ __forceinline__ void stsm4(uint32_t a, uint32_t r0, uint32_t r1, uint32_t r2, uint32_t r3) {
  asm volatile("stmatrix.sync.aligned.m8n8.x4.shared.b16 [%0], {%1,%2,%3,%4};" ::"r"(a), "r"(r0), "r"(r1), "r"(r2), "r"(r3) : "memory");
}
__device__ __forceinline__ void tma3(uint32_t dst, const CUtensorMap* m, int c0, int c1, int c2, uint32_t bar) {
  asm volatile("cp.async.bulk.tensor.3d.shared::cluster.global.mbarrier::complete_tx::bytes [%0], [%1, {%3,%4,%5}], [%2];"
               ::"r"(dst), "l"(m), "r"(bar), "r"(c0), "r"(c1), "r"(c2) : "memory");
}
__device__ __forceinline__ void tma2(uint32_t dst, const CUtensorMap* m, int c0, int c1, uint32_t bar) {
  asm volatile("cp.async.bulk.tensor.2d.shared::cluster.global.mbarrier::complete_tx::bytes [%0], [%1, {%3,%4}], [%2];"
               ::"r"(dst), "l"(m), "r"(bar), "r"(c0), "r"(c1) : "memory");
}
__device__ __forceinline__ uint32_t lds32(uint32_t a) { uint32_t v; asm volatile("ld.shared.u32 %0, [%1];" : "=r"(v) : "r"(a) : "memory"); return v; }
__device__ __forceinline__ void bulk_ld(uint32_t dst, const void* src, int bytes, uint32_t bar) {
  asm volatile("cp.async.bulk.shared::cluster.global.mbarrier::complete_tx::bytes [%0], [%1], %2, [%3];" ::"r"(dst), "l"(src), "r"(bytes), "r"(bar) : "memory");
}
__device__ __forceinline__ uint4 ldcg4(const void* p) {
  uint4 v; asm volatile("ld.global.cg.v4.u32 {%0,%1,%2,%3}, [%4];" : "=r"(v.x), "=r"(v.y), "=r"(v.z), "=r"(v.w) : "l"(p) : "memory"); return v;
}

__device__ __forceinline__ uint2 ldcg2(const void* p) {
  uint2 v; asm volatile("ld.global.cg.v2.u32 {%0,%1}, [%2];" : "=r"(v.x), "=r"(v.y) : "l"(p) : "memory"); return v;
}

__device__ __forceinline__ void mma_ss_184(float (&d)[92], uint64_t da, uint64_t db, int acc) {
  asm volatile("{.reg .pred p; setp.ne.b32 p, %94, 0;\n"
    "wgmma.mma_async.sync.aligned.m64n184k16.f32.bf16.bf16 {%0,%1,%2,%3,%4,%5,%6,%7,%8,%9,%10,%11,%12,%13,%14,%15,%16,%17,%18,%19,%20,%21,%22,%23,%24,%25,%26,%27,%28,%29,%30,%31,%32,%33,%34,%35,%36,%37,%38,%39,%40,%41,%42,%43,%44,%45,%46,%47,%48,%49,%50,%51,%52,%53,%54,%55,%56,%57,%58,%59,%60,%61,%62,%63,%64,%65,%66,%67,%68,%69,%70,%71,%72,%73,%74,%75,%76,%77,%78,%79,%80,%81,%82,%83,%84,%85,%86,%87,%88,%89,%90,%91}, %92, %93, p, 1, 1, 0, 1;}\n"
    : "+f"(d[0]),"+f"(d[1]),"+f"(d[2]),"+f"(d[3]),"+f"(d[4]),"+f"(d[5]),"+f"(d[6]),"+f"(d[7]),"+f"(d[8]),"+f"(d[9]),"+f"(d[10]),"+f"(d[11]),"+f"(d[12]),"+f"(d[13]),"+f"(d[14]),"+f"(d[15]),"+f"(d[16]),"+f"(d[17]),"+f"(d[18]),"+f"(d[19]),"+f"(d[20]),"+f"(d[21]),"+f"(d[22]),"+f"(d[23]),"+f"(d[24]),"+f"(d[25]),"+f"(d[26]),"+f"(d[27]),"+f"(d[28]),"+f"(d[29]),"+f"(d[30]),"+f"(d[31]),"+f"(d[32]),"+f"(d[33]),"+f"(d[34]),"+f"(d[35]),"+f"(d[36]),"+f"(d[37]),"+f"(d[38]),"+f"(d[39]),"+f"(d[40]),"+f"(d[41]),"+f"(d[42]),"+f"(d[43]),"+f"(d[44]),"+f"(d[45]),"+f"(d[46]),"+f"(d[47]),"+f"(d[48]),"+f"(d[49]),"+f"(d[50]),"+f"(d[51]),"+f"(d[52]),"+f"(d[53]),"+f"(d[54]),"+f"(d[55]),"+f"(d[56]),"+f"(d[57]),"+f"(d[58]),"+f"(d[59]),"+f"(d[60]),"+f"(d[61]),"+f"(d[62]),"+f"(d[63]),"+f"(d[64]),"+f"(d[65]),"+f"(d[66]),"+f"(d[67]),"+f"(d[68]),"+f"(d[69]),"+f"(d[70]),"+f"(d[71]),"+f"(d[72]),"+f"(d[73]),"+f"(d[74]),"+f"(d[75]),"+f"(d[76]),"+f"(d[77]),"+f"(d[78]),"+f"(d[79]),"+f"(d[80]),"+f"(d[81]),"+f"(d[82]),"+f"(d[83]),"+f"(d[84]),"+f"(d[85]),"+f"(d[86]),"+f"(d[87]),"+f"(d[88]),"+f"(d[89]),"+f"(d[90]),"+f"(d[91])
    : "l"(da), "l"(db), "r"(acc));
}
__device__ __forceinline__ void mma_ss_224(float (&d)[112], uint64_t da, uint64_t db, int acc) {
  asm volatile("{.reg .pred p; setp.ne.b32 p, %114, 0;\n"
    "wgmma.mma_async.sync.aligned.m64n224k16.f32.bf16.bf16 {%0,%1,%2,%3,%4,%5,%6,%7,%8,%9,%10,%11,%12,%13,%14,%15,%16,%17,%18,%19,%20,%21,%22,%23,%24,%25,%26,%27,%28,%29,%30,%31,%32,%33,%34,%35,%36,%37,%38,%39,%40,%41,%42,%43,%44,%45,%46,%47,%48,%49,%50,%51,%52,%53,%54,%55,%56,%57,%58,%59,%60,%61,%62,%63,%64,%65,%66,%67,%68,%69,%70,%71,%72,%73,%74,%75,%76,%77,%78,%79,%80,%81,%82,%83,%84,%85,%86,%87,%88,%89,%90,%91,%92,%93,%94,%95,%96,%97,%98,%99,%100,%101,%102,%103,%104,%105,%106,%107,%108,%109,%110,%111}, %112, %113, p, 1, 1, 0, 1;}\n"
    : "+f"(d[0]),"+f"(d[1]),"+f"(d[2]),"+f"(d[3]),"+f"(d[4]),"+f"(d[5]),"+f"(d[6]),"+f"(d[7]),"+f"(d[8]),"+f"(d[9]),"+f"(d[10]),"+f"(d[11]),"+f"(d[12]),"+f"(d[13]),"+f"(d[14]),"+f"(d[15]),"+f"(d[16]),"+f"(d[17]),"+f"(d[18]),"+f"(d[19]),"+f"(d[20]),"+f"(d[21]),"+f"(d[22]),"+f"(d[23]),"+f"(d[24]),"+f"(d[25]),"+f"(d[26]),"+f"(d[27]),"+f"(d[28]),"+f"(d[29]),"+f"(d[30]),"+f"(d[31]),"+f"(d[32]),"+f"(d[33]),"+f"(d[34]),"+f"(d[35]),"+f"(d[36]),"+f"(d[37]),"+f"(d[38]),"+f"(d[39]),"+f"(d[40]),"+f"(d[41]),"+f"(d[42]),"+f"(d[43]),"+f"(d[44]),"+f"(d[45]),"+f"(d[46]),"+f"(d[47]),"+f"(d[48]),"+f"(d[49]),"+f"(d[50]),"+f"(d[51]),"+f"(d[52]),"+f"(d[53]),"+f"(d[54]),"+f"(d[55]),"+f"(d[56]),"+f"(d[57]),"+f"(d[58]),"+f"(d[59]),"+f"(d[60]),"+f"(d[61]),"+f"(d[62]),"+f"(d[63]),"+f"(d[64]),"+f"(d[65]),"+f"(d[66]),"+f"(d[67]),"+f"(d[68]),"+f"(d[69]),"+f"(d[70]),"+f"(d[71]),"+f"(d[72]),"+f"(d[73]),"+f"(d[74]),"+f"(d[75]),"+f"(d[76]),"+f"(d[77]),"+f"(d[78]),"+f"(d[79]),"+f"(d[80]),"+f"(d[81]),"+f"(d[82]),"+f"(d[83]),"+f"(d[84]),"+f"(d[85]),"+f"(d[86]),"+f"(d[87]),"+f"(d[88]),"+f"(d[89]),"+f"(d[90]),"+f"(d[91]),"+f"(d[92]),"+f"(d[93]),"+f"(d[94]),"+f"(d[95]),"+f"(d[96]),"+f"(d[97]),"+f"(d[98]),"+f"(d[99]),"+f"(d[100]),"+f"(d[101]),"+f"(d[102]),"+f"(d[103]),"+f"(d[104]),"+f"(d[105]),"+f"(d[106]),"+f"(d[107]),"+f"(d[108]),"+f"(d[109]),"+f"(d[110]),"+f"(d[111])
    : "l"(da), "l"(db), "r"(acc));
}
__device__ __forceinline__ void mma_ss_56(float (&d)[28], uint64_t da, uint64_t db, int acc) {
  asm volatile("{.reg .pred p; setp.ne.b32 p, %30, 0;\n"
    "wgmma.mma_async.sync.aligned.m64n56k16.f32.bf16.bf16 {%0,%1,%2,%3,%4,%5,%6,%7,%8,%9,%10,%11,%12,%13,%14,%15,%16,%17,%18,%19,%20,%21,%22,%23,%24,%25,%26,%27}, %28, %29, p, 1, 1, 0, 1;}\n"
    : "+f"(d[0]),"+f"(d[1]),"+f"(d[2]),"+f"(d[3]),"+f"(d[4]),"+f"(d[5]),"+f"(d[6]),"+f"(d[7]),"+f"(d[8]),"+f"(d[9]),"+f"(d[10]),"+f"(d[11]),"+f"(d[12]),"+f"(d[13]),"+f"(d[14]),"+f"(d[15]),"+f"(d[16]),"+f"(d[17]),"+f"(d[18]),"+f"(d[19]),"+f"(d[20]),"+f"(d[21]),"+f"(d[22]),"+f"(d[23]),"+f"(d[24]),"+f"(d[25]),"+f"(d[26]),"+f"(d[27])
    : "l"(da), "l"(db), "r"(acc));
}
__device__ __forceinline__ void mma_rs_56(float (&d)[28], uint32_t a0, uint32_t a1, uint32_t a2, uint32_t a3, uint64_t db, int acc) {
  asm volatile("{.reg .pred p; setp.ne.b32 p, %33, 0;\n"
    "wgmma.mma_async.sync.aligned.m64n56k16.f32.bf16.bf16 {%0,%1,%2,%3,%4,%5,%6,%7,%8,%9,%10,%11,%12,%13,%14,%15,%16,%17,%18,%19,%20,%21,%22,%23,%24,%25,%26,%27}, {%28,%29,%30,%31}, %32, p, 1, 1, 1;}\n"
    : "+f"(d[0]),"+f"(d[1]),"+f"(d[2]),"+f"(d[3]),"+f"(d[4]),"+f"(d[5]),"+f"(d[6]),"+f"(d[7]),"+f"(d[8]),"+f"(d[9]),"+f"(d[10]),"+f"(d[11]),"+f"(d[12]),"+f"(d[13]),"+f"(d[14]),"+f"(d[15]),"+f"(d[16]),"+f"(d[17]),"+f"(d[18]),"+f"(d[19]),"+f"(d[20]),"+f"(d[21]),"+f"(d[22]),"+f"(d[23]),"+f"(d[24]),"+f"(d[25]),"+f"(d[26]),"+f"(d[27])
    : "r"(a0), "r"(a1), "r"(a2), "r"(a3), "l"(db), "r"(acc));
}
__device__ __forceinline__ void mma_ss_64t(float (&d)[32], uint64_t da, uint64_t db, int acc) {
  asm volatile("{.reg .pred p; setp.ne.b32 p, %34, 0;\n"
    "wgmma.mma_async.sync.aligned.m64n64k16.f32.bf16.bf16 {%0,%1,%2,%3,%4,%5,%6,%7,%8,%9,%10,%11,%12,%13,%14,%15,%16,%17,%18,%19,%20,%21,%22,%23,%24,%25,%26,%27,%28,%29,%30,%31}, %32, %33, p, 1, 1, 1, 1;}\n"
    : "+f"(d[0]),"+f"(d[1]),"+f"(d[2]),"+f"(d[3]),"+f"(d[4]),"+f"(d[5]),"+f"(d[6]),"+f"(d[7]),"+f"(d[8]),"+f"(d[9]),"+f"(d[10]),"+f"(d[11]),"+f"(d[12]),"+f"(d[13]),"+f"(d[14]),"+f"(d[15]),"+f"(d[16]),"+f"(d[17]),"+f"(d[18]),"+f"(d[19]),"+f"(d[20]),"+f"(d[21]),"+f"(d[22]),"+f"(d[23]),"+f"(d[24]),"+f"(d[25]),"+f"(d[26]),"+f"(d[27]),"+f"(d[28]),"+f"(d[29]),"+f"(d[30]),"+f"(d[31])
    : "l"(da), "l"(db), "r"(acc));
}
__device__ __forceinline__ void mma_rs_64(float (&d)[32], uint32_t a0, uint32_t a1, uint32_t a2, uint32_t a3, uint64_t db, int acc) {
  asm volatile("{.reg .pred p; setp.ne.b32 p, %37, 0;\n"
    "wgmma.mma_async.sync.aligned.m64n64k16.f32.bf16.bf16 {%0,%1,%2,%3,%4,%5,%6,%7,%8,%9,%10,%11,%12,%13,%14,%15,%16,%17,%18,%19,%20,%21,%22,%23,%24,%25,%26,%27,%28,%29,%30,%31}, {%32,%33,%34,%35}, %36, p, 1, 1, 1;}\n"
    : "+f"(d[0]),"+f"(d[1]),"+f"(d[2]),"+f"(d[3]),"+f"(d[4]),"+f"(d[5]),"+f"(d[6]),"+f"(d[7]),"+f"(d[8]),"+f"(d[9]),"+f"(d[10]),"+f"(d[11]),"+f"(d[12]),"+f"(d[13]),"+f"(d[14]),"+f"(d[15]),"+f"(d[16]),"+f"(d[17]),"+f"(d[18]),"+f"(d[19]),"+f"(d[20]),"+f"(d[21]),"+f"(d[22]),"+f"(d[23]),"+f"(d[24]),"+f"(d[25]),"+f"(d[26]),"+f"(d[27]),"+f"(d[28]),"+f"(d[29]),"+f"(d[30]),"+f"(d[31])
    : "r"(a0), "r"(a1), "r"(a2), "r"(a3), "l"(db), "r"(acc));
}

__device__ __forceinline__ void dual_softmax(const float (&p)[28], uint32_t (&phi)[4][7]) {
  constexpr float L2E = 1.4426950408889634f;
#pragma unroll
  for (int i = 0; i < 4; i++) {
    float mx = p[i], mn = p[i];
#pragma unroll
    for (int j = 1; j < 7; j++) { mx = fmaxf(mx, p[4 * j + i]); mn = fminf(mn, p[4 * j + i]); }
    mx = fmaxf(mx, __shfl_xor_sync(~0u, mx, 1)); mn = fminf(mn, __shfl_xor_sync(~0u, mn, 1));
    mx = fmaxf(mx, __shfl_xor_sync(~0u, mx, 2)); mn = fminf(mn, __shfl_xor_sync(~0u, mn, 2));
    float a[7], b[7], sa = 0.f, sb = 0.f;
    const float mxl = mx * L2E, mnl = mn * L2E;
#pragma unroll
    for (int j = 0; j < 7; j++) {
      a[j] = ex2(fmaf(p[4 * j + i], L2E, -mxl)); b[j] = ex2(fmaf(p[4 * j + i], -L2E, mnl));
      sa += a[j]; sb += b[j];
    }
    sa += __shfl_xor_sync(~0u, sa, 1); sb += __shfl_xor_sync(~0u, sb, 1);
    sa += __shfl_xor_sync(~0u, sa, 2); sb += __shfl_xor_sync(~0u, sb, 2);
    const float ra = __fdividef(1.f, sa), rb = __fdividef(1.f, sb);
#pragma unroll
    for (int j = 0; j < 7; j++) phi[i][j] = pack(a[j] * ra, b[j] * rb);
  }
}

struct Ring {
  uint32_t full, empty, base; int slot, par;
  __device__ __forceinline__ void uniform() { slot = __shfl_sync(~0u, slot, 0); par = __shfl_sync(~0u, par, 0); }
  __device__ __forceinline__ uint32_t acquire() { mbar_wait(full + slot * 8, par); return base + slot * SLOT; }
  __device__ __forceinline__ int advance() { int s = slot; if (++slot == NSLOT) { slot = 0; par ^= 1; } return s; }
  __device__ __forceinline__ void release(int s, bool elect) { if (elect) mbar_arrive(empty + s * 8); }
};
constexpr int UNR = 14;
constexpr int FL_KV = 448, FL_CS = FL_KV + 16, FL_DONE = FL_KV + 32;

__global__ void __launch_bounds__(384, 1)
fused_kernel(const __grid_constant__ CUtensorMap mQKV, const __grid_constant__ CUtensorMap mWO,
             const __grid_constant__ CUtensorMap mW1, const __grid_constant__ CUtensorMap mW2,
             const __grid_constant__ CUtensorMap mX, const __nv_bfloat16* __restrict__ wphi,
             const __nv_bfloat16* __restrict__ b1, const __nv_bfloat16* __restrict__ b2,
             const __nv_bfloat16* __restrict__ wqkv, const __nv_bfloat16* __restrict__ wo, const __nv_bfloat16* __restrict__ w1,
             const __nv_bfloat16* __restrict__ w2, __nv_bfloat16* __restrict__ out) {
  extern __shared__ unsigned char smem_raw[];
  const uint32_t sb = (smem_u32(smem_raw) + 1023) & ~1023u;
  unsigned char* sg = smem_raw + (sb - smem_u32(smem_raw));
  const int tid = threadIdx.x, lane = tid & 31;
  const int G = blockIdx.x >> 3, r = blockIdx.x & 7;
  const uint32_t barFull = sb + OFF_BAR, barEmpty = barFull + 56, barA = barEmpty + 56, barCS = barA + 112, barX = barCS + 16;
  const int warp = __shfl_sync(~0u, tid >> 5, 0);
  uint32_t wv[7] = {}, bv = 0;
  if (warp < 8) {
#pragma unroll
    for (int i = 0; i < 7; i++)
      wv[i] = __ldg(reinterpret_cast<const unsigned short*>(wphi) + (56 * r + i * 8 + warp) * 28 + min(lane, 27));
    bv = __ldg(reinterpret_cast<const unsigned short*>(b1) + 224 * r + min(tid, 223));
  }
  if (lane == 0) {
    if (warp >= 10) {
      const int cc = warp - 10;
      mbar_init(barX + cc * 8, 1);
      fence_async_smem();
      mbar_expect(barX + cc * 8, ABYTES);
#pragma unroll 1
      for (int k = 0; k < 7; k++) tma2(sb + cc * ABYTES + k * 8192, &mX, 64 * k, G * 128 + 64 * cc, barX + cc * 8);
    } else if (warp < 7) { mbar_init(barFull + warp * 8, 1); mbar_init(barEmpty + warp * 8, 2); mbar_init(barA + warp * 8, 1); mbar_init(barA + 56 + warp * 8, 1); }
    else if (warp < 9) { mbar_init(barCS + (warp - 7) * 8, 64); if (warp == 7) mbar_init(barX + 16, 1); }
    else
      asm volatile("cp.async.bulk.prefetch.L2.global [%0], %1;" ::"l"((const char*)wqkv + blockIdx.x * 9408), "r"(9408) : "memory");
    asm volatile("fence.mbarrier_init.release.cluster;" ::: "memory");
  }
  if (tid < 192) reinterpret_cast<float*>(sg + OFF_CS)[tid] = 0.f;
  __syncthreads();
  const int wgid = warp >> 2;
  if (wgid == 2) {
    asm volatile("setmaxnreg.dec.sync.aligned.u32 40;");
    if (warp == 8) {
      int slot = 0, par = 1;
#pragma unroll 1
      for (int it = 0; it < 2 * TILES_PER_LAYER; it++) {
        const int i = it >= TILES_PER_LAYER ? it - TILES_PER_LAYER : it;
        mbar_wait(barEmpty + slot * 8, par);
        const uint32_t dst = sb + OFF_RING + slot * SLOT, fb = barFull + slot * 8;
        if (elect_one()) {
          mbar_expect(fb, i < 14 ? 12288 : SLOT);
          if (i < 14) tma3(dst, &mQKV, 56 * r, 32 * i, 0, fb);
          else if (i < 18) tma2(dst, &mWO, 56 * r, 112 * (i - 14), fb);
          else if (i < 32) tma3(dst, &mW1, 0, 32 * (i - 18), 7 * r, fb);
          else tma2(dst, &mW2, 64 * ((i - 32) >> 1), 224 * r + 112 * (i & 1), fb);
        }
        if (++slot == NSLOT) { slot = 0; par ^= 1; }
      }
    } else if (warp == 11) {
      unsigned ep;
      asm volatile("ld.relaxed.gpu.global.u32 %0, [%1];" : "=r"(ep) : "l"(gFlag + FL_DONE * 32) : "memory");
#pragma unroll 1
      for (int layer = 0; layer < 2; layer++) {
        bar_sync<4, 288>();
        if (lane == 0) {
          flag_arrive(gFlag + (FL_KV + layer * 8 + r) * 32);
          flag_wait(gFlag + (FL_KV + layer * 8 + r) * 32, (ep / NCTA + 1) * 16);
          mbar_arrive(barX + 16);
        }
        __syncwarp();
      }
    } else {
      unsigned ep;
      asm volatile("ld.relaxed.gpu.global.u32 %0, [%1];" : "=r"(ep) : "l"(gFlag + FL_DONE * 32) : "memory");
      const int idx = tid - 288;
      ep = (ep / NCTA + 1) * 2;
      if (G == 0) {
#pragma unroll 1
        for (int i = idx; i < 2 * 1280; i += 64) gKV[((i >= 1280) * 7 + r) * 1280 + i] = make_float4(0.f, 0.f, 0.f, 0.f);
        __syncwarp();
        if (lane == 0) flag_arrive(gFlag + (FL_CS + r) * 32);
      }
      mbar_wait(barFull + 48, 0);
      if (idx < 3) {
        const char* pf = idx ? (idx == 1 ? (const char*)w1 : (const char*)w2) + blockIdx.x * 12544 : (const char*)wo + blockIdx.x * 3136;
        asm volatile("cp.async.bulk.prefetch.L2.global [%0], %1;" ::"l"(pf), "r"(idx ? 12544 : 3136) : "memory");
      }
      if (lane == 0) flag_wait(gFlag + (FL_CS + r) * 32, ep);
      __syncwarp();
      mbar_arrive(barCS);
#pragma unroll 1
      for (int ps = 0; ps < 4; ps++) {
        const int ch = min(ps * 16 + (idx >> 2), 48), p = ch / 7, k0 = G * 28 + (idx & 3) * 7;
        const uint4* src = ch >= 21 ? reinterpret_cast<const uint4*>(w1 + (size_t)k0 * 1792 + 224 * r) + (ch - 21)
                                    : reinterpret_cast<const uint4*>(wqkv + (size_t)k0 * 1344 + p * 448 + 56 * r) + (ch - 7 * p);
        uint4 cu[7];
#pragma unroll
        for (int i = 0; i < 7; i++) cu[i] = __ldg(src + i * (ch >= 21 ? 224 : 168));
        float s[8] = {};
#pragma unroll
        for (int i = 0; i < 7; i++) { s[0] += lo(cu[i].x); s[1] += hi(cu[i].x); s[2] += lo(cu[i].y); s[3] += hi(cu[i].y); s[4] += lo(cu[i].z); s[5] += hi(cu[i].z); s[6] += lo(cu[i].w); s[7] += hi(cu[i].w); }
#pragma unroll
        for (int i = 0; i < 8; i++) { s[i] += __shfl_xor_sync(~0u, s[i], 1); s[i] += __shfl_xor_sync(~0u, s[i], 2); }
        if ((idx & 3) < 2) gCS[(r * 16 + G) * 104 + (ch + min(p, 3)) * 2 + (idx & 1)] = (idx & 1) ? make_float4(s[4], s[5], s[6], s[7]) : make_float4(s[0], s[1], s[2], s[3]);
      }
      __syncwarp();
      if (lane == 0) { flag_arrive(gFlag + (FL_CS + 8 + r) * 32); flag_wait(gFlag + (FL_CS + 8 + r) * 32, ep * 16); }
      __syncwarp();
#pragma unroll 1
      for (int j = idx; j < 208; j += 64) {
        float2 a = make_float2(0.f, 0.f);
#pragma unroll 8
        for (int i = 0; i < 16; i++) { const float2 v = __ldcg(reinterpret_cast<const float2*>(gCS + (r * 16 + i) * 104) + j); a.x += v.x; a.y += v.y; }
        reinterpret_cast<float2*>(sg + OFF_CS)[j] = a;
      }
      mbar_arrive(barCS + 8);
    }
  } else {
  asm volatile("setmaxnreg.inc.sync.aligned.u32 232;");
  const int c = wgid, w = warp & 3, g = lane >> 2, t = lane & 3;
  int elect_i = (tid & 127) == 0;
  asm volatile("" : "+r"(elect_i));
  const bool elect = elect_i;
  const uint32_t abuf = sb + c * ABYTES, barAc = barA + c * 56;
  const int row0 = G * 128 + c * 64;
  unsigned epoch;
  asm volatile("ld.relaxed.gpu.global.u32 %0, [%1];" : "=r"(epoch) : "l"(gFlag + FL_DONE * 32) : "memory");
  STAMP(24);
  float mean[2], rstd[2] = {0.f, 0.f};
  uint4 su[2] = {};
  uint32_t xs[7][2];
  {
#pragma unroll
    for (int i = 0; i < 8; i++) {
      const int k = i * 8 + (tid >> 5);
      *reinterpret_cast<uint32_t*>(sg + OFF_WPHI + k * 128 + ((g ^ (k & 7)) << 4) + t * 4) = (i < 7 && lane < 28) ? wv[i % 7] << (k >= 28 ? 16 : 0) : 0u;
    }
    if (tid < 224) reinterpret_cast<uint32_t*>(sg + OFF_B1)[tid] = bv << 16;
    mbar_wait(barX + c * 8, 0);
    STAMP(25);
#pragma unroll
    for (int j = 0; j < 7; j++) {
      const int ci = 7 * r + j;
      const uint32_t a = abuf + (ci >> 3) * 8192 + (w * 16 + g) * 128 + (((ci & 7) ^ g) << 4) + t * 4;
      xs[j][0] = lds32(a); xs[j][1] = lds32(a + 1024);
    }
    __syncwarp();
#pragma unroll 1
    for (int hh = 0; hh < 2; hh++) {
      uint4* p = reinterpret_cast<uint4*>(sg + c * ABYTES + (w * 16 + hh * 8 + g) * 128) + t;
      uint4 v[14];
#pragma unroll
      for (int k = 0; k < 14; k++) v[k] = p[(k >> 1) * 512 + ((k ^ g) & 1) * 4];
      float a8[8] = {};
#pragma unroll
      for (int k = 0; k < 14; k++) {
        const uint32_t e[4] = {v[k].x, v[k].y, v[k].z, v[k].w};
#pragma unroll
        for (int z = 0; z < 4; z++) { a8[2 * z] += lo(e[z]); a8[2 * z + 1] += hi(e[z]); }
      }
      float sm = ((a8[0] + a8[1]) + (a8[2] + a8[3])) + ((a8[4] + a8[5]) + (a8[6] + a8[7]));
      sm += __shfl_xor_sync(~0u, sm, 1); sm += __shfl_xor_sync(~0u, sm, 2);
      sm *= 1.f / DM;
#pragma unroll
      for (int k = 0; k < 14; k++) {
        uint32_t e[4] = {v[k].x, v[k].y, v[k].z, v[k].w};
#pragma unroll
        for (int z = 0; z < 4; z++) {
          const float a = lo(e[z]) - sm, b = hi(e[z]) - sm;
          a8[2 * z] = fmaf(a, a, k ? a8[2 * z] : 0.f); a8[2 * z + 1] = fmaf(b, b, k ? a8[2 * z + 1] : 0.f);
          e[z] = pack(a, b);
        }
        p[(k >> 1) * 512 + ((k ^ g) & 1) * 4] = make_uint4(e[0], e[1], e[2], e[3]);
      }
      float q = ((a8[0] + a8[1]) + (a8[2] + a8[3])) + ((a8[4] + a8[5]) + (a8[6] + a8[7]));
      q += __shfl_xor_sync(~0u, q, 1); q += __shfl_xor_sync(~0u, q, 2);
      rstd[1] = rsqrtf(q * (1.f / DM) + 1e-5f);
      if (hh == 0) rstd[0] = rstd[1];
    }
    fence_async_smem();
    bar_sync<3, 256>();
    epoch = epoch / NCTA + 1;
    mean[0] = mean[1] = 0.f;
  }
  STAMP(0);
  Ring ring{barFull, barEmpty, sb + OFF_RING, 0, 0};
  int apar = 1;
  const uint32_t stsm_off = (w * 16 + ((lane >> 3) & 1) * 8 + (lane & 7)) * 128;
  const uint32_t stsm_hi = lane >> 4;
  const uint64_t dA = mkdesc(abuf, 1024, 128, 0);

  auto gather = [&](unsigned* fl, const unsigned char* img) {
    bar_wg(c);
    if (w == 0) {
      if (elect_one()) {
        flag_arrive(fl);
        flag_wait(fl, epoch * 8);
        fence_async();
#pragma unroll
        for (int k = 0; k < 7; k++) { mbar_expect(barAc + k * 8, 8192); bulk_ld(abuf + k * 8192, img + k * 8192, 8192, barAc + k * 8); }
      }
      __syncwarp();
    }
    apar ^= 1;
  };
  auto slice_off = [&](int j, int hh) -> uint32_t {
    return (7 * r + j) * 1024 + (w * 2 + hh) * 128 + lane * 4;
  };
  auto load_stats = [&](const float2* st) {
    mbar_wait(barAc, apar);
#pragma unroll
    for (int hh = 0; hh < 2; hh++) su[hh] = ldcg4(st + (size_t)(row0 + w * 16 + hh * 8 + g) * 8 + 2 * t);
  };
  auto finish_stats = [&]() {
#pragma unroll
    for (int hh = 0; hh < 2; hh++) {
      const float m0 = __uint_as_float(su[hh].x), m1 = __uint_as_float(su[hh].z);
      float m = m0 + m1;
      m += __shfl_xor_sync(~0u, m, 1); m += __shfl_xor_sync(~0u, m, 2);
      m *= 0.125f;
      float q = __uint_as_float(su[hh].y) + __uint_as_float(su[hh].w) + 56.f * ((m0 - m) * (m0 - m) + (m1 - m) * (m1 - m));
      q += __shfl_xor_sync(~0u, q, 1); q += __shfl_xor_sync(~0u, q, 2);
      mean[hh] = m; rstd[hh] = rsqrtf(q * (1.f / DM) + 1e-5f);
    }
  };

#pragma unroll 1
  for (int lyr = 0; lyr < 2; lyr++) {
    const int layer = __shfl_sync(~0u, lyr, 0);
    unsigned* const fl = gFlag + (layer * 32 + G * 2 + c) * 7 * 32;
    uint32_t phiq[4][7];
    {
      float acc[92]; reg_def(acc);
      int prev = 0, prev2 = 0;
      ring.uniform();
      const uint64_t dQ = layer ? dA : mkdesc(abuf, 16, 1024, 1);
      const int kstep = layer ? 128 : 2;
      if (layer) load_stats(gStat + 2048 * 8);
#pragma unroll UNR
      for (int st = 0; st < 14; st++) {
        if (!(st & 1) && layer) mbar_wait(barAc + (st >> 1) * 8, apar);
        const uint64_t da = dQ + (st >> 1) * 512 + (st & 1) * 2 * kstep, db = mkdesc(ring.acquire(), 4096, 1024, 1);
        wg_fence();
        mma_ss_184(acc, da, db, 1);
        mma_ss_184(acc, da + kstep, db + 128, 1);
        wg_commit();
        if (st > 1) { wg_wait<2>(); ring.release(prev2, elect); }
        prev2 = prev; prev = ring.advance();
      }
      if (layer) {
        finish_stats();
#pragma unroll
        for (int j = 0; j < 7; j++) { xs[j][0] = lds32(abuf + slice_off(j, 0)); xs[j][1] = lds32(abuf + slice_off(j, 1)); }
      }
      wg_wait<0>(); reg_fence(acc);
      ring.release(prev2, elect); ring.release(prev, elect);
      STAMP(1 + layer * 12);
      uint32_t f[3][14];
      auto frags = [&](const int p0, const int p1) {
        const float2* cs = reinterpret_cast<const float2*>(sg + OFF_CS) + t;
        const float mr0 = -mean[0] * rstd[0], mr1 = -mean[1] * rstd[1];
#pragma unroll
        for (int p = p0; p < p1; p++)
#pragma unroll
          for (int j = 0; j < 7; j++) {
            const float2 s = cs[p * 32 + j * 4];
            const int b = p * 32 + j * 4;
            f[p][2 * j] = pack(fmaf(acc[b], rstd[0], s.x * mr0), fmaf(acc[b + 1], rstd[0], s.y * mr0));
            f[p][2 * j + 1] = pack(fmaf(acc[b + 2], rstd[1], s.x * mr1), fmaf(acc[b + 3], rstd[1], s.y * mr1));
          }
      };
      frags(1, 2);
      float pk[28]; reg_def(pk);
      const uint64_t dW = mkdesc(sb + OFF_WPHI, 4096, 1024, 1);
      wg_fence();
#pragma unroll
      for (int s = 0; s < 4; s++) {
        mma_rs_56(pk, f[1][4 * s], f[1][4 * s + 1], s < 3 ? f[1][(4 * s + 2) % 14] : 0u, s < 3 ? f[1][(4 * s + 3) % 14] : 0u, dW + s * 128, s);
      }
      wg_commit();
      frags(2, 3);
      bar_wg(c);
      const uint32_t srow = abuf + stsm_off, ones = t == 0 ? 0x3F803F80u : 0u;
#pragma unroll
      for (int jp = 0; jp < 4; jp++)
        stsm4(srow + 16384 + (((2 * jp + stsm_hi) ^ (lane & 7)) << 4), f[2][4 * jp], f[2][4 * jp + 1],
              jp < 3 ? f[2][(4 * jp + 2) % 14] : ones, jp < 3 ? f[2][(4 * jp + 3) % 14] : ones);
      wg_wait<0>(); reg_fence(pk);
      {
        dual_softmax(pk, phiq);
#pragma unroll
        for (int e = 0; e < 2; e++)
#pragma unroll
          for (int jp = 0; jp < 4; jp++)
            stsm4(srow + e * 8192 + (((2 * jp + stsm_hi) ^ (lane & 7)) << 4), phiq[e][2 * jp], phiq[2 + e][2 * jp],
                  jp < 3 ? phiq[e][(2 * jp + 1) % 7] : 0u, jp < 3 ? phiq[2 + e][(2 * jp + 1) % 7] : 0u);
        fence_async_smem();
        bar_sync<3, 256>();
        float kv[32], kw[32]; reg_def(kv); reg_def(kw);
        const uint64_t dP = mkdesc(sb + c * 8192, 4096, 1024, 1), dV = mkdesc(sb + 16384, 4096, 1024, 1);
        wg_fence();
#pragma unroll
        for (int s = 0; s < 4; s++) { mma_ss_64t(kv, dP + s * 128, dV + s * 128, s); mma_ss_64t(kw, dP + ABYTES / 16 + s * 128, dV + ABYTES / 16 + s * 128, s); }
        wg_commit();
        mbar_wait(barCS, 0);
        wg_wait<0>(); reg_fence(kv); reg_fence(kw);
#pragma unroll
        for (int i = 0; i < 32; i++) kv[i] += kw[i];
        float4* kvg = gKV + ((layer * 8 + r) * 2 + c) * 640 + (tid & 127);
#pragma unroll
        for (int i = 0; i < 5; i++) {
          float v0, v1, v2, v3;
          if (i == 4) { v0 = kv[28]; v1 = kv[29]; v2 = kv[30]; v3 = kv[31]; }
          else { v0 = c ? kv[12 + 4 * i] : kv[4 * i]; v1 = c ? kv[13 + 4 * i] : kv[1 + 4 * i]; v2 = c ? kv[14 + 4 * i] : kv[2 + 4 * i]; v3 = c ? kv[15 + 4 * i] : kv[3 + 4 * i]; }
          const bool use = i == 4 ? t == 0 : (i == 0 ? (c == 0 || t >= 2) : (i == 3 ? (c == 1 || t < 2) : true));
          if (use) asm volatile("red.relaxed.gpu.global.add.v4.f32 [%0], {%1,%2,%3,%4};" ::"l"(kvg + i * 128), "f"(v0), "f"(v1), "f"(v2), "f"(v3) : "memory");
        }
        asm volatile("bar.arrive 4, 288;" ::: "memory");
        STAMP(2 + layer * 12);
      }
      frags(0, 1);
      float pq[28]; reg_def(pq);
      wg_fence();
#pragma unroll
      for (int s = 0; s < 4; s++)
        mma_rs_56(pq, f[0][4 * s], f[0][4 * s + 1], s < 3 ? f[0][(4 * s + 2) % 14] : 0u, s < 3 ? f[0][(4 * s + 3) % 14] : 0u, dW + s * 128, s);
      wg_commit();
      wg_wait<0>(); reg_fence(pq);
      dual_softmax(pq, phiq);
    }
    {
      mbar_wait(barX + 16, layer);
      STAMP(3 + layer * 12);
      const float4* kvg = gKV + (layer * 8 + r) * 1280 + c * 640 + (tid & 127);
      uint4 kk[5];
#pragma unroll
      for (int i = 0; i < 5; i++) kk[i] = ldcg4(kvg + i * 128);
      uint32_t f[5][2];
#pragma unroll
      for (int i = 0; i < 5; i++) { f[i][0] = pack(__uint_as_float(kk[i].x), __uint_as_float(kk[i].y)); f[i][1] = pack(__uint_as_float(kk[i].z), __uint_as_float(kk[i].w)); }
      const uint32_t zm = c ? 0xFFFF0000u : 0xFFFFu;
      const uint32_t srow = abuf + 24576 + stsm_off;
#pragma unroll
      for (int jp = 0; jp < 4; jp++) {
        uint32_t v[2][2];
#pragma unroll
        for (int u = 0; u < 2; u++) {
          const int j = 2 * jp + u;
#pragma unroll
          for (int hh = 0; hh < 2; hh++) v[u][hh] = j == 7 ? f[4][hh] & zm : (c ? (j >= 3 ? f[(j + 2) % 5][hh] : 0u) : (j < 4 ? f[j % 5][hh] : 0u));
        }
        stsm4(srow + (((2 * jp + stsm_hi) ^ (lane & 7)) << 4), v[0][0], v[0][1], v[1][0], v[1][1]);
      }
      fence_async_smem();
      bar_sync<3, 256>();
      float num[32], nub[32]; reg_def(num); reg_def(nub);
      const uint64_t dK = mkdesc(sb + 24576, 4096, 1024, 1);
      wg_fence();
#pragma unroll
      for (int s = 0; s < 4; s++) {
        mma_rs_64(num, phiq[0][2 * s], phiq[2][2 * s], s < 3 ? phiq[0][(2 * s + 1) % 7] : 0u, s < 3 ? phiq[2][(2 * s + 1) % 7] : 0u, dK + s * 128, s);
        mma_rs_64(nub, phiq[1][2 * s], phiq[3][2 * s], s < 3 ? phiq[1][(2 * s + 1) % 7] : 0u, s < 3 ? phiq[3][(2 * s + 1) % 7] : 0u, dK + ABYTES / 16 + s * 128, s);
      }
      wg_commit();
      wg_wait<0>(); reg_fence(num); reg_fence(nub);
      bar_sync<3, 256>();
#pragma unroll
      for (int i = 12; i < 32; i++) num[i] += nub[i];
      float rd[4];
#pragma unroll
      for (int i = 0; i < 4; i++) rd[i] = __fdividef(1.f, __shfl_sync(~0u, num[28 + i], lane & ~3) + 1e-6f);
      unsigned char* img = gImg + (size_t)(G * 2 + c) * ABYTES;
#pragma unroll
      for (int j = 0; j < 7; j++) {
        const bool hb = j > 3 || (j == 3 && t >= 2);
        const float r0 = hb ? rd[1] : rd[0], r1 = hb ? rd[3] : rd[2];
        *reinterpret_cast<uint32_t*>(img + slice_off(j, 0)) = pack(num[4 * j] * r0, num[4 * j + 1] * r0);
        *reinterpret_cast<uint32_t*>(img + slice_off(j, 1)) = pack(num[4 * j + 2] * r1, num[4 * j + 3] * r1);
      }
      STAMP(4 + layer * 12);
      gather(fl, img);
      STAMP(5 + layer * 12);
    }
    {
      float acc[28], acc2[28]; reg_def(acc); reg_def(acc2); reg_fence(acc); reg_fence(acc2);
      int sl[4];
      ring.uniform();
#pragma unroll
      for (int st = 0; st < 4; st++) {
        const uint64_t db = mkdesc(ring.acquire(), 4096, 1024, 1);
        sl[st] = ring.advance();
#pragma unroll
        for (int s = 0; s < 7; s++) {
          const int ks = st * 7 + s;
          if (!(ks & 3)) mbar_wait(barAc + (ks >> 2) * 8, apar);
          if (!(ks & 3) || !s) wg_fence();
          if (ks & 1) mma_ss_56(acc2, dA + ks * 128, db + s * 128, ks > 1); else mma_ss_56(acc, dA + ks * 128, db + s * 128, ks > 1);
        }
        wg_commit();
      }
      wg_wait<0>(); reg_fence(acc); reg_fence(acc2);
      unsigned char* img = gImg + (size_t)(32 + G * 2 + c) * ABYTES;
#pragma unroll
      for (int hh = 0; hh < 2; hh++) {
        float s = 0.f, q = 0.f;
#pragma unroll
        for (int j = 0; j < 7; j++) {
          xs[j][hh] = pack(lo(xs[j][hh]) + (acc[4 * j + 2 * hh] + acc2[4 * j + 2 * hh]), hi(xs[j][hh]) + (acc[4 * j + 2 * hh + 1] + acc2[4 * j + 2 * hh + 1]));
          *reinterpret_cast<uint32_t*>(img + slice_off(j, hh)) = xs[j][hh];
          s += lo(xs[j][hh]) + hi(xs[j][hh]);
        }
        s += __shfl_xor_sync(~0u, s, 1); s += __shfl_xor_sync(~0u, s, 2);
        s *= 1.f / 56.f;
#pragma unroll
        for (int j = 0; j < 7; j++) { const float a = lo(xs[j][hh]) - s, b = hi(xs[j][hh]) - s; q = fmaf(a, a, q); q = fmaf(b, b, q); }
        q += __shfl_xor_sync(~0u, q, 1); q += __shfl_xor_sync(~0u, q, 2);
        if (t == 0) gStat[(size_t)(row0 + w * 16 + hh * 8 + g) * 8 + r] = make_float2(s, q);
      }
#pragma unroll
      for (int j = 0; j < 7; j++) xs[j][0] = xs[j][1] = 0u;
      STAMP(6 + layer * 12);
      gather(fl + 32, img);
#pragma unroll
      for (int st = 0; st < 4; st++) ring.release(sl[st], elect);
      STAMP(7 + layer * 12);
    }
    {
      uint32_t hf[28][2];
      {
        float acc[112]; reg_def(acc);
        int prev = 0, prev2 = 0;
        load_stats(gStat);
        ring.uniform();
#pragma unroll UNR
        for (int st = 0; st < 14; st++) {
          if (!(st & 1)) mbar_wait(barAc + (st >> 1) * 8, apar);
          const uint64_t da = dA + st * 256, db = mkdesc(ring.acquire(), 2048, 512, 2);
          wg_fence();
          mma_ss_224(acc, da, db, 1);
          mma_ss_224(acc, da + 128, db + 64, 1);
          wg_commit();
          if (st > 1) { wg_wait<2>(); ring.release(prev2, elect); }
          prev2 = prev; prev = ring.advance();
        }
        finish_stats();
        mbar_wait(barCS + 8, 0);
        wg_wait<0>(); reg_fence(acc);
        ring.release(prev2, elect); ring.release(prev, elect);
        STAMP(8 + layer * 12);
        const float2* bs = reinterpret_cast<const float2*>(sg + OFF_B1) + t;
        const float2* cs = reinterpret_cast<const float2*>(sg + OFF_CS + 768) + t;
        const float mr0 = -mean[0] * rstd[0], mr1 = -mean[1] * rstd[1];
#pragma unroll
        for (int j = 0; j < 28; j++) {
          const float2 b = bs[4 * j], s = cs[4 * j];
          hf[j][0] = relu_sq(fmaf(acc[4 * j], rstd[0], fmaf(s.x, mr0, b.x)), fmaf(acc[4 * j + 1], rstd[0], fmaf(s.y, mr0, b.y)));
          hf[j][1] = relu_sq(fmaf(acc[4 * j + 2], rstd[1], fmaf(s.x, mr1, b.x)), fmaf(acc[4 * j + 3], rstd[1], fmaf(s.y, mr1, b.y)));
        }
      }
      unsigned char* pd[2]; int pstr[2];
#pragma unroll
      for (int hh = 0; hh < 2; hh++) {
        const bool own = 2 * w + hh == r;
        pd[hh] = own ? sg + c * ABYTES + (lane >> 4) * 1024 + (r ^ 1) * 128 + (lane & 15) * 8
                     : gP + (size_t)(((G * 2 + c) * 8 + 2 * w + hh) * 8 + r) * 7168 + lane * 8;
        pstr[hh] = own ? 2048 : 256;
      }
      uint2 pk[8] = {};
      ring.uniform();
#pragma unroll 1
      for (int ch = 0; ch < 7; ch++) {
        float acc[32], acc2[32]; reg_def(acc); reg_def(acc2);
        const uint64_t db0 = mkdesc(ring.acquire(), 4096, 1024, 1);
        const int sl0 = ring.advance();
        const uint64_t db1 = mkdesc(ring.acquire(), 4096, 1024, 1);
        const int sl1 = ring.advance();
        wg_fence();
#pragma unroll
        for (int s = 0; s < 7; s++) {
          mma_rs_64(acc, hf[2 * s][0], hf[2 * s][1], hf[2 * s + 1][0], hf[2 * s + 1][1], db0 + s * 128, s);
          mma_rs_64(acc2, hf[14 + 2 * s][0], hf[14 + 2 * s][1], hf[15 + 2 * s][0], hf[15 + 2 * s][1], db1 + s * 128, s);
        }
        wg_commit();
        if (ch > 0) {
#pragma unroll
          for (int i = 0; i < 8; i++) { *reinterpret_cast<uint2*>(pd[i & 1]) = pk[i]; pd[i & 1] += pstr[i & 1]; }
        }
        wg_wait<0>(); reg_fence(acc); reg_fence(acc2); ring.release(sl0, elect && ch < 5); ring.release(sl1, elect && ch < 5);
#pragma unroll
        for (int i = 0; i < 8; i++) {
          const int b = (i >> 1) * 8 + (i & 1) * 2;
          pk[i] = make_uint2((pack(acc[b] + acc2[b], acc[b + 1] + acc2[b + 1]) & ~1u) | (layer ^ 1), pack(acc[b + 4] + acc2[b + 4], acc[b + 5] + acc2[b + 5]));
        }
      }
#pragma unroll
      for (int i = 0; i < 8; i++) { *reinterpret_cast<uint2*>(pd[i & 1]) = pk[i]; pd[i & 1] += pstr[i & 1]; }
      STAMP(9 + layer * 12);
    }
    {
      uint32_t bx[14];
#pragma unroll
      for (int j = 0; j < 14; j++) bx[j] = __ldg(reinterpret_cast<const uint32_t*>(b2 + (j >> 1) * 64 + w * 16 + (j & 1) * 8 + 2 * t));
      const unsigned char* psrc = gP + (size_t)(((G * 2 + c) * 8 + r) * 8) * 7168 + w * 256 + lane * 8;
      unsigned char* img = gImg + (size_t)(64 + G * 2 + c) * ABYTES;
      uint2 pv[7][7];
      const unsigned char* ps[7];
#pragma unroll
      for (int s = 0; s < 7; s++) ps[s] = psrc + ((r + 1 + s) & 7) * 7168;
#pragma unroll
      for (int i = 0; i < 5; i++)
#pragma unroll
        for (int s = 0; s < 7; s++) pv[s][i] = ldcg2(ps[s] + i * 1024);
      bar_wg(c);
      const uint32_t off = w * 2048 + r * 128 + lane * 4;
      unsigned char* dst = layer ? reinterpret_cast<unsigned char*>(out + (size_t)(row0 + r * 8 + g) * DM + w * 16 + 4 * t) : img + off;
      float sm = 0.f, q = 0.f;
#pragma unroll
      for (int i = 0; i < 7; i++) {
        const uint2 own = *reinterpret_cast<const uint2*>(sg + c * ABYTES + i * 8192 + w * 2048 + (lane >> 4) * 1024 + (r ^ 1) * 128 + (lane & 15) * 8);
#pragma unroll 1
        for (int n = 0; n < (1 << 16); n++) {
          const uint32_t all = pv[0][i].x & pv[1][i].x & pv[2][i].x & pv[3][i].x & pv[4][i].x & pv[5][i].x & pv[6][i].x;
          const uint32_t any = pv[0][i].x | pv[1][i].x | pv[2][i].x | pv[3][i].x | pv[4][i].x | pv[5][i].x | pv[6][i].x;
          if (!__any_sync(~0u, (layer ? any : ~all) & 1u)) break;
#pragma unroll
          for (int s = 0; s < 7; s++) pv[s][i] = ldcg2(ps[s] + i * 1024);
        }
        if (i < 2) {
#pragma unroll
          for (int s = 0; s < 7; s++) pv[s][5 + (i & 1)] = ldcg2(ps[s] + (5 + i) * 1024);
        }
#pragma unroll
        for (int jj = 0; jj < 2; jj++) {
          const int j = 2 * i + jj;
          const uint32_t xo = lds32(abuf + off + i * 8192 + jj * 1024), uo = jj ? own.y : own.x;
          float y0 = lo(bx[j]) + lo(xo) + lo(uo), y1 = hi(bx[j]) + hi(xo) + hi(uo);
#pragma unroll
          for (int s = 0; s < 7; s++) { const uint32_t u = jj ? pv[s][i].y : pv[s][i].x; y0 += lo(u); y1 += hi(u); }
          bx[j] = pack(y0, y1);
          if (!layer) *reinterpret_cast<uint32_t*>(dst + (i * 8 + jj) * 1024) = bx[j];
          sm += lo(bx[j]) + hi(bx[j]);
        }
        if (layer) {
          const int sl = (lane & ~3) | ((t & 1) << 1);
          const uint32_t a0 = __shfl_sync(~0u, bx[2 * i], sl), a1 = __shfl_sync(~0u, bx[2 * i], sl + 1);
          const uint32_t b0 = __shfl_sync(~0u, bx[2 * i + 1], sl), b1v = __shfl_sync(~0u, bx[2 * i + 1], sl + 1);
          *reinterpret_cast<uint2*>(dst + i * 128) = t < 2 ? make_uint2(a0, a1) : make_uint2(b0, b1v);
        }
      }
      if (layer) break;
      sm += __shfl_xor_sync(~0u, sm, 1); sm += __shfl_xor_sync(~0u, sm, 2);
      sm *= 1.f / 112.f;
#pragma unroll
      for (int j = 0; j < 14; j++) { const float a = lo(bx[j]) - sm, b = hi(bx[j]) - sm; q = fmaf(a, a, q); q = fmaf(b, b, q); }
      q += __shfl_xor_sync(~0u, q, 1); q += __shfl_xor_sync(~0u, q, 2);
      if (t < 2) gStat[(size_t)(2048 + row0 + r * 8 + g) * 8 + 2 * w + t] = make_float2(sm, q * 0.5f);
      STAMP(11);
      gather(fl + 64, img);
#pragma unroll
      for (int i = 3; i < 7; i++) ring.release((ring.slot + i) % NSLOT, elect);
      STAMP(12);
    }
  }
  STAMP(30);
  if (tid == 0) asm volatile("red.relaxed.gpu.global.add.u32 [%0], 1;" ::"l"(gFlag + FL_DONE * 32) : "memory");
  }
}

typedef CUresult (*EncFn)(CUtensorMap*, CUtensorMapDataType, cuuint32_t, void*, const cuuint64_t*, const cuuint64_t*,
                          const cuuint32_t*, const cuuint32_t*, CUtensorMapInterleave, CUtensorMapSwizzle,
                          CUtensorMapL2promotion, CUtensorMapFloatOOBfill);

void make_map(EncFn enc, CUtensorMap* m, void* p, int rank, uint64_t d0, uint64_t d1, uint64_t d2, uint64_t s1, uint64_t s2,
              uint32_t b0, uint32_t b1, uint32_t b2, CUtensorMapSwizzle sw) {
  cuuint64_t dims[3] = {d0, d1, d2}, strides[2] = {s1, s2};
  cuuint32_t box[3] = {b0, b1, b2}, es[3] = {1, 1, 1};
  enc(m, CU_TENSOR_MAP_DATA_TYPE_BFLOAT16, rank, p, dims, strides, box, es, CU_TENSOR_MAP_INTERLEAVE_NONE, sw,
      CU_TENSOR_MAP_L2_PROMOTION_L2_128B, CU_TENSOR_MAP_FLOAT_OOB_FILL_NONE);
}

}

extern "C" void kernel_launch(void* const* d_in, const int* in_sizes, int n_in, void* d_out, int out_size) {
  static EncFn enc = nullptr;
  if (!enc) {
    cudaDriverEntryPointQueryResult st;
    void* fn = nullptr;
    cudaGetDriverEntryPoint("cuTensorMapEncodeTiled", &fn, cudaEnableDefault, &st);
    enc = (EncFn)fn;
    cudaFuncSetAttribute(fused_kernel, cudaFuncAttributeMaxDynamicSharedMemorySize, SMEM_BYTES);
  }
  CUtensorMap mQKV, mWO, mW1, mW2, mX;
  make_map(enc, &mX, d_in[0], 2, 448, 2048, 1, 896, 0, 64, 64, 1, CU_TENSOR_MAP_SWIZZLE_128B);
  make_map(enc, &mQKV, d_in[1], 3, 448, 448, 3, 2688, 896, 64, 32, 3, CU_TENSOR_MAP_SWIZZLE_128B);
  make_map(enc, &mWO, d_in[3], 2, 448, 448, 1, 896, 0, 64, 112, 1, CU_TENSOR_MAP_SWIZZLE_128B);
  make_map(enc, &mW1, d_in[5], 3, 32, 448, 56, 3584, 64, 32, 32, 7, CU_TENSOR_MAP_SWIZZLE_64B);
  make_map(enc, &mW2, d_in[7], 2, 448, 1792, 1, 896, 0, 64, 112, 1, CU_TENSOR_MAP_SWIZZLE_128B);
  fused_kernel<<<NCTA, 384, SMEM_BYTES, cudaStreamPerThread>>>(
      mQKV, mWO, mW1, mW2, mX, (const __nv_bfloat16*)d_in[2], (const __nv_bfloat16*)d_in[6],
      (const __nv_bfloat16*)d_in[8], (const __nv_bfloat16*)d_in[1], (const __nv_bfloat16*)d_in[3], (const __nv_bfloat16*)d_in[5],
      (const __nv_bfloat16*)d_in[7], (__nv_bfloat16*)d_out);
}
```

```cpp
#include <cuda_runtime.h>
#include <cuda_bf16.h>
#include <cuda.h>
#include <stdint.h>

namespace {

constexpr int DM = 448, NCTA = 128;
constexpr int ABYTES = 57344;
constexpr int SLOT = 14336, NSLOT = 7;
constexpr int OFF_RING = 2 * ABYTES;
constexpr int OFF_WPHI = OFF_RING + NSLOT * SLOT;
constexpr int OFF_B1 = OFF_WPHI + 8192;
constexpr int OFF_CS = OFF_B1 + 1792;
constexpr int OFF_BAR = OFF_CS + 768;
constexpr int SMEM_BYTES = OFF_BAR + 272 + 1024;
constexpr int TILES_PER_LAYER = 46;

__device__ __align__(1024) unsigned char gP[16 * 2 * 8 * 8 * 7168];
__device__ __align__(1024) unsigned char gImg[3 * 32 * ABYTES];
__device__ __align__(1024) float2 gStat[2 * 2048 * 8];
__device__ __align__(1024) float4 gKV[2 * 8 * 2 * 5 * 128];
__device__ __align__(1024) float4 gCS[8 * 16 * 104];
__device__ __align__(128) unsigned gFlag[(2 * 32 * 7 + 32 + 1 + 16) * 32];
#define STAMP(i)

__device__ __forceinline__ uint32_t smem_u32(const void* p) { return (uint32_t)__cvta_generic_to_shared(p); }
__device__ __forceinline__ void mbar_init(uint32_t b, int c) { asm volatile("mbarrier.init.shared::cta.b64 [%0], %1;" ::"r"(b), "r"(c)); }
__device__ __forceinline__ void mbar_expect(uint32_t b, int bytes) { asm volatile("mbarrier.arrive.expect_tx.shared::cta.b64 _, [%0], %1;" ::"r"(b), "r"(bytes) : "memory"); }
__device__ __forceinline__ void mbar_arrive(uint32_t b) { asm volatile("mbarrier.arrive.shared::cta.b64 _, [%0];" ::"r"(b) : "memory"); }
__device__ __forceinline__ void mbar_wait(uint32_t b, int par) {
  uint32_t ok; int n = 0;
#pragma unroll 1
  while (true) {
    asm volatile("{.reg .pred p; mbarrier.try_wait.parity.shared::cta.b64 p, [%1], %2; selp.u32 %0,1,0,p;}" : "=r"(ok) : "r"(b), "r"(par) : "memory");
    if (ok) break;
    if (++n > (1 << 20)) break;
  }
}
__device__ __forceinline__ void flag_wait(const unsigned* f, unsigned target) {
  unsigned v; int n = 0;
#pragma unroll 1
  while (true) {
    asm volatile("ld.relaxed.gpu.global.u32 %0, [%1];" : "=r"(v) : "l"(f) : "memory");
    if ((int)(v - target) >= 0) break;
    if (++n > (1 << 18)) break;
  }
}
__device__ __forceinline__ void flag_arrive(unsigned* f) { asm volatile("red.release.gpu.global.add.u32 [%0], 1;" ::"l"(f) : "memory"); }
__device__ __forceinline__ bool elect_one() {
  uint32_t p; asm volatile("{.reg .pred P; elect.sync _|P, 0xffffffff; selp.u32 %0, 1, 0, P;}" : "=r"(p)); return p;
}
__device__ __forceinline__ void fence_async() { asm volatile("fence.proxy.async.global;" ::: "memory"); }
__device__ __forceinline__ void fence_async_smem() { asm volatile("fence.proxy.async.shared::cta;" ::: "memory"); }
template <int ID, int N> __device__ __forceinline__ void bar_sync() { asm volatile("bar.sync %0, %1;" ::"n"(ID), "n"(N) : "memory"); }
__device__ __forceinline__ void bar_wg(int c) { if (c) bar_sync<2, 128>(); else bar_sync<1, 128>(); }
__device__ __forceinline__ void wg_fence() { asm volatile("wgmma.fence.sync.aligned;" ::: "memory"); }
__device__ __forceinline__ void wg_commit() { asm volatile("wgmma.commit_group.sync.aligned;" ::: "memory"); }
template <int N> __device__ __forceinline__ void wg_wait() { asm volatile("wgmma.wait_group.sync.aligned %0;" ::"n"(N) : "memory"); }
template <int N> __device__ __forceinline__ void reg_fence(float (&d)[N]) {
#pragma unroll
  for (int i = 0; i < N; i++) asm volatile("" : "+f"(d[i])::"memory");
}
template <int N> __device__ __forceinline__ void reg_def(float (&d)[N]) {
#pragma unroll
  for (int i = 0; i < N; i++) d[i] = 0.f;
}
__device__ __forceinline__ uint64_t mkdesc(uint32_t addr, uint32_t lbo, uint32_t sbo, uint64_t swz) {
  return (uint64_t)((addr & 0x3FFFF) >> 4) | ((uint64_t)(lbo >> 4) << 16) | ((uint64_t)(sbo >> 4) << 32) | (swz << 62);
}
__device__ __forceinline__ uint32_t pack(float a, float b) {
  uint32_t r; asm("cvt.rn.bf16x2.f32 %0, %1, %2;" : "=r"(r) : "f"(b), "f"(a)); return r;
}
__device__ __forceinline__ uint32_t relu_sq(float a, float b) {
  uint32_t r; asm("{.reg .b32 v; cvt.rn.relu.bf16x2.f32 v, %1, %2; mul.rn.bf16x2 %0, v, v;}" : "=r"(r) : "f"(b), "f"(a)); return r;
}
__device__ __forceinline__ float lo(uint32_t u) { return __uint_as_float(u << 16); }
__device__ __forceinline__ float hi(uint32_t u) { return __uint_as_float(u & 0xFFFF0000u); }
__device__ __forceinline__ float ex2(float x) { float y; asm("ex2.approx.ftz.f32 %0, %1;" : "=f"(y) : "f"(x)); return y; }
__device__ __forceinline__ void stsm4(uint32_t a, uint32_t r0, uint32_t r1, uint32_t r2, uint32_t r3) {
  asm volatile("stmatrix.sync.aligned.m8n8.x4.shared.b16 [%0], {%1,%2,%3,%4};" ::"r"(a), "r"(r0), "r"(r1), "r"(r2), "r"(r3) : "memory");
}
__device__ __forceinline__ void tma3(uint32_t dst, const CUtensorMap* m, int c0, int c1, int c2, uint32_t bar) {
  asm volatile("cp.async.bulk.tensor.3d.shared::cluster.global.mbarrier::complete_tx::bytes [%0], [%1, {%3,%4,%5}], [%2];"
               ::"r"(dst), "l"(m), "r"(bar), "r"(c0), "r"(c1), "r"(c2) : "memory");
}
__device__ __forceinline__ void tma2(uint32_t dst, const CUtensorMap* m, int c0, int c1, uint32_t bar) {
  asm volatile("cp.async.bulk.tensor.2d.shared::cluster.global.mbarrier::complete_tx::bytes [%0], [%1, {%3,%4}], [%2];"
               ::"r"(dst), "l"(m), "r"(bar), "r"(c0), "r"(c1) : "memory");
}
__device__ __forceinline__ uint32_t lds32(uint32_t a) { uint32_t v; asm volatile("ld.shared.u32 %0, [%1];" : "=r"(v) : "r"(a) : "memory"); return v; }
__device__ __forceinline__ void bulk_ld(uint32_t dst, const void* src, int bytes, uint32_t bar) {
  asm volatile("cp.async.bulk.shared::cluster.global.mbarrier::complete_tx::bytes [%0], [%1], %2, [%3];" ::"r"(dst), "l"(src), "r"(bytes), "r"(bar) : "memory");
}
__device__ __forceinline__ uint4 ldcg4(const void* p) {
  uint4 v; asm volatile("ld.global.cg.v4.u32 {%0,%1,%2,%3}, [%4];" : "=r"(v.x), "=r"(v.y), "=r"(v.z), "=r"(v.w) : "l"(p) : "memory"); return v;
}

__device__ __forceinline__ uint2 ldcg2(const void* p) {
  uint2 v; asm volatile("ld.global.cg.v2.u32 {%0,%1}, [%2];" : "=r"(v.x), "=r"(v.y) : "l"(p) : "memory"); return v;
}

__device__ __forceinline__ void mma_ss_184(float (&d)[92], uint64_t da, uint64_t db, int acc) {
  asm volatile("{.reg .pred p; setp.ne.b32 p, %94, 0;\n"
    "wgmma.mma_async.sync.aligned.m64n184k16.f32.bf16.bf16 {%0,%1,%2,%3,%4,%5,%6,%7,%8,%9,%10,%11,%12,%13,%14,%15,%16,%17,%18,%19,%20,%21,%22,%23,%24,%25,%26,%27,%28,%29,%30,%31,%32,%33,%34,%35,%36,%37,%38,%39,%40,%41,%42,%43,%44,%45,%46,%47,%48,%49,%50,%51,%52,%53,%54,%55,%56,%57,%58,%59,%60,%61,%62,%63,%64,%65,%66,%67,%68,%69,%70,%71,%72,%73,%74,%75,%76,%77,%78,%79,%80,%81,%82,%83,%84,%85,%86,%87,%88,%89,%90,%91}, %92, %93, p, 1, 1, 0, 1;}\n"
    : "+f"(d[0]),"+f"(d[1]),"+f"(d[2]),"+f"(d[3]),"+f"(d[4]),"+f"(d[5]),"+f"(d[6]),"+f"(d[7]),"+f"(d[8]),"+f"(d[9]),"+f"(d[10]),"+f"(d[11]),"+f"(d[12]),"+f"(d[13]),"+f"(d[14]),"+f"(d[15]),"+f"(d[16]),"+f"(d[17]),"+f"(d[18]),"+f"(d[19]),"+f"(d[20]),"+f"(d[21]),"+f"(d[22]),"+f"(d[23]),"+f"(d[24]),"+f"(d[25]),"+f"(d[26]),"+f"(d[27]),"+f"(d[28]),"+f"(d[29]),"+f"(d[30]),"+f"(d[31]),"+f"(d[32]),"+f"(d[33]),"+f"(d[34]),"+f"(d[35]),"+f"(d[36]),"+f"(d[37]),"+f"(d[38]),"+f"(d[39]),"+f"(d[40]),"+f"(d[41]),"+f"(d[42]),"+f"(d[43]),"+f"(d[44]),"+f"(d[45]),"+f"(d[46]),"+f"(d[47]),"+f"(d[48]),"+f"(d[49]),"+f"(d[50]),"+f"(d[51]),"+f"(d[52]),"+f"(d[53]),"+f"(d[54]),"+f"(d[55]),"+f"(d[56]),"+f"(d[57]),"+f"(d[58]),"+f"(d[59]),"+f"(d[60]),"+f"(d[61]),"+f"(d[62]),"+f"(d[63]),"+f"(d[64]),"+f"(d[65]),"+f"(d[66]),"+f"(d[67]),"+f"(d[68]),"+f"(d[69]),"+f"(d[70]),"+f"(d[71]),"+f"(d[72]),"+f"(d[73]),"+f"(d[74]),"+f"(d[75]),"+f"(d[76]),"+f"(d[77]),"+f"(d[78]),"+f"(d[79]),"+f"(d[80]),"+f"(d[81]),"+f"(d[82]),"+f"(d[83]),"+f"(d[84]),"+f"(d[85]),"+f"(d[86]),"+f"(d[87]),"+f"(d[88]),"+f"(d[89]),"+f"(d[90]),"+f"(d[91])
    : "l"(da), "l"(db), "r"(acc));
}
__device__ __forceinline__ void mma_ss_224(float (&d)[112], uint64_t da, uint64_t db, int acc) {
  asm volatile("{.reg .pred p; setp.ne.b32 p, %114, 0;\n"
    "wgmma.mma_async.sync.aligned.m64n224k16.f32.bf16.bf16 {%0,%1,%2,%3,%4,%5,%6,%7,%8,%9,%10,%11,%12,%13,%14,%15,%16,%17,%18,%19,%20,%21,%22,%23,%24,%25,%26,%27,%28,%29,%30,%31,%32,%33,%34,%35,%36,%37,%38,%39,%40,%41,%42,%43,%44,%45,%46,%47,%48,%49,%50,%51,%52,%53,%54,%55,%56,%57,%58,%59,%60,%61,%62,%63,%64,%65,%66,%67,%68,%69,%70,%71,%72,%73,%74,%75,%76,%77,%78,%79,%80,%81,%82,%83,%84,%85,%86,%87,%88,%89,%90,%91,%92,%93,%94,%95,%96,%97,%98,%99,%100,%101,%102,%103,%104,%105,%106,%107,%108,%109,%110,%111}, %112, %113, p, 1, 1, 0, 1;}\n"
    : "+f"(d[0]),"+f"(d[1]),"+f"(d[2]),"+f"(d[3]),"+f"(d[4]),"+f"(d[5]),"+f"(d[6]),"+f"(d[7]),"+f"(d[8]),"+f"(d[9]),"+f"(d[10]),"+f"(d[11]),"+f"(d[12]),"+f"(d[13]),"+f"(d[14]),"+f"(d[15]),"+f"(d[16]),"+f"(d[17]),"+f"(d[18]),"+f"(d[19]),"+f"(d[20]),"+f"(d[21]),"+f"(d[22]),"+f"(d[23]),"+f"(d[24]),"+f"(d[25]),"+f"(d[26]),"+f"(d[27]),"+f"(d[28]),"+f"(d[29]),"+f"(d[30]),"+f"(d[31]),"+f"(d[32]),"+f"(d[33]),"+f"(d[34]),"+f"(d[35]),"+f"(d[36]),"+f"(d[37]),"+f"(d[38]),"+f"(d[39]),"+f"(d[40]),"+f"(d[41]),"+f"(d[42]),"+f"(d[43]),"+f"(d[44]),"+f"(d[45]),"+f"(d[46]),"+f"(d[47]),"+f"(d[48]),"+f"(d[49]),"+f"(d[50]),"+f"(d[51]),"+f"(d[52]),"+f"(d[53]),"+f"(d[54]),"+f"(d[55]),"+f"(d[56]),"+f"(d[57]),"+f"(d[58]),"+f"(d[59]),"+f"(d[60]),"+f"(d[61]),"+f"(d[62]),"+f"(d[63]),"+f"(d[64]),"+f"(d[65]),"+f"(d[66]),"+f"(d[67]),"+f"(d[68]),"+f"(d[69]),"+f"(d[70]),"+f"(d[71]),"+f"(d[72]),"+f"(d[73]),"+f"(d[74]),"+f"(d[75]),"+f"(d[76]),"+f"(d[77]),"+f"(d[78]),"+f"(d[79]),"+f"(d[80]),"+f"(d[81]),"+f"(d[82]),"+f"(d[83]),"+f"(d[84]),"+f"(d[85]),"+f"(d[86]),"+f"(d[87]),"+f"(d[88]),"+f"(d[89]),"+f"(d[90]),"+f"(d[91]),"+f"(d[92]),"+f"(d[93]),"+f"(d[94]),"+f"(d[95]),"+f"(d[96]),"+f"(d[97]),"+f"(d[98]),"+f"(d[99]),"+f"(d[100]),"+f"(d[101]),"+f"(d[102]),"+f"(d[103]),"+f"(d[104]),"+f"(d[105]),"+f"(d[106]),"+f"(d[107]),"+f"(d[108]),"+f"(d[109]),"+f"(d[110]),"+f"(d[111])
    : "l"(da), "l"(db), "r"(acc));
}
__device__ __forceinline__ void mma_ss_56(float (&d)[28], uint64_t da, uint64_t db, int acc) {
  asm volatile("{.reg .pred p; setp.ne.b32 p, %30, 0;\n"
    "wgmma.mma_async.sync.aligned.m64n56k16.f32.bf16.bf16 {%0,%1,%2,%3,%4,%5,%6,%7,%8,%9,%10,%11,%12,%13,%14,%15,%16,%17,%18,%19,%20,%21,%22,%23,%24,%25,%26,%27}, %28, %29, p, 1, 1, 0, 1;}\n"
    : "+f"(d[0]),"+f"(d[1]),"+f"(d[2]),"+f"(d[3]),"+f"(d[4]),"+f"(d[5]),"+f"(d[6]),"+f"(d[7]),"+f"(d[8]),"+f"(d[9]),"+f"(d[10]),"+f"(d[11]),"+f"(d[12]),"+f"(d[13]),"+f"(d[14]),"+f"(d[15]),"+f"(d[16]),"+f"(d[17]),"+f"(d[18]),"+f"(d[19]),"+f"(d[20]),"+f"(d[21]),"+f"(d[22]),"+f"(d[23]),"+f"(d[24]),"+f"(d[25]),"+f"(d[26]),"+f"(d[27])
    : "l"(da), "l"(db), "r"(acc));
}
__device__ __forceinline__ void mma_rs_56(float (&d)[28], uint32_t a0, uint32_t a1, uint32_t a2, uint32_t a3, uint64_t db, int acc) {
  asm volatile("{.reg .pred p; setp.ne.b32 p, %33, 0;\n"
    "wgmma.mma_async.sync.aligned.m64n56k16.f32.bf16.bf16 {%0,%1,%2,%3,%4,%5,%6,%7,%8,%9,%10,%11,%12,%13,%14,%15,%16,%17,%18,%19,%20,%21,%22,%23,%24,%25,%26,%27}, {%28,%29,%30,%31}, %32, p, 1, 1, 1;}\n"
    : "+f"(d[0]),"+f"(d[1]),"+f"(d[2]),"+f"(d[3]),"+f"(d[4]),"+f"(d[5]),"+f"(d[6]),"+f"(d[7]),"+f"(d[8]),"+f"(d[9]),"+f"(d[10]),"+f"(d[11]),"+f"(d[12]),"+f"(d[13]),"+f"(d[14]),"+f"(d[15]),"+f"(d[16]),"+f"(d[17]),"+f"(d[18]),"+f"(d[19]),"+f"(d[20]),"+f"(d[21]),"+f"(d[22]),"+f"(d[23]),"+f"(d[24]),"+f"(d[25]),"+f"(d[26]),"+f"(d[27])
    : "r"(a0), "r"(a1), "r"(a2), "r"(a3), "l"(db), "r"(acc));
}
__device__ __forceinline__ void mma_ss_64t(float (&d)[32], uint64_t da, uint64_t db, int acc) {
  asm volatile("{.reg .pred p; setp.ne.b32 p, %34, 0;\n"
    "wgmma.mma_async.sync.aligned.m64n64k16.f32.bf16.bf16 {%0,%1,%2,%3,%4,%5,%6,%7,%8,%9,%10,%11,%12,%13,%14,%15,%16,%17,%18,%19,%20,%21,%22,%23,%24,%25,%26,%27,%28,%29,%30,%31}, %32, %33, p, 1, 1, 1, 1;}\n"
    : "+f"(d[0]),"+f"(d[1]),"+f"(d[2]),"+f"(d[3]),"+f"(d[4]),"+f"(d[5]),"+f"(d[6]),"+f"(d[7]),"+f"(d[8]),"+f"(d[9]),"+f"(d[10]),"+f"(d[11]),"+f"(d[12]),"+f"(d[13]),"+f"(d[14]),"+f"(d[15]),"+f"(d[16]),"+f"(d[17]),"+f"(d[18]),"+f"(d[19]),"+f"(d[20]),"+f"(d[21]),"+f"(d[22]),"+f"(d[23]),"+f"(d[24]),"+f"(d[25]),"+f"(d[26]),"+f"(d[27]),"+f"(d[28]),"+f"(d[29]),"+f"(d[30]),"+f"(d[31])
    : "l"(da), "l"(db), "r"(acc));
}
__device__ __forceinline__ void mma_rs_64(float (&d)[32], uint32_t a0, uint32_t a1, uint32_t a2, uint32_t a3, uint64_t db, int acc) {
  asm volatile("{.reg .pred p; setp.ne.b32 p, %37, 0;\n"
    "wgmma.mma_async.sync.aligned.m64n64k16.f32.bf16.bf16 {%0,%1,%2,%3,%4,%5,%6,%7,%8,%9,%10,%11,%12,%13,%14,%15,%16,%17,%18,%19,%20,%21,%22,%23,%24,%25,%26,%27,%28,%29,%30,%31}, {%32,%33,%34,%35}, %36, p, 1, 1, 1;}\n"
    : "+f"(d[0]),"+f"(d[1]),"+f"(d[2]),"+f"(d[3]),"+f"(d[4]),"+f"(d[5]),"+f"(d[6]),"+f"(d[7]),"+f"(d[8]),"+f"(d[9]),"+f"(d[10]),"+f"(d[11]),"+f"(d[12]),"+f"(d[13]),"+f"(d[14]),"+f"(d[15]),"+f"(d[16]),"+f"(d[17]),"+f"(d[18]),"+f"(d[19]),"+f"(d[20]),"+f"(d[21]),"+f"(d[22]),"+f"(d[23]),"+f"(d[24]),"+f"(d[25]),"+f"(d[26]),"+f"(d[27]),"+f"(d[28]),"+f"(d[29]),"+f"(d[30]),"+f"(d[31])
    : "r"(a0), "r"(a1), "r"(a2), "r"(a3), "l"(db), "r"(acc));
}

__device__ __forceinline__ void dual_softmax(const float (&p)[28], uint32_t (&phi)[4][7]) {
  constexpr float L2E = 1.4426950408889634f;
#pragma unroll
  for (int i = 0; i < 4; i++) {
    float mx = p[i], mn = p[i];
#pragma unroll
    for (int j = 1; j < 7; j++) { mx = fmaxf(mx, p[4 * j + i]); mn = fminf(mn, p[4 * j + i]); }
    mx = fmaxf(mx, __shfl_xor_sync(~0u, mx, 1)); mn = fminf(mn, __shfl_xor_sync(~0u, mn, 1));
    mx = fmaxf(mx, __shfl_xor_sync(~0u, mx, 2)); mn = fminf(mn, __shfl_xor_sync(~0u, mn, 2));
    float a[7], b[7], sa = 0.f, sb = 0.f;
    const float mxl = mx * L2E, mnl = mn * L2E;
#pragma unroll
    for (int j = 0; j < 7; j++) {
      a[j] = ex2(fmaf(p[4 * j + i], L2E, -mxl)); b[j] = ex2(fmaf(p[4 * j + i], -L2E, mnl));
      sa += a[j]; sb += b[j];
    }
    sa += __shfl_xor_sync(~0u, sa, 1); sb += __shfl_xor_sync(~0u, sb, 1);
    sa += __shfl_xor_sync(~0u, sa, 2); sb += __shfl_xor_sync(~0u, sb, 2);
    const float ra = __fdividef(1.f, sa), rb = __fdividef(1.f, sb);
#pragma unroll
    for (int j = 0; j < 7; j++) phi[i][j] = pack(a[j] * ra, b[j] * rb);
  }
}

struct Ring {
  uint32_t full, empty, base; int slot, par;
  __device__ __forceinline__ void uniform() { slot = __shfl_sync(~0u, slot, 0); par = __shfl_sync(~0u, par, 0); }
  __device__ __forceinline__ uint32_t acquire() { mbar_wait(full + slot * 8, par); return base + slot * SLOT; }
  __device__ __forceinline__ int advance() { int s = slot; if (++slot == NSLOT) { slot = 0; par ^= 1; } return s; }
  __device__ __forceinline__ void release(int s, bool elect) { if (elect) mbar_arrive(empty + s * 8); }
};
constexpr int UNR = 14;
constexpr int FL_KV = 448, FL_CS = FL_KV + 16, FL_DONE = FL_KV + 32;

__global__ void __launch_bounds__(384, 1)
fused_kernel(const __grid_constant__ CUtensorMap mQKV, const __grid_constant__ CUtensorMap mWO,
             const __grid_constant__ CUtensorMap mW1, const __grid_constant__ CUtensorMap mW2,
             const __grid_constant__ CUtensorMap mX, const __nv_bfloat16* __restrict__ wphi,
             const __nv_bfloat16* __restrict__ b1, const __nv_bfloat16* __restrict__ b2,
             const __nv_bfloat16* __restrict__ wqkv, const __nv_bfloat16* __restrict__ wo, const __nv_bfloat16* __restrict__ w1,
             const __nv_bfloat16* __restrict__ w2, __nv_bfloat16* __restrict__ out) {
  extern __shared__ unsigned char smem_raw[];
  const uint32_t sb = (smem_u32(smem_raw) + 1023) & ~1023u;
  unsigned char* sg = smem_raw + (sb - smem_u32(smem_raw));
  const int tid = threadIdx.x, lane = tid & 31;
  const int G = blockIdx.x >> 3, r = blockIdx.x & 7;
  const uint32_t barFull = sb + OFF_BAR, barEmpty = barFull + 56, barA = barEmpty + 56, barCS = barA + 112, barX = barCS + 16;
  const int warp = __shfl_sync(~0u, tid >> 5, 0);
  uint32_t wv[7] = {}, bv = 0;
  if (warp < 8) {
#pragma unroll
    for (int i = 0; i < 7; i++)
      wv[i] = __ldg(reinterpret_cast<const unsigned short*>(wphi) + (56 * r + i * 8 + warp) * 28 + min(lane, 27));
    bv = __ldg(reinterpret_cast<const unsigned short*>(b1) + 224 * r + min(tid, 223));
  }
  if (lane == 0) {
    if (warp >= 10) {
      const int cc = warp - 10;
      mbar_init(barX + cc * 8, 1);
      fence_async_smem();
      mbar_expect(barX + cc * 8, ABYTES);
#pragma unroll 1
      for (int k = 0; k < 7; k++) tma2(sb + cc * ABYTES + k * 8192, &mX, 64 * k, G * 128 + 64 * cc, barX + cc * 8);
    } else if (warp < 7) { mbar_init(barFull + warp * 8, 1); mbar_init(barEmpty + warp * 8, 2); mbar_init(barA + warp * 8, 1); mbar_init(barA + 56 + warp * 8, 1); }
    else if (warp < 9) { mbar_init(barCS + (warp - 7) * 8, 64); if (warp == 7) mbar_init(barX + 16, 1); }
    else
      asm volatile("cp.async.bulk.prefetch.L2.global [%0], %1;" ::"l"((const char*)wqkv + blockIdx.x * 9408), "r"(9408) : "memory");
    asm volatile("fence.mbarrier_init.release.cluster;" ::: "memory");
  }
  if (tid < 192) reinterpret_cast<float*>(sg + OFF_CS)[tid] = 0.f;
  __syncthreads();
  const int wgid = warp >> 2;
  if (wgid == 2) {
    asm volatile("setmaxnreg.dec.sync.aligned.u32 40;");
    if (warp == 8) {
      int slot = 0, par = 1;
#pragma unroll 1
      for (int it = 0; it < 2 * TILES_PER_LAYER; it++) {
        const int i = it >= TILES_PER_LAYER ? it - TILES_PER_LAYER : it;
        mbar_wait(barEmpty + slot * 8, par);
        const uint32_t dst = sb + OFF_RING + slot * SLOT, fb = barFull + slot * 8;
        if (elect_one()) {
          mbar_expect(fb, i < 14 ? 12288 : SLOT);
          if (i < 14) tma3(dst, &mQKV, 56 * r, 32 * i, 0, fb);
          else if (i < 18) tma2(dst, &mWO, 56 * r, 112 * (i - 14), fb);
          else if (i < 32) tma3(dst, &mW1, 0, 32 * (i - 18), 7 * r, fb);
          else tma2(dst, &mW2, 64 * ((i - 32) >> 1), 224 * r + 112 * (i & 1), fb);
        }
        if (++slot == NSLOT) { slot = 0; par ^= 1; }
      }
    } else if (warp == 11) {
      unsigned ep;
      asm volatile("ld.relaxed.gpu.global.u32 %0, [%1];" : "=r"(ep) : "l"(gFlag + FL_DONE * 32) : "memory");
#pragma unroll 1
      for (int layer = 0; layer < 2; layer++) {
        bar_sync<4, 288>();
        if (lane == 0) {
          flag_arrive(gFlag + (FL_KV + layer * 8 + r) * 32);
          flag_wait(gFlag + (FL_KV + layer * 8 + r) * 32, (ep / NCTA + 1) * 16);
          mbar_arrive(barX + 16);
        }
        __syncwarp();
      }
    } else {
      unsigned ep;
      asm volatile("ld.relaxed.gpu.global.u32 %0, [%1];" : "=r"(ep) : "l"(gFlag + FL_DONE * 32) : "memory");
      const int idx = tid - 288;
      ep = (ep / NCTA + 1) * 2;
      if (G == 0) {
#pragma unroll 1
        for (int i = idx; i < 2 * 1280; i += 64) gKV[((i >= 1280) * 7 + r) * 1280 + i] = make_float4(0.f, 0.f, 0.f, 0.f);
        __syncwarp();
        if (lane == 0) flag_arrive(gFlag + (FL_CS + r) * 32);
      }
      mbar_wait(barFull + 48, 0);
      if (idx < 3) {
        const char* pf = idx ? (idx == 1 ? (const char*)w1 : (const char*)w2) + blockIdx.x * 12544 : (const char*)wo + blockIdx.x * 3136;
        asm volatile("cp.async.bulk.prefetch.L2.global [%0], %1;" ::"l"(pf), "r"(idx ? 12544 : 3136) : "memory");
      }
      if (lane == 0) flag_wait(gFlag + (FL_CS + r) * 32, ep);
      __syncwarp();
      mbar_arrive(barCS);
#pragma unroll 1
      for (int ps = 0; ps < 4; ps++) {
        const int ch = min(ps * 16 + (idx >> 2), 48), p = ch / 7, k0 = G * 28 + (idx & 3) * 7;
        const uint4* src = ch >= 21 ? reinterpret_cast<const uint4*>(w1 + (size_t)k0 * 1792 + 224 * r) + (ch - 21)
                                    : reinterpret_cast<const uint4*>(wqkv + (size_t)k0 * 1344 + p * 448 + 56 * r) + (ch - 7 * p);
        uint4 cu[7];
#pragma unroll
        for (int i = 0; i < 7; i++) cu[i] = __ldg(src + i * (ch >= 21 ? 224 : 168));
        float s[8] = {};
#pragma unroll
        for (int i = 0; i < 7; i++) { s[0] += lo(cu[i].x); s[1] += hi(cu[i].x); s[2] += lo(cu[i].y); s[3] += hi(cu[i].y); s[4] += lo(cu[i].z); s[5] += hi(cu[i].z); s[6] += lo(cu[i].w); s[7] += hi(cu[i].w); }
#pragma unroll
        for (int i = 0; i < 8; i++) { s[i] += __shfl_xor_sync(~0u, s[i], 1); s[i] += __shfl_xor_sync(~0u, s[i], 2); }
        if ((idx & 3) < 2) gCS[(r * 16 + G) * 104 + (ch + min(p, 3)) * 2 + (idx & 1)] = (idx & 1) ? make_float4(s[4], s[5], s[6], s[7]) : make_float4(s[0], s[1], s[2], s[3]);
      }
      __syncwarp();
      if (lane == 0) { flag_arrive(gFlag + (FL_CS + 8 + r) * 32); flag_wait(gFlag + (FL_CS + 8 + r) * 32, ep * 16); }
      __syncwarp();
#pragma unroll 1
      for (int j = idx; j < 208; j += 64) {
        float2 a = make_float2(0.f, 0.f);
#pragma unroll 8
        for (int i = 0; i < 16; i++) { const float2 v = __ldcg(reinterpret_cast<const float2*>(gCS + (r * 16 + i) * 104) + j); a.x += v.x; a.y += v.y; }
        *reinterpret_cast<float2*>(sg + (j < 96 ? OFF_CS + j * 8 : OFF_B1 + (j - 96) * 16 + 8)) = a;
      }
      mbar_arrive(barCS + 8);
    }
  } else {
  asm volatile("setmaxnreg.inc.sync.aligned.u32 232;");
  const int c = wgid, w = warp & 3, g = lane >> 2, t = lane & 3;
  int elect_i = (tid & 127) == 0;
  asm volatile("" : "+r"(elect_i));
  const bool elect = elect_i;
  const uint32_t abuf = sb + c * ABYTES, barAc = barA + c * 56;
  const int row0 = G * 128 + c * 64;
  unsigned epoch;
  asm volatile("ld.relaxed.gpu.global.u32 %0, [%1];" : "=r"(epoch) : "l"(gFlag + FL_DONE * 32) : "memory");
  STAMP(24);
  float mean[2], rstd[2] = {0.f, 0.f};
  uint4 su[2] = {};
  uint32_t xs[7][2];
  {
#pragma unroll
    for (int i = 0; i < 8; i++) {
      const int k = i * 8 + (tid >> 5);
      *reinterpret_cast<uint32_t*>(sg + OFF_WPHI + k * 128 + ((g ^ (k & 7)) << 4) + t * 4) = (i < 7 && lane < 28) ? wv[i % 7] << (k >= 28 ? 16 : 0) : 0u;
    }
    if (tid < 224) reinterpret_cast<uint32_t*>(sg + OFF_B1)[(tid >> 1) * 4 + (tid & 1)] = bv << 16;
    mbar_wait(barX + c * 8, 0);
    STAMP(25);
#pragma unroll
    for (int j = 0; j < 7; j++) {
      const int ci = 7 * r + j;
      const uint32_t a = abuf + (ci >> 3) * 8192 + (w * 16 + g) * 128 + (((ci & 7) ^ g) << 4) + t * 4;
      xs[j][0] = lds32(a); xs[j][1] = lds32(a + 1024);
    }
    __syncwarp();
#pragma unroll 1
    for (int hh = 0; hh < 2; hh++) {
      uint4* p = reinterpret_cast<uint4*>(sg + c * ABYTES + (w * 16 + hh * 8 + g) * 128) + t;
      uint4 v[14];
#pragma unroll
      for (int k = 0; k < 14; k++) v[k] = p[(k >> 1) * 512 + ((k ^ g) & 1) * 4];
      float a8[8] = {};
#pragma unroll
      for (int k = 0; k < 14; k++) {
        const uint32_t e[4] = {v[k].x, v[k].y, v[k].z, v[k].w};
#pragma unroll
        for (int z = 0; z < 4; z++) { a8[2 * z] += lo(e[z]); a8[2 * z + 1] += hi(e[z]); }
      }
      float sm = ((a8[0] + a8[1]) + (a8[2] + a8[3])) + ((a8[4] + a8[5]) + (a8[6] + a8[7]));
      sm += __shfl_xor_sync(~0u, sm, 1); sm += __shfl_xor_sync(~0u, sm, 2);
      sm *= 1.f / DM;
#pragma unroll
      for (int k = 0; k < 14; k++) {
        uint32_t e[4] = {v[k].x, v[k].y, v[k].z, v[k].w};
#pragma unroll
        for (int z = 0; z < 4; z++) {
          const float a = lo(e[z]) - sm, b = hi(e[z]) - sm;
          a8[2 * z] = fmaf(a, a, k ? a8[2 * z] : 0.f); a8[2 * z + 1] = fmaf(b, b, k ? a8[2 * z + 1] : 0.f);
          e[z] = pack(a, b);
        }
        p[(k >> 1) * 512 + ((k ^ g) & 1) * 4] = make_uint4(e[0], e[1], e[2], e[3]);
      }
      float q = ((a8[0] + a8[1]) + (a8[2] + a8[3])) + ((a8[4] + a8[5]) + (a8[6] + a8[7]));
      q += __shfl_xor_sync(~0u, q, 1); q += __shfl_xor_sync(~0u, q, 2);
      rstd[1] = rsqrtf(q * (1.f / DM) + 1e-5f);
      if (hh == 0) rstd[0] = rstd[1];
    }
    fence_async_smem();
    bar_sync<3, 256>();
    epoch = epoch / NCTA + 1;
    mean[0] = mean[1] = 0.f;
  }
  STAMP(0);
  Ring ring{barFull, barEmpty, sb + OFF_RING, 0, 0};
  int apar = 1;
  const uint32_t stsm_off = (w * 16 + ((lane >> 3) & 1) * 8 + (lane & 7)) * 128;
  const uint32_t stsm_hi = lane >> 4;
  const uint64_t dA = mkdesc(abuf, 1024, 128, 0);

  auto gather = [&](unsigned* fl, const unsigned char* img) {
    bar_wg(c);
    if (w == 0) {
      if (elect_one()) {
        flag_arrive(fl);
#pragma unroll
        for (int k = 0; k < 7; k++) mbar_expect(barAc + k * 8, 8192);
        flag_wait(fl, epoch * 8);
        fence_async();
#pragma unroll
        for (int k = 0; k < 7; k++) bulk_ld(abuf + k * 8192, img + k * 8192, 8192, barAc + k * 8);
      }
      __syncwarp();
    }
    apar ^= 1;
  };
  auto slice_off = [&](int j, int hh) -> uint32_t {
    return (7 * r + j) * 1024 + (w * 2 + hh) * 128 + lane * 4;
  };
  auto load_stats = [&](const float2* st) {
    mbar_wait(barAc, apar);
#pragma unroll
    for (int hh = 0; hh < 2; hh++) su[hh] = ldcg4(st + (size_t)(row0 + w * 16 + hh * 8 + g) * 8 + 2 * t);
  };
  auto finish_stats = [&]() {
#pragma unroll
    for (int hh = 0; hh < 2; hh++) {
      const float m0 = __uint_as_float(su[hh].x), m1 = __uint_as_float(su[hh].z);
      float m = m0 + m1;
      m += __shfl_xor_sync(~0u, m, 1); m += __shfl_xor_sync(~0u, m, 2);
      m *= 0.125f;
      float q = __uint_as_float(su[hh].y) + __uint_as_float(su[hh].w) + 56.f * ((m0 - m) * (m0 - m) + (m1 - m) * (m1 - m));
      q += __shfl_xor_sync(~0u, q, 1); q += __shfl_xor_sync(~0u, q, 2);
      mean[hh] = m; rstd[hh] = rsqrtf(q * (1.f / DM) + 1e-5f);
    }
  };

#pragma unroll 1
  for (int lyr = 0; lyr < 2; lyr++) {
    const int layer = __shfl_sync(~0u, lyr, 0);
    unsigned* const fl = gFlag + (layer * 32 + G * 2 + c) * 7 * 32;
    uint32_t phiq[4][7];
    {
      float acc[92]; reg_def(acc);
      int prev = 0, prev2 = 0;
      ring.uniform();
      const uint64_t dQ = layer ? dA : mkdesc(abuf, 16, 1024, 1);
      const int kstep = layer ? 128 : 2;
      if (layer) load_stats(gStat + 2048 * 8);
#pragma unroll UNR
      for (int st = 0; st < 14; st++) {
        if (!(st & 1) && layer) mbar_wait(barAc + (st >> 1) * 8, apar);
        const uint64_t da = dQ + (st >> 1) * 512 + (st & 1) * 2 * kstep, db = mkdesc(ring.acquire(), 4096, 1024, 1);
        wg_fence();
        mma_ss_184(acc, da, db, 1);
        mma_ss_184(acc, da + kstep, db + 128, 1);
        wg_commit();
        if (st > 1) { wg_wait<2>(); ring.release(prev2, elect); }
        prev2 = prev; prev = ring.advance();
      }
      if (layer) {
        finish_stats();
#pragma unroll
        for (int j = 0; j < 7; j++) { xs[j][0] = lds32(abuf + slice_off(j, 0)); xs[j][1] = lds32(abuf + slice_off(j, 1)); }
      }
      wg_wait<0>(); reg_fence(acc);
      ring.release(prev2, elect); ring.release(prev, elect);
      STAMP(1 + layer * 12);
      uint32_t f[3][14];
      auto frags = [&](const int p0, const int p1) {
        const float2* cs = reinterpret_cast<const float2*>(sg + OFF_CS) + t;
        const float mr0 = -mean[0] * rstd[0], mr1 = -mean[1] * rstd[1];
#pragma unroll
        for (int p = p0; p < p1; p++)
#pragma unroll
          for (int j = 0; j < 7; j++) {
            const float2 s = cs[p * 32 + j * 4];
            const int b = p * 32 + j * 4;
            f[p][2 * j] = pack(fmaf(acc[b], rstd[0], s.x * mr0), fmaf(acc[b + 1], rstd[0], s.y * mr0));
            f[p][2 * j + 1] = pack(fmaf(acc[b + 2], rstd[1], s.x * mr1), fmaf(acc[b + 3], rstd[1], s.y * mr1));
          }
      };
      frags(1, 2);
      float pk[28]; reg_def(pk);
      const uint64_t dW = mkdesc(sb + OFF_WPHI, 4096, 1024, 1);
      wg_fence();
#pragma unroll
      for (int s = 0; s < 4; s++) {
        mma_rs_56(pk, f[1][4 * s], f[1][4 * s + 1], s < 3 ? f[1][(4 * s + 2) % 14] : 0u, s < 3 ? f[1][(4 * s + 3) % 14] : 0u, dW + s * 128, s);
      }
      wg_commit();
      frags(2, 3);
      bar_wg(c);
      const uint32_t srow = abuf + stsm_off, ones = t == 0 ? 0x3F803F80u : 0u;
#pragma unroll
      for (int jp = 0; jp < 4; jp++)
        stsm4(srow + 16384 + (((2 * jp + stsm_hi) ^ (lane & 7)) << 4), f[2][4 * jp], f[2][4 * jp + 1],
              jp < 3 ? f[2][(4 * jp + 2) % 14] : ones, jp < 3 ? f[2][(4 * jp + 3) % 14] : ones);
      wg_wait<0>(); reg_fence(pk);
      {
        dual_softmax(pk, phiq);
#pragma unroll
        for (int e = 0; e < 2; e++)
#pragma unroll
          for (int jp = 0; jp < 4; jp++)
            stsm4(srow + e * 8192 + (((2 * jp + stsm_hi) ^ (lane & 7)) << 4), phiq[e][2 * jp], phiq[2 + e][2 * jp],
                  jp < 3 ? phiq[e][(2 * jp + 1) % 7] : 0u, jp < 3 ? phiq[2 + e][(2 * jp + 1) % 7] : 0u);
        fence_async_smem();
        bar_sync<3, 256>();
        float kv[32], kw[32]; reg_def(kv); reg_def(kw);
        const uint64_t dP = mkdesc(sb + c * 8192, 4096, 1024, 1), dV = mkdesc(sb + 16384, 4096, 1024, 1);
        wg_fence();
#pragma unroll
        for (int s = 0; s < 4; s++) { mma_ss_64t(kv, dP + s * 128, dV + s * 128, s); mma_ss_64t(kw, dP + ABYTES / 16 + s * 128, dV + ABYTES / 16 + s * 128, s); }
        wg_commit();
        if (layer == 0) mbar_wait(barCS, 0);
        wg_wait<0>(); reg_fence(kv); reg_fence(kw);
#pragma unroll
        for (int i = 0; i < 32; i++) kv[i] += kw[i];
        float4* kvg = gKV + ((layer * 8 + r) * 2 + c) * 640 + (tid & 127);
#pragma unroll
        for (int i = 0; i < 5; i++) {
          float v0, v1, v2, v3;
          if (i == 4) { v0 = kv[28]; v1 = kv[29]; v2 = kv[30]; v3 = kv[31]; }
          else { v0 = c ? kv[12 + 4 * i] : kv[4 * i]; v1 = c ? kv[13 + 4 * i] : kv[1 + 4 * i]; v2 = c ? kv[14 + 4 * i] : kv[2 + 4 * i]; v3 = c ? kv[15 + 4 * i] : kv[3 + 4 * i]; }
          const bool use = i == 4 ? t == 0 : (i == 0 ? (c == 0 || t >= 2) : (i == 3 ? (c == 1 || t < 2) : true));
          if (use) asm volatile("red.relaxed.gpu.global.add.v4.f32 [%0], {%1,%2,%3,%4};" ::"l"(kvg + i * 128), "f"(v0), "f"(v1), "f"(v2), "f"(v3) : "memory");
        }
        asm volatile("bar.arrive 4, 288;" ::: "memory");
        STAMP(2 + layer * 12);
      }
      frags(0, 1);
      float pq[28]; reg_def(pq);
      wg_fence();
#pragma unroll
      for (int s = 0; s < 4; s++)
        mma_rs_56(pq, f[0][4 * s], f[0][4 * s + 1], s < 3 ? f[0][(4 * s + 2) % 14] : 0u, s < 3 ? f[0][(4 * s + 3) % 14] : 0u, dW + s * 128, s);
      wg_commit();
      wg_wait<0>(); reg_fence(pq);
      dual_softmax(pq, phiq);
    }
    {
      mbar_wait(barX + 16, layer);
      STAMP(3 + layer * 12);
      const float4* kvg = gKV + (layer * 8 + r) * 1280 + c * 640 + (tid & 127);
      uint4 kk[5];
#pragma unroll
      for (int i = 0; i < 5; i++) kk[i] = ldcg4(kvg + i * 128);
      uint32_t f[5][2];
#pragma unroll
      for (int i = 0; i < 5; i++) { f[i][0] = pack(__uint_as_float(kk[i].x), __uint_as_float(kk[i].y)); f[i][1] = pack(__uint_as_float(kk[i].z), __uint_as_float(kk[i].w)); }
      const uint32_t zm = c ? 0xFFFF0000u : 0xFFFFu;
      const uint32_t srow = abuf + 24576 + stsm_off;
#pragma unroll
      for (int jp = 0; jp < 4; jp++) {
        uint32_t v[2][2];
#pragma unroll
        for (int u = 0; u < 2; u++) {
          const int j = 2 * jp + u;
#pragma unroll
          for (int hh = 0; hh < 2; hh++) v[u][hh] = j == 7 ? f[4][hh] & zm : (c ? (j >= 3 ? f[(j + 2) % 5][hh] : 0u) : (j < 4 ? f[j % 5][hh] : 0u));
        }
        stsm4(srow + (((2 * jp + stsm_hi) ^ (lane & 7)) << 4), v[0][0], v[0][1], v[1][0], v[1][1]);
      }
      fence_async_smem();
      bar_sync<3, 256>();
      float num[32], nub[32]; reg_def(num); reg_def(nub);
      const uint64_t dK = mkdesc(sb + 24576, 4096, 1024, 1);
      wg_fence();
#pragma unroll
      for (int s = 0; s < 4; s++) {
        mma_rs_64(num, phiq[0][2 * s], phiq[2][2 * s], s < 3 ? phiq[0][(2 * s + 1) % 7] : 0u, s < 3 ? phiq[2][(2 * s + 1) % 7] : 0u, dK + s * 128, s);
        mma_rs_64(nub, phiq[1][2 * s], phiq[3][2 * s], s < 3 ? phiq[1][(2 * s + 1) % 7] : 0u, s < 3 ? phiq[3][(2 * s + 1) % 7] : 0u, dK + ABYTES / 16 + s * 128, s);
      }
      wg_commit();
      wg_wait<0>(); reg_fence(num); reg_fence(nub);
      bar_sync<3, 256>();
#pragma unroll
      for (int i = 12; i < 32; i++) num[i] += nub[i];
      float rd[4];
#pragma unroll
      for (int i = 0; i < 4; i++) rd[i] = __fdividef(1.f, __shfl_sync(~0u, num[28 + i], lane & ~3) + 1e-6f);
      unsigned char* img = gImg + (size_t)(G * 2 + c) * ABYTES;
#pragma unroll
      for (int j = 0; j < 7; j++) {
        const bool hb = j > 3 || (j == 3 && t >= 2);
        const float r0 = hb ? rd[1] : rd[0], r1 = hb ? rd[3] : rd[2];
        *reinterpret_cast<uint32_t*>(img + slice_off(j, 0)) = pack(num[4 * j] * r0, num[4 * j + 1] * r0);
        *reinterpret_cast<uint32_t*>(img + slice_off(j, 1)) = pack(num[4 * j + 2] * r1, num[4 * j + 3] * r1);
      }
      STAMP(4 + layer * 12);
      gather(fl, img);
      STAMP(5 + layer * 12);
    }
    {
      float acc[28], acc2[28]; reg_def(acc); reg_def(acc2); reg_fence(acc); reg_fence(acc2);
      int sl[4];
      ring.uniform();
#pragma unroll
      for (int st = 0; st < 4; st++) {
        const uint64_t db = mkdesc(ring.acquire(), 4096, 1024, 1);
        sl[st] = ring.advance();
#pragma unroll
        for (int s = 0; s < 7; s++) {
          const int ks = st * 7 + s;
          if (!(ks & 3)) mbar_wait(barAc + (ks >> 2) * 8, apar);
          if (!(ks & 3) || !s) wg_fence();
          if (ks & 1) mma_ss_56(acc2, dA + ks * 128, db + s * 128, ks > 1); else mma_ss_56(acc, dA + ks * 128, db + s * 128, ks > 1);
        }
        wg_commit();
      }
      wg_wait<0>(); reg_fence(acc); reg_fence(acc2);
      unsigned char* img = gImg + (size_t)(32 + G * 2 + c) * ABYTES;
#pragma unroll
      for (int hh = 0; hh < 2; hh++) {
        float s = 0.f, q = 0.f;
#pragma unroll
        for (int j = 0; j < 7; j++) {
          xs[j][hh] = pack(lo(xs[j][hh]) + (acc[4 * j + 2 * hh] + acc2[4 * j + 2 * hh]), hi(xs[j][hh]) + (acc[4 * j + 2 * hh + 1] + acc2[4 * j + 2 * hh + 1]));
          *reinterpret_cast<uint32_t*>(img + slice_off(j, hh)) = xs[j][hh];
          s += lo(xs[j][hh]) + hi(xs[j][hh]);
        }
        s += __shfl_xor_sync(~0u, s, 1); s += __shfl_xor_sync(~0u, s, 2);
        s *= 1.f / 56.f;
#pragma unroll
        for (int j = 0; j < 7; j++) { const float a = lo(xs[j][hh]) - s, b = hi(xs[j][hh]) - s; q = fmaf(a, a, q); q = fmaf(b, b, q); }
        q += __shfl_xor_sync(~0u, q, 1); q += __shfl_xor_sync(~0u, q, 2);
        if (t == 0) gStat[(size_t)(row0 + w * 16 + hh * 8 + g) * 8 + r] = make_float2(s, q);
      }
#pragma unroll
      for (int j = 0; j < 7; j++) xs[j][0] = xs[j][1] = 0u;
      STAMP(6 + layer * 12);
      gather(fl + 32, img);
#pragma unroll
      for (int st = 0; st < 4; st++) ring.release(sl[st], elect);
      STAMP(7 + layer * 12);
    }
    {
      uint32_t hf[28][2];
      {
        float acc[112]; reg_def(acc);
        int prev = 0, prev2 = 0;
        load_stats(gStat);
        ring.uniform();
#pragma unroll UNR
        for (int st = 0; st < 14; st++) {
          if (!(st & 1)) mbar_wait(barAc + (st >> 1) * 8, apar);
          const uint64_t da = dA + st * 256, db = mkdesc(ring.acquire(), 2048, 512, 2);
          wg_fence();
          mma_ss_224(acc, da, db, 1);
          mma_ss_224(acc, da + 128, db + 64, 1);
          wg_commit();
          if (st > 1) { wg_wait<2>(); ring.release(prev2, elect); }
          prev2 = prev; prev = ring.advance();
        }
        finish_stats();
        if (layer == 0) mbar_wait(barCS + 8, 0);
        wg_wait<0>(); reg_fence(acc);
        ring.release(prev2, elect); ring.release(prev, elect);
        STAMP(8 + layer * 12);
        const float4* bs = reinterpret_cast<const float4*>(sg + OFF_B1) + t;
        const float mr0 = -mean[0] * rstd[0], mr1 = -mean[1] * rstd[1];
#pragma unroll
        for (int j = 0; j < 28; j++) {
          const float4 b = bs[4 * j];
          const float2 s = make_float2(b.z, b.w);
          hf[j][0] = relu_sq(fmaf(acc[4 * j], rstd[0], fmaf(s.x, mr0, b.x)), fmaf(acc[4 * j + 1], rstd[0], fmaf(s.y, mr0, b.y)));
          hf[j][1] = relu_sq(fmaf(acc[4 * j + 2], rstd[1], fmaf(s.x, mr1, b.x)), fmaf(acc[4 * j + 3], rstd[1], fmaf(s.y, mr1, b.y)));
        }
      }
      unsigned char* pd[2]; int pstr[2];
#pragma unroll
      for (int hh = 0; hh < 2; hh++) {
        const bool own = 2 * w + hh == r;
        pd[hh] = own ? sg + c * ABYTES + (lane >> 4) * 1024 + (r ^ 1) * 128 + (lane & 15) * 8
                     : gP + (size_t)(((G * 2 + c) * 8 + 2 * w + hh) * 8 + r) * 7168 + lane * 8;
        pstr[hh] = own ? 2048 : 256;
      }
      uint2 pk[8] = {};
      ring.uniform();
#pragma unroll 1
      for (int ch = 0; ch < 7; ch++) {
        float acc[32], acc2[32]; reg_def(acc); reg_def(acc2);
        const uint64_t db0 = mkdesc(ring.acquire(), 4096, 1024, 1);
        const int sl0 = ring.advance();
        const uint64_t db1 = mkdesc(ring.acquire(), 4096, 1024, 1);
        const int sl1 = ring.advance();
        wg_fence();
#pragma unroll
        for (int s = 0; s < 7; s++) {
          mma_rs_64(acc, hf[2 * s][0], hf[2 * s][1], hf[2 * s + 1][0], hf[2 * s + 1][1], db0 + s * 128, s);
          mma_rs_64(acc2, hf[14 + 2 * s][0], hf[14 + 2 * s][1], hf[15 + 2 * s][0], hf[15 + 2 * s][1], db1 + s * 128, s);
        }
        wg_commit();
        if (ch > 0) {
#pragma unroll
          for (int i = 0; i < 8; i++) { *reinterpret_cast<uint2*>(pd[i & 1]) = pk[i]; pd[i & 1] += pstr[i & 1]; }
        }
        wg_wait<0>(); reg_fence(acc); reg_fence(acc2); ring.release(sl0, elect && ch < 5); ring.release(sl1, elect && ch < 5);
#pragma unroll
        for (int i = 0; i < 8; i++) {
          const int b = (i >> 1) * 8 + (i & 1) * 2;
          pk[i] = make_uint2((pack(acc[b] + acc2[b], acc[b + 1] + acc2[b + 1]) & ~1u) | (layer ^ 1), pack(acc[b + 4] + acc2[b + 4], acc[b + 5] + acc2[b + 5]));
        }
      }
#pragma unroll
      for (int i = 0; i < 8; i++) { *reinterpret_cast<uint2*>(pd[i & 1]) = pk[i]; pd[i & 1] += pstr[i & 1]; }
      STAMP(9 + layer * 12);
    }
    {
      uint32_t bx[14];
#pragma unroll
      for (int j = 0; j < 14; j++) bx[j] = __ldg(reinterpret_cast<const uint32_t*>(b2 + (j >> 1) * 64 + w * 16 + (j & 1) * 8 + 2 * t));
      const unsigned char* psrc = gP + (size_t)(((G * 2 + c) * 8 + r) * 8) * 7168 + w * 256 + lane * 8;
      unsigned char* img = gImg + (size_t)(64 + G * 2 + c) * ABYTES;
      uint2 pv[7][7];
      const unsigned char* ps[7];
#pragma unroll
      for (int s = 0; s < 7; s++) ps[s] = psrc + ((r + 1 + s) & 7) * 7168;
#pragma unroll
      for (int i = 0; i < 5; i++)
#pragma unroll
        for (int s = 0; s < 7; s++) pv[s][i] = ldcg2(ps[s] + i * 1024);
      bar_wg(c);
      const uint32_t off = w * 2048 + r * 128 + lane * 4;
      unsigned char* dst = layer ? reinterpret_cast<unsigned char*>(out + (size_t)(row0 + r * 8 + g) * DM + w * 16 + 4 * t) : img + off;
      float sm = 0.f, q = 0.f;
#pragma unroll
      for (int i = 0; i < 7; i++) {
        const uint2 own = *reinterpret_cast<const uint2*>(sg + c * ABYTES + i * 8192 + w * 2048 + (lane >> 4) * 1024 + (r ^ 1) * 128 + (lane & 15) * 8);
#pragma unroll 1
        for (int n = 0; n < (1 << 16); n++) {
          const uint32_t all = pv[0][i].x & pv[1][i].x & pv[2][i].x & pv[3][i].x & pv[4][i].x & pv[5][i].x & pv[6][i].x;
          const uint32_t any = pv[0][i].x | pv[1][i].x | pv[2][i].x | pv[3][i].x | pv[4][i].x | pv[5][i].x | pv[6][i].x;
          if (!__any_sync(~0u, (layer ? any : ~all) & 1u)) break;
#pragma unroll
          for (int s = 0; s < 7; s++) pv[s][i] = ldcg2(ps[s] + i * 1024);
        }
        if (i < 2) {
#pragma unroll
          for (int s = 0; s < 7; s++) pv[s][5 + (i & 1)] = ldcg2(ps[s] + (5 + i) * 1024);
        }
#pragma unroll
        for (int jj = 0; jj < 2; jj++) {
          const int j = 2 * i + jj;
          const uint32_t xo = lds32(abuf + off + i * 8192 + jj * 1024), uo = jj ? own.y : own.x;
          float y0 = lo(bx[j]) + lo(xo) + lo(uo), y1 = hi(bx[j]) + hi(xo) + hi(uo);
#pragma unroll
          for (int s = 0; s < 7; s++) { const uint32_t u = jj ? pv[s][i].y : pv[s][i].x; y0 += lo(u); y1 += hi(u); }
          bx[j] = pack(y0, y1);
          if (!layer) *reinterpret_cast<uint32_t*>(dst + (i * 8 + jj) * 1024) = bx[j];
          sm += lo(bx[j]) + hi(bx[j]);
        }
        if (layer) {
          const int sl = (lane & ~3) | ((t & 1) << 1);
          const uint32_t a0 = __shfl_sync(~0u, bx[2 * i], sl), a1 = __shfl_sync(~0u, bx[2 * i], sl + 1);
          const uint32_t b0 = __shfl_sync(~0u, bx[2 * i + 1], sl), b1v = __shfl_sync(~0u, bx[2 * i + 1], sl + 1);
          *reinterpret_cast<uint2*>(dst + i * 128) = t < 2 ? make_uint2(a0, a1) : make_uint2(b0, b1v);
        }
      }
      if (layer) break;
      sm += __shfl_xor_sync(~0u, sm, 1); sm += __shfl_xor_sync(~0u, sm, 2);
      sm *= 1.f / 112.f;
#pragma unroll
      for (int j = 0; j < 14; j++) { const float a = lo(bx[j]) - sm, b = hi(bx[j]) - sm; q = fmaf(a, a, q); q = fmaf(b, b, q); }
      q += __shfl_xor_sync(~0u, q, 1); q += __shfl_xor_sync(~0u, q, 2);
      if (t < 2) gStat[(size_t)(2048 + row0 + r * 8 + g) * 8 + 2 * w + t] = make_float2(sm, q * 0.5f);
      STAMP(11);
      gather(fl + 64, img);
#pragma unroll
      for (int i = 3; i < 7; i++) ring.release((ring.slot + i) % NSLOT, elect);
      STAMP(12);
    }
  }
  STAMP(30);
  if (tid == 0) asm volatile("red.relaxed.gpu.global.add.u32 [%0], 1;" ::"l"(gFlag + FL_DONE * 32) : "memory");
  }
}

typedef CUresult (*EncFn)(CUtensorMap*, CUtensorMapDataType, cuuint32_t, void*, const cuuint64_t*, const cuuint64_t*,
                          const cuuint32_t*, const cuuint32_t*, CUtensorMapInterleave, CUtensorMapSwizzle,
                          CUtensorMapL2promotion, CUtensorMapFloatOOBfill);

void make_map(EncFn enc, CUtensorMap* m, void* p, int rank, uint64_t d0, uint64_t d1, uint64_t d2, uint64_t s1, uint64_t s2,
              uint32_t b0, uint32_t b1, uint32_t b2, CUtensorMapSwizzle sw) {
  cuuint64_t dims[3] = {d0, d1, d2}, strides[2] = {s1, s2};
  cuuint32_t box[3] = {b0, b1, b2}, es[3] = {1, 1, 1};
  enc(m, CU_TENSOR_MAP_DATA_TYPE_BFLOAT16, rank, p, dims, strides, box, es, CU_TENSOR_MAP_INTERLEAVE_NONE, sw,
      CU_TENSOR_MAP_L2_PROMOTION_L2_128B, CU_TENSOR_MAP_FLOAT_OOB_FILL_NONE);
}

}

extern "C" void kernel_launch(void* const* d_in, const int* in_sizes, int n_in, void* d_out, int out_size) {
  static EncFn enc = nullptr;
  if (!enc) {
    cudaDriverEntryPointQueryResult st;
    void* fn = nullptr;
    cudaGetDriverEntryPoint("cuTensorMapEncodeTiled", &fn, cudaEnableDefault, &st);
    enc = (EncFn)fn;
    cudaFuncSetAttribute(fused_kernel, cudaFuncAttributeMaxDynamicSharedMemorySize, SMEM_BYTES);
  }
  CUtensorMap mQKV, mWO, mW1, mW2, mX;
  make_map(enc, &mX, d_in[0], 2, 448, 2048, 1, 896, 0, 64, 64, 1, CU_TENSOR_MAP_SWIZZLE_128B);
  make_map(enc, &mQKV, d_in[1], 3, 448, 448, 3, 2688, 896, 64, 32, 3, CU_TENSOR_MAP_SWIZZLE_128B);
  make_map(enc, &mWO, d_in[3], 2, 448, 448, 1, 896, 0, 64, 112, 1, CU_TENSOR_MAP_SWIZZLE_128B);
  make_map(enc, &mW1, d_in[5], 3, 32, 448, 56, 3584, 64, 32, 32, 7, CU_TENSOR_MAP_SWIZZLE_64B);
  make_map(enc, &mW2, d_in[7], 2, 448, 1792, 1, 896, 0, 64, 112, 1, CU_TENSOR_MAP_SWIZZLE_128B);
  fused_kernel<<<NCTA, 384, SMEM_BYTES, cudaStreamPerThread>>>(
      mQKV, mWO, mW1, mW2, mX, (const __nv_bfloat16*)d_in[2], (const __nv_bfloat16*)d_in[6],
      (const __nv_bfloat16*)d_in[8], (const __nv_bfloat16*)d_in[1], (const __nv_bfloat16*)d_in[3], (const __nv_bfloat16*)d_in[5],
      (const __nv_bfloat16*)d_in[7], (__nv_bfloat16*)d_out);
}
```

```cpp
#include <cuda_runtime.h>
#include <cuda_bf16.h>
#include <cuda.h>
#include <stdint.h>

namespace {

constexpr int DM = 448, NCTA = 128;
constexpr int ABYTES = 57344;
constexpr int SLOT = 14336, NSLOT = 7;
constexpr int OFF_RING = 2 * ABYTES;
constexpr int OFF_WPHI = OFF_RING + NSLOT * SLOT;
constexpr int OFF_B1 = OFF_WPHI + 8192;
constexpr int OFF_CS = OFF_B1 + 1792;
constexpr int OFF_BAR = OFF_CS + 768;
constexpr int SMEM_BYTES = OFF_BAR + 272 + 1024;
constexpr int TILES_PER_LAYER = 46;

__device__ __align__(1024) unsigned char gP[16 * 2 * 8 * 8 * 7168];
__device__ __align__(1024) unsigned char gImg[3 * 32 * ABYTES];
__device__ __align__(1024) float2 gStat[2 * 2048 * 8];
__device__ __align__(1024) float4 gKV[2 * 8 * 2 * 5 * 128];
__device__ __align__(1024) float4 gCS[8 * 16 * 104];
__device__ __align__(128) unsigned gFlag[(2 * 32 * 7 + 32 + 1 + 16) * 32];
#define STAMP(i)

__device__ __forceinline__ uint32_t smem_u32(const void* p) { return (uint32_t)__cvta_generic_to_shared(p); }
__device__ __forceinline__ void mbar_init(uint32_t b, int c) { asm volatile("mbarrier.init.shared::cta.b64 [%0], %1;" ::"r"(b), "r"(c)); }
__device__ __forceinline__ void mbar_expect(uint32_t b, int bytes) { asm volatile("mbarrier.arrive.expect_tx.shared::cta.b64 _, [%0], %1;" ::"r"(b), "r"(bytes) : "memory"); }
__device__ __forceinline__ void mbar_arrive(uint32_t b) { asm volatile("mbarrier.arrive.shared::cta.b64 _, [%0];" ::"r"(b) : "memory"); }
__device__ __forceinline__ void mbar_wait(uint32_t b, int par) {
  uint32_t ok; int n = 0;
#pragma unroll 1
  while (true) {
    asm volatile("{.reg .pred p; mbarrier.try_wait.parity.shared::cta.b64 p, [%1], %2; selp.u32 %0,1,0,p;}" : "=r"(ok) : "r"(b), "r"(par) : "memory");
    if (ok) break;
    if (++n > (1 << 20)) break;
  }
}
__device__ __forceinline__ void flag_wait(const unsigned* f, unsigned target) {
  unsigned v; int n = 0;
#pragma unroll 1
  while (true) {
    asm volatile("ld.relaxed.gpu.global.u32 %0, [%1];" : "=r"(v) : "l"(f) : "memory");
    if ((int)(v - target) >= 0) break;
    if (++n > (1 << 18)) break;
  }
}
__device__ __forceinline__ void flag_arrive(unsigned* f) { asm volatile("red.release.gpu.global.add.u32 [%0], 1;" ::"l"(f) : "memory"); }
__device__ __forceinline__ bool elect_one() {
  uint32_t p; asm volatile("{.reg .pred P; elect.sync _|P, 0xffffffff; selp.u32 %0, 1, 0, P;}" : "=r"(p)); return p;
}
__device__ __forceinline__ void fence_async() { asm volatile("fence.proxy.async.global;" ::: "memory"); }
__device__ __forceinline__ void fence_async_smem() { asm volatile("fence.proxy.async.shared::cta;" ::: "memory"); }
template <int ID, int N> __device__ __forceinline__ void bar_sync() { asm volatile("bar.sync %0, %1;" ::"n"(ID), "n"(N) : "memory"); }
__device__ __forceinline__ void bar_wg(int c) { if (c) bar_sync<2, 128>(); else bar_sync<1, 128>(); }
__device__ __forceinline__ void wg_fence() { asm volatile("wgmma.fence.sync.aligned;" ::: "memory"); }
__device__ __forceinline__ void wg_commit() { asm volatile("wgmma.commit_group.sync.aligned;" ::: "memory"); }
template <int N> __device__ __forceinline__ void wg_wait() { asm volatile("wgmma.wait_group.sync.aligned %0;" ::"n"(N) : "memory"); }
template <int N> __device__ __forceinline__ void reg_fence(float (&d)[N]) {
#pragma unroll
  for (int i = 0; i < N; i++) asm volatile("" : "+f"(d[i])::"memory");
}
template <int N> __device__ __forceinline__ void reg_def(float (&d)[N]) {
#pragma unroll
  for (int i = 0; i < N; i++) d[i] = 0.f;
}
__device__ __forceinline__ uint64_t mkdesc(uint32_t addr, uint32_t lbo, uint32_t sbo, uint64_t swz) {
  return (uint64_t)((addr & 0x3FFFF) >> 4) | ((uint64_t)(lbo >> 4) << 16) | ((uint64_t)(sbo >> 4) << 32) | (swz << 62);
}
__device__ __forceinline__ uint32_t pack(float a, float b) {
  uint32_t r; asm("cvt.rn.bf16x2.f32 %0, %1, %2;" : "=r"(r) : "f"(b), "f"(a)); return r;
}
__device__ __forceinline__ uint32_t relu_sq(float a, float b) {
  uint32_t r; asm("{.reg .b32 v; cvt.rn.relu.bf16x2.f32 v, %1, %2; mul.rn.bf16x2 %0, v, v;}" : "=r"(r) : "f"(b), "f"(a)); return r;
}
__device__ __forceinline__ float lo(uint32_t u) { return __uint_as_float(u << 16); }
__device__ __forceinline__ float hi(uint32_t u) { return __uint_as_float(u & 0xFFFF0000u); }
__device__ __forceinline__ float ex2(float x) { float y; asm("ex2.approx.ftz.f32 %0, %1;" : "=f"(y) : "f"(x)); return y; }
__device__ __forceinline__ void stsm4(uint32_t a, uint32_t r0, uint32_t r1, uint32_t r2, uint32_t r3) {
  asm volatile("stmatrix.sync.aligned.m8n8.x4.shared.b16 [%0], {%1,%2,%3,%4};" ::"r"(a), "r"(r0), "r"(r1), "r"(r2), "r"(r3) : "memory");
}
__device__ __forceinline__ void tma3(uint32_t dst, const CUtensorMap* m, int c0, int c1, int c2, uint32_t bar) {
  asm volatile("cp.async.bulk.tensor.3d.shared::cluster.global.mbarrier::complete_tx::bytes [%0], [%1, {%3,%4,%5}], [%2];"
               ::"r"(dst), "l"(m), "r"(bar), "r"(c0), "r"(c1), "r"(c2) : "memory");
}
__device__ __forceinline__ void tma2(uint32_t dst, const CUtensorMap* m, int c0, int c1, uint32_t bar) {
  asm volatile("cp.async.bulk.tensor.2d.shared::cluster.global.mbarrier::complete_tx::bytes [%0], [%1, {%3,%4}], [%2];"
               ::"r"(dst), "l"(m), "r"(bar), "r"(c0), "r"(c1) : "memory");
}
__device__ __forceinline__ uint32_t lds32(uint32_t a) { uint32_t v; asm volatile("ld.shared.u32 %0, [%1];" : "=r"(v) : "r"(a) : "memory"); return v; }
__device__ __forceinline__ void bulk_ld(uint32_t dst, const void* src, int bytes, uint32_t bar) {
  asm volatile("cp.async.bulk.shared::cluster.global.mbarrier::complete_tx::bytes [%0], [%1], %2, [%3];" ::"r"(dst), "l"(src), "r"(bytes), "r"(bar) : "memory");
}
__device__ __forceinline__ uint4 ldcg4(const void* p) {
  uint4 v; asm volatile("ld.global.cg.v4.u32 {%0,%1,%2,%3}, [%4];" : "=r"(v.x), "=r"(v.y), "=r"(v.z), "=r"(v.w) : "l"(p) : "memory"); return v;
}

__device__ __forceinline__ uint2 ldcg2(const void* p) {
  uint2 v; asm volatile("ld.global.cg.v2.u32 {%0,%1}, [%2];" : "=r"(v.x), "=r"(v.y) : "l"(p) : "memory"); return v;
}

__device__ __forceinline__ void mma_ss_184(float (&d)[92], uint64_t da, uint64_t db, int acc) {
  asm volatile("{.reg .pred p; setp.ne.b32 p, %94, 0;\n"
    "wgmma.mma_async.sync.aligned.m64n184k16.f32.bf16.bf16 {%0,%1,%2,%3,%4,%5,%6,%7,%8,%9,%10,%11,%12,%13,%14,%15,%16,%17,%18,%19,%20,%21,%22,%23,%24,%25,%26,%27,%28,%29,%30,%31,%32,%33,%34,%35,%36,%37,%38,%39,%40,%41,%42,%43,%44,%45,%46,%47,%48,%49,%50,%51,%52,%53,%54,%55,%56,%57,%58,%59,%60,%61,%62,%63,%64,%65,%66,%67,%68,%69,%70,%71,%72,%73,%74,%75,%76,%77,%78,%79,%80,%81,%82,%83,%84,%85,%86,%87,%88,%89,%90,%91}, %92, %93, p, 1, 1, 0, 1;}\n"
    : "+f"(d[0]),"+f"(d[1]),"+f"(d[2]),"+f"(d[3]),"+f"(d[4]),"+f"(d[5]),"+f"(d[6]),"+f"(d[7]),"+f"(d[8]),"+f"(d[9]),"+f"(d[10]),"+f"(d[11]),"+f"(d[12]),"+f"(d[13]),"+f"(d[14]),"+f"(d[15]),"+f"(d[16]),"+f"(d[17]),"+f"(d[18]),"+f"(d[19]),"+f"(d[20]),"+f"(d[21]),"+f"(d[22]),"+f"(d[23]),"+f"(d[24]),"+f"(d[25]),"+f"(d[26]),"+f"(d[27]),"+f"(d[28]),"+f"(d[29]),"+f"(d[30]),"+f"(d[31]),"+f"(d[32]),"+f"(d[33]),"+f"(d[34]),"+f"(d[35]),"+f"(d[36]),"+f"(d[37]),"+f"(d[38]),"+f"(d[39]),"+f"(d[40]),"+f"(d[41]),"+f"(d[42]),"+f"(d[43]),"+f"(d[44]),"+f"(d[45]),"+f"(d[46]),"+f"(d[47]),"+f"(d[48]),"+f"(d[49]),"+f"(d[50]),"+f"(d[51]),"+f"(d[52]),"+f"(d[53]),"+f"(d[54]),"+f"(d[55]),"+f"(d[56]),"+f"(d[57]),"+f"(d[58]),"+f"(d[59]),"+f"(d[60]),"+f"(d[61]),"+f"(d[62]),"+f"(d[63]),"+f"(d[64]),"+f"(d[65]),"+f"(d[66]),"+f"(d[67]),"+f"(d[68]),"+f"(d[69]),"+f"(d[70]),"+f"(d[71]),"+f"(d[72]),"+f"(d[73]),"+f"(d[74]),"+f"(d[75]),"+f"(d[76]),"+f"(d[77]),"+f"(d[78]),"+f"(d[79]),"+f"(d[80]),"+f"(d[81]),"+f"(d[82]),"+f"(d[83]),"+f"(d[84]),"+f"(d[85]),"+f"(d[86]),"+f"(d[87]),"+f"(d[88]),"+f"(d[89]),"+f"(d[90]),"+f"(d[91])
    : "l"(da), "l"(db), "r"(acc));
}
__device__ __forceinline__ void mma_ss_224(float (&d)[112], uint64_t da, uint64_t db, int acc) {
  asm volatile("{.reg .pred p; setp.ne.b32 p, %114, 0;\n"
    "wgmma.mma_async.sync.aligned.m64n224k16.f32.bf16.bf16 {%0,%1,%2,%3,%4,%5,%6,%7,%8,%9,%10,%11,%12,%13,%14,%15,%16,%17,%18,%19,%20,%21,%22,%23,%24,%25,%26,%27,%28,%29,%30,%31,%32,%33,%34,%35,%36,%37,%38,%39,%40,%41,%42,%43,%44,%45,%46,%47,%48,%49,%50,%51,%52,%53,%54,%55,%56,%57,%58,%59,%60,%61,%62,%63,%64,%65,%66,%67,%68,%69,%70,%71,%72,%73,%74,%75,%76,%77,%78,%79,%80,%81,%82,%83,%84,%85,%86,%87,%88,%89,%90,%91,%92,%93,%94,%95,%96,%97,%98,%99,%100,%101,%102,%103,%104,%105,%106,%107,%108,%109,%110,%111}, %112, %113, p, 1, 1, 0, 1;}\n"
    : "+f"(d[0]),"+f"(d[1]),"+f"(d[2]),"+f"(d[3]),"+f"(d[4]),"+f"(d[5]),"+f"(d[6]),"+f"(d[7]),"+f"(d[8]),"+f"(d[9]),"+f"(d[10]),"+f"(d[11]),"+f"(d[12]),"+f"(d[13]),"+f"(d[14]),"+f"(d[15]),"+f"(d[16]),"+f"(d[17]),"+f"(d[18]),"+f"(d[19]),"+f"(d[20]),"+f"(d[21]),"+f"(d[22]),"+f"(d[23]),"+f"(d[24]),"+f"(d[25]),"+f"(d[26]),"+f"(d[27]),"+f"(d[28]),"+f"(d[29]),"+f"(d[30]),"+f"(d[31]),"+f"(d[32]),"+f"(d[33]),"+f"(d[34]),"+f"(d[35]),"+f"(d[36]),"+f"(d[37]),"+f"(d[38]),"+f"(d[39]),"+f"(d[40]),"+f"(d[41]),"+f"(d[42]),"+f"(d[43]),"+f"(d[44]),"+f"(d[45]),"+f"(d[46]),"+f"(d[47]),"+f"(d[48]),"+f"(d[49]),"+f"(d[50]),"+f"(d[51]),"+f"(d[52]),"+f"(d[53]),"+f"(d[54]),"+f"(d[55]),"+f"(d[56]),"+f"(d[57]),"+f"(d[58]),"+f"(d[59]),"+f"(d[60]),"+f"(d[61]),"+f"(d[62]),"+f"(d[63]),"+f"(d[64]),"+f"(d[65]),"+f"(d[66]),"+f"(d[67]),"+f"(d[68]),"+f"(d[69]),"+f"(d[70]),"+f"(d[71]),"+f"(d[72]),"+f"(d[73]),"+f"(d[74]),"+f"(d[75]),"+f"(d[76]),"+f"(d[77]),"+f"(d[78]),"+f"(d[79]),"+f"(d[80]),"+f"(d[81]),"+f"(d[82]),"+f"(d[83]),"+f"(d[84]),"+f"(d[85]),"+f"(d[86]),"+f"(d[87]),"+f"(d[88]),"+f"(d[89]),"+f"(d[90]),"+f"(d[91]),"+f"(d[92]),"+f"(d[93]),"+f"(d[94]),"+f"(d[95]),"+f"(d[96]),"+f"(d[97]),"+f"(d[98]),"+f"(d[99]),"+f"(d[100]),"+f"(d[101]),"+f"(d[102]),"+f"(d[103]),"+f"(d[104]),"+f"(d[105]),"+f"(d[106]),"+f"(d[107]),"+f"(d[108]),"+f"(d[109]),"+f"(d[110]),"+f"(d[111])
    : "l"(da), "l"(db), "r"(acc));
}
__device__ __forceinline__ void mma_ss_56(float (&d)[28], uint64_t da, uint64_t db, int acc) {
  asm volatile("{.reg .pred p; setp.ne.b32 p, %30, 0;\n"
    "wgmma.mma_async.sync.aligned.m64n56k16.f32.bf16.bf16 {%0,%1,%2,%3,%4,%5,%6,%7,%8,%9,%10,%11,%12,%13,%14,%15,%16,%17,%18,%19,%20,%21,%22,%23,%24,%25,%26,%27}, %28, %29, p, 1, 1, 0, 1;}\n"
    : "+f"(d[0]),"+f"(d[1]),"+f"(d[2]),"+f"(d[3]),"+f"(d[4]),"+f"(d[5]),"+f"(d[6]),"+f"(d[7]),"+f"(d[8]),"+f"(d[9]),"+f"(d[10]),"+f"(d[11]),"+f"(d[12]),"+f"(d[13]),"+f"(d[14]),"+f"(d[15]),"+f"(d[16]),"+f"(d[17]),"+f"(d[18]),"+f"(d[19]),"+f"(d[20]),"+f"(d[21]),"+f"(d[22]),"+f"(d[23]),"+f"(d[24]),"+f"(d[25]),"+f"(d[26]),"+f"(d[27])
    : "l"(da), "l"(db), "r"(acc));
}
__device__ __forceinline__ void mma_rs_56(float (&d)[28], uint32_t a0, uint32_t a1, uint32_t a2, uint32_t a3, uint64_t db, int acc) {
  asm volatile("{.reg .pred p; setp.ne.b32 p, %33, 0;\n"
    "wgmma.mma_async.sync.aligned.m64n56k16.f32.bf16.bf16 {%0,%1,%2,%3,%4,%5,%6,%7,%8,%9,%10,%11,%12,%13,%14,%15,%16,%17,%18,%19,%20,%21,%22,%23,%24,%25,%26,%27}, {%28,%29,%30,%31}, %32, p, 1, 1, 1;}\n"
    : "+f"(d[0]),"+f"(d[1]),"+f"(d[2]),"+f"(d[3]),"+f"(d[4]),"+f"(d[5]),"+f"(d[6]),"+f"(d[7]),"+f"(d[8]),"+f"(d[9]),"+f"(d[10]),"+f"(d[11]),"+f"(d[12]),"+f"(d[13]),"+f"(d[14]),"+f"(d[15]),"+f"(d[16]),"+f"(d[17]),"+f"(d[18]),"+f"(d[19]),"+f"(d[20]),"+f"(d[21]),"+f"(d[22]),"+f"(d[23]),"+f"(d[24]),"+f"(d[25]),"+f"(d[26]),"+f"(d[27])
    : "r"(a0), "r"(a1), "r"(a2), "r"(a3), "l"(db), "r"(acc));
}
__device__ __forceinline__ void mma_ss_64t(float (&d)[32], uint64_t da, uint64_t db, int acc) {
  asm volatile("{.reg .pred p; setp.ne.b32 p, %34, 0;\n"
    "wgmma.mma_async.sync.aligned.m64n64k16.f32.bf16.bf16 {%0,%1,%2,%3,%4,%5,%6,%7,%8,%9,%10,%11,%12,%13,%14,%15,%16,%17,%18,%19,%20,%21,%22,%23,%24,%25,%26,%27,%28,%29,%30,%31}, %32, %33, p, 1, 1, 1, 1;}\n"
    : "+f"(d[0]),"+f"(d[1]),"+f"(d[2]),"+f"(d[3]),"+f"(d[4]),"+f"(d[5]),"+f"(d[6]),"+f"(d[7]),"+f"(d[8]),"+f"(d[9]),"+f"(d[10]),"+f"(d[11]),"+f"(d[12]),"+f"(d[13]),"+f"(d[14]),"+f"(d[15]),"+f"(d[16]),"+f"(d[17]),"+f"(d[18]),"+f"(d[19]),"+f"(d[20]),"+f"(d[21]),"+f"(d[22]),"+f"(d[23]),"+f"(d[24]),"+f"(d[25]),"+f"(d[26]),"+f"(d[27]),"+f"(d[28]),"+f"(d[29]),"+f"(d[30]),"+f"(d[31])
    : "l"(da), "l"(db), "r"(acc));
}
__device__ __forceinline__ void mma_rs_64(float (&d)[32], uint32_t a0, uint32_t a1, uint32_t a2, uint32_t a3, uint64_t db, int acc) {
  asm volatile("{.reg .pred p; setp.ne.b32 p, %37, 0;\n"
    "wgmma.mma_async.sync.aligned.m64n64k16.f32.bf16.bf16 {%0,%1,%2,%3,%4,%5,%6,%7,%8,%9,%10,%11,%12,%13,%14,%15,%16,%17,%18,%19,%20,%21,%22,%23,%24,%25,%26,%27,%28,%29,%30,%31}, {%32,%33,%34,%35}, %36, p, 1, 1, 1;}\n"
    : "+f"(d[0]),"+f"(d[1]),"+f"(d[2]),"+f"(d[3]),"+f"(d[4]),"+f"(d[5]),"+f"(d[6]),"+f"(d[7]),"+f"(d[8]),"+f"(d[9]),"+f"(d[10]),"+f"(d[11]),"+f"(d[12]),"+f"(d[13]),"+f"(d[14]),"+f"(d[15]),"+f"(d[16]),"+f"(d[17]),"+f"(d[18]),"+f"(d[19]),"+f"(d[20]),"+f"(d[21]),"+f"(d[22]),"+f"(d[23]),"+f"(d[24]),"+f"(d[25]),"+f"(d[26]),"+f"(d[27]),"+f"(d[28]),"+f"(d[29]),"+f"(d[30]),"+f"(d[31])
    : "r"(a0), "r"(a1), "r"(a2), "r"(a3), "l"(db), "r"(acc));
}

__device__ __forceinline__ void dual_softmax(const float (&p)[28], uint32_t (&phi)[4][7]) {
  constexpr float L2E = 1.4426950408889634f;
#pragma unroll
  for (int i = 0; i < 4; i++) {
    float mx = p[i], mn = p[i];
#pragma unroll
    for (int j = 1; j < 7; j++) { mx = fmaxf(mx, p[4 * j + i]); mn = fminf(mn, p[4 * j + i]); }
    mx = fmaxf(mx, __shfl_xor_sync(~0u, mx, 1)); mn = fminf(mn, __shfl_xor_sync(~0u, mn, 1));
    mx = fmaxf(mx, __shfl_xor_sync(~0u, mx, 2)); mn = fminf(mn, __shfl_xor_sync(~0u, mn, 2));
    float a[7], b[7], sa = 0.f, sb = 0.f;
    const float mxl = mx * L2E, mnl = mn * L2E;
#pragma unroll
    for (int j = 0; j < 7; j++) {
      a[j] = ex2(fmaf(p[4 * j + i], L2E, -mxl)); b[j] = ex2(fmaf(p[4 * j + i], -L2E, mnl));
      sa += a[j]; sb += b[j];
    }
    sa += __shfl_xor_sync(~0u, sa, 1); sb += __shfl_xor_sync(~0u, sb, 1);
    sa += __shfl_xor_sync(~0u, sa, 2); sb += __shfl_xor_sync(~0u, sb, 2);
    const float ra = __fdividef(1.f, sa), rb = __fdividef(1.f, sb);
#pragma unroll
    for (int j = 0; j < 7; j++) phi[i][j] = pack(a[j] * ra, b[j] * rb);
  }
}

struct Ring {
  uint32_t full, empty, base; int slot, par;
  __device__ __forceinline__ void uniform() { slot = __shfl_sync(~0u, slot, 0); par = __shfl_sync(~0u, par, 0); }
  __device__ __forceinline__ uint32_t acquire() { mbar_wait(full + slot * 8, par); return base + slot * SLOT; }
  __device__ __forceinline__ int advance() { int s = slot; if (++slot == NSLOT) { slot = 0; par ^= 1; } return s; }
  __device__ __forceinline__ void release(int s, bool elect) { if (elect) mbar_arrive(empty + s * 8); }
};
constexpr int UNR = 14;
constexpr int FL_KV = 448, FL_CS = FL_KV + 16, FL_DONE = FL_KV + 32;

__global__ void __launch_bounds__(384, 1)
fused_kernel(const __grid_constant__ CUtensorMap mQKV, const __grid_constant__ CUtensorMap mWO,
             const __grid_constant__ CUtensorMap mW1, const __grid_constant__ CUtensorMap mW2,
             const __grid_constant__ CUtensorMap mX, const __nv_bfloat16* __restrict__ wphi,
             const __nv_bfloat16* __restrict__ b1, const __nv_bfloat16* __restrict__ b2,
             const __nv_bfloat16* __restrict__ wqkv, const __nv_bfloat16* __restrict__ wo, const __nv_bfloat16* __restrict__ w1,
             const __nv_bfloat16* __restrict__ w2, __nv_bfloat16* __restrict__ out) {
  extern __shared__ unsigned char smem_raw[];
  const uint32_t sb = (smem_u32(smem_raw) + 1023) & ~1023u;
  unsigned char* sg = smem_raw + (sb - smem_u32(smem_raw));
  const int tid = threadIdx.x, lane = tid & 31;
  const int G = blockIdx.x >> 3, r = blockIdx.x & 7;
  const uint32_t barFull = sb + OFF_BAR, barEmpty = barFull + 56, barA = barEmpty + 56, barCS = barA + 112, barX = barCS + 16;
  const int warp = __shfl_sync(~0u, tid >> 5, 0);
  uint32_t wv[7] = {}, bv = 0;
  if (warp < 8) {
#pragma unroll
    for (int i = 0; i < 7; i++)
      wv[i] = __ldg(reinterpret_cast<const unsigned short*>(wphi) + (56 * r + i * 8 + warp) * 28 + min(lane, 27));
    bv = __ldg(reinterpret_cast<const unsigned short*>(b1) + 224 * r + min(tid, 223));
  }
  if (lane == 0) {
    if (warp >= 10) {
      const int cc = warp - 10;
      mbar_init(barX + cc * 8, 1);
      fence_async_smem();
      mbar_expect(barX + cc * 8, ABYTES);
#pragma unroll 1
      for (int k = 0; k < 7; k++) tma2(sb + cc * ABYTES + k * 8192, &mX, 64 * k, G * 128 + 64 * cc, barX + cc * 8);
    } else if (warp < 7) { mbar_init(barFull + warp * 8, 1); mbar_init(barEmpty + warp * 8, 2); mbar_init(barA + warp * 8, 1); mbar_init(barA + 56 + warp * 8, 1); }
    else if (warp < 9) { mbar_init(barCS + (warp - 7) * 8, 64); if (warp == 7) mbar_init(barX + 16, 1); }
    else
      asm volatile("cp.async.bulk.prefetch.L2.global [%0], %1;" ::"l"((const char*)wqkv + blockIdx.x * 9408), "r"(9408) : "memory");
    asm volatile("fence.mbarrier_init.release.cluster;" ::: "memory");
  }
  if (tid < 192) reinterpret_cast<float*>(sg + OFF_CS)[tid] = 0.f;
  __syncthreads();
  const int wgid = warp >> 2;
  if (wgid == 2) {
    asm volatile("setmaxnreg.dec.sync.aligned.u32 40;");
    if (warp == 8) {
      int slot = 0, par = 1;
#pragma unroll 1
      for (int it = 0; it < 2 * TILES_PER_LAYER; it++) {
        const int i = it >= TILES_PER_LAYER ? it - TILES_PER_LAYER : it;
        mbar_wait(barEmpty + slot * 8, par);
        const uint32_t dst = sb + OFF_RING + slot * SLOT, fb = barFull + slot * 8;
        if (elect_one()) {
          mbar_expect(fb, i < 14 ? 12288 : SLOT);
          if (i < 14) tma3(dst, &mQKV, 56 * r, 32 * i, 0, fb);
          else if (i < 18) tma2(dst, &mWO, 56 * r, 112 * (i - 14), fb);
          else if (i < 32) tma3(dst, &mW1, 0, 32 * (i - 18), 7 * r, fb);
          else tma2(dst, &mW2, 64 * ((i - 32) >> 1), 224 * r + 112 * (i & 1), fb);
        }
        if (++slot == NSLOT) { slot = 0; par ^= 1; }
      }
    } else if (warp == 11) {
      unsigned ep;
      asm volatile("ld.relaxed.gpu.global.u32 %0, [%1];" : "=r"(ep) : "l"(gFlag + FL_DONE * 32) : "memory");
#pragma unroll 1
      for (int layer = 0; layer < 2; layer++) {
        bar_sync<4, 288>();
        if (lane == 0) {
          flag_arrive(gFlag + (FL_KV + layer * 8 + r) * 32);
          flag_wait(gFlag + (FL_KV + layer * 8 + r) * 32, (ep / NCTA + 1) * 16);
          mbar_arrive(barX + 16);
        }
        __syncwarp();
      }
    } else {
      unsigned ep;
      asm volatile("ld.relaxed.gpu.global.u32 %0, [%1];" : "=r"(ep) : "l"(gFlag + FL_DONE * 32) : "memory");
      const int idx = tid - 288;
      ep = (ep / NCTA + 1) * 2;
      if (G == 0) {
#pragma unroll 1
        for (int i = idx; i < 2 * 1280; i += 64) gKV[((i >= 1280) * 7 + r) * 1280 + i] = make_float4(0.f, 0.f, 0.f, 0.f);
        __syncwarp();
        if (lane == 0) flag_arrive(gFlag + (FL_CS + r) * 32);
      }
      mbar_wait(barFull + 48, 0);
      if (idx < 3) {
        const char* pf = idx ? (idx == 1 ? (const char*)w1 : (const char*)w2) + blockIdx.x * 12544 : (const char*)wo + blockIdx.x * 3136;
        asm volatile("cp.async.bulk.prefetch.L2.global [%0], %1;" ::"l"(pf), "r"(idx ? 12544 : 3136) : "memory");
      }
      if (lane == 0) flag_wait(gFlag + (FL_CS + r) * 32, ep);
      __syncwarp();
      mbar_arrive(barCS);
#pragma unroll 1
      for (int ps = 0; ps < 4; ps++) {
        const int ch = min(ps * 16 + (idx >> 2), 48), p = ch / 7, k0 = G * 28 + (idx & 3) * 7;
        const uint4* src = ch >= 21 ? reinterpret_cast<const uint4*>(w1 + (size_t)k0 * 1792 + 224 * r) + (ch - 21)
                                    : reinterpret_cast<const uint4*>(wqkv + (size_t)k0 * 1344 + p * 448 + 56 * r) + (ch - 7 * p);
        uint4 cu[7];
#pragma unroll
        for (int i = 0; i < 7; i++) cu[i] = __ldg(src + i * (ch >= 21 ? 224 : 168));
        float s[8] = {};
#pragma unroll
        for (int i = 0; i < 7; i++) { s[0] += lo(cu[i].x); s[1] += hi(cu[i].x); s[2] += lo(cu[i].y); s[3] += hi(cu[i].y); s[4] += lo(cu[i].z); s[5] += hi(cu[i].z); s[6] += lo(cu[i].w); s[7] += hi(cu[i].w); }
#pragma unroll
        for (int i = 0; i < 8; i++) { s[i] += __shfl_xor_sync(~0u, s[i], 1); s[i] += __shfl_xor_sync(~0u, s[i], 2); }
        if ((idx & 3) < 2) gCS[(r * 16 + G) * 104 + (ch + min(p, 3)) * 2 + (idx & 1)] = (idx & 1) ? make_float4(s[4], s[5], s[6], s[7]) : make_float4(s[0], s[1], s[2], s[3]);
      }
      __syncwarp();
      if (lane == 0) { flag_arrive(gFlag + (FL_CS + 8 + r) * 32); flag_wait(gFlag + (FL_CS + 8 + r) * 32, ep * 16); }
      __syncwarp();
#pragma unroll 1
      for (int j = idx; j < 208; j += 64) {
        float2 a = make_float2(0.f, 0.f);
#pragma unroll 8
        for (int i = 0; i < 16; i++) { const float2 v = __ldcg(reinterpret_cast<const float2*>(gCS + (r * 16 + i) * 104) + j); a.x += v.x; a.y += v.y; }
        *reinterpret_cast<float2*>(sg + (j < 96 ? OFF_CS + j * 8 : OFF_B1 + (j - 96) * 16 + 8)) = a;
      }
      mbar_arrive(barCS + 8);
    }
  } else {
  asm volatile("setmaxnreg.inc.sync.aligned.u32 232;");
  const int c = wgid, w = warp & 3, g = lane >> 2, t = lane & 3;
  int elect_i = (tid & 127) == 0;
  asm volatile("" : "+r"(elect_i));
  const bool elect = elect_i;
  const uint32_t abuf = sb + c * ABYTES, barAc = barA + c * 56;
  const int row0 = G * 128 + c * 64;
  unsigned epoch;
  asm volatile("ld.relaxed.gpu.global.u32 %0, [%1];" : "=r"(epoch) : "l"(gFlag + FL_DONE * 32) : "memory");
  STAMP(24);
  float mean[2], rstd[2] = {0.f, 0.f};
  uint4 su[2] = {};
  uint32_t xs[7][2];
  {
#pragma unroll
    for (int i = 0; i < 8; i++) {
      const int k = i * 8 + (tid >> 5);
      *reinterpret_cast<uint32_t*>(sg + OFF_WPHI + k * 128 + ((g ^ (k & 7)) << 4) + t * 4) = (i < 7 && lane < 28) ? wv[i % 7] << (k >= 28 ? 16 : 0) : 0u;
    }
    if (tid < 224) reinterpret_cast<uint32_t*>(sg + OFF_B1)[(tid >> 1) * 4 + (tid & 1)] = bv << 16;
    mbar_wait(barX + c * 8, 0);
    STAMP(25);
#pragma unroll
    for (int j = 0; j < 7; j++) {
      const int ci = 7 * r + j;
      const uint32_t a = abuf + (ci >> 3) * 8192 + (w * 16 + g) * 128 + (((ci & 7) ^ g) << 4) + t * 4;
      xs[j][0] = lds32(a); xs[j][1] = lds32(a + 1024);
    }
    __syncwarp();
#pragma unroll 1
    for (int hh = 0; hh < 2; hh++) {
      uint4* p = reinterpret_cast<uint4*>(sg + c * ABYTES + (w * 16 + hh * 8 + g) * 128) + t;
      uint4 v[14];
#pragma unroll
      for (int k = 0; k < 14; k++) v[k] = p[(k >> 1) * 512 + ((k ^ g) & 1) * 4];
      float a8[8] = {};
#pragma unroll
      for (int k = 0; k < 14; k++) {
        const uint32_t e[4] = {v[k].x, v[k].y, v[k].z, v[k].w};
#pragma unroll
        for (int z = 0; z < 4; z++) { a8[2 * z] += lo(e[z]); a8[2 * z + 1] += hi(e[z]); }
      }
      float sm = ((a8[0] + a8[1]) + (a8[2] + a8[3])) + ((a8[4] + a8[5]) + (a8[6] + a8[7]));
      sm += __shfl_xor_sync(~0u, sm, 1); sm += __shfl_xor_sync(~0u, sm, 2);
      sm *= 1.f / DM;
#pragma unroll
      for (int k = 0; k < 14; k++) {
        uint32_t e[4] = {v[k].x, v[k].y, v[k].z, v[k].w};
#pragma unroll
        for (int z = 0; z < 4; z++) {
          const float a = lo(e[z]) - sm, b = hi(e[z]) - sm;
          a8[2 * z] = fmaf(a, a, k ? a8[2 * z] : 0.f); a8[2 * z + 1] = fmaf(b, b, k ? a8[2 * z + 1] : 0.f);
          e[z] = pack(a, b);
        }
        p[(k >> 1) * 512 + ((k ^ g) & 1) * 4] = make_uint4(e[0], e[1], e[2], e[3]);
      }
      float q = ((a8[0] + a8[1]) + (a8[2] + a8[3])) + ((a8[4] + a8[5]) + (a8[6] + a8[7]));
      q += __shfl_xor_sync(~0u, q, 1); q += __shfl_xor_sync(~0u, q, 2);
      rstd[1] = rsqrtf(q * (1.f / DM) + 1e-5f);
      if (hh == 0) rstd[0] = rstd[1];
    }
    fence_async_smem();
    bar_sync<3, 256>();
    epoch = epoch / NCTA + 1;
    mean[0] = mean[1] = 0.f;
  }
  STAMP(0);
  Ring ring{barFull, barEmpty, sb + OFF_RING, 0, 0};
  int apar = 1;
  const uint32_t stsm_off = (w * 16 + ((lane >> 3) & 1) * 8 + (lane & 7)) * 128;
  const uint32_t stsm_hi = lane >> 4;
  const uint64_t dA = mkdesc(abuf, 1024, 128, 0);

  auto gather = [&](unsigned* fl, const unsigned char* img) {
    bar_wg(c);
    if (w == 0) {
      if (elect_one()) {
        flag_arrive(fl);
#pragma unroll
        for (int k = 0; k < 7; k++) mbar_expect(barAc + k * 8, 8192);
        flag_wait(fl, epoch * 8);
        fence_async();
#pragma unroll
        for (int k = 0; k < 7; k++) bulk_ld(abuf + k * 8192, img + k * 8192, 8192, barAc + k * 8);
      }
      __syncwarp();
    }
    apar ^= 1;
  };
  auto slice_off = [&](int j, int hh) -> uint32_t {
    return (7 * r + j) * 1024 + (w * 2 + hh) * 128 + lane * 4;
  };
  auto load_stats = [&](const float2* st) {
    mbar_wait(barAc, apar);
#pragma unroll
    for (int hh = 0; hh < 2; hh++) {
      const float2* p = st + (size_t)row0 * 8 + 2 * t * 64 + w * 16 + hh * 8 + g;
      const uint2 a = ldcg2(p), b = ldcg2(p + 64);
      su[hh] = make_uint4(a.x, a.y, b.x, b.y);
    }
  };
  auto finish_stats = [&]() {
#pragma unroll
    for (int hh = 0; hh < 2; hh++) {
      const float m0 = __uint_as_float(su[hh].x), m1 = __uint_as_float(su[hh].z);
      float m = m0 + m1;
      m += __shfl_xor_sync(~0u, m, 1); m += __shfl_xor_sync(~0u, m, 2);
      m *= 0.125f;
      float q = __uint_as_float(su[hh].y) + __uint_as_float(su[hh].w) + 56.f * ((m0 - m) * (m0 - m) + (m1 - m) * (m1 - m));
      q += __shfl_xor_sync(~0u, q, 1); q += __shfl_xor_sync(~0u, q, 2);
      mean[hh] = m; rstd[hh] = rsqrtf(q * (1.f / DM) + 1e-5f);
    }
  };

#pragma unroll 1
  for (int lyr = 0; lyr < 2; lyr++) {
    const int layer = __shfl_sync(~0u, lyr, 0);
    unsigned* const fl = gFlag + (layer * 32 + G * 2 + c) * 7 * 32;
    uint32_t phiq[4][7];
    {
      float acc[92]; reg_def(acc);
      int prev = 0, prev2 = 0;
      ring.uniform();
      const uint64_t dQ = layer ? dA : mkdesc(abuf, 16, 1024, 1);
      const int kstep = layer ? 128 : 2;
      if (layer) load_stats(gStat + 2048 * 8);
#pragma unroll UNR
      for (int st = 0; st < 14; st++) {
        if (!(st & 1) && layer) mbar_wait(barAc + (st >> 1) * 8, apar);
        const uint64_t da = dQ + (st >> 1) * 512 + (st & 1) * 2 * kstep, db = mkdesc(ring.acquire(), 4096, 1024, 1);
        wg_fence();
        mma_ss_184(acc, da, db, 1);
        mma_ss_184(acc, da + kstep, db + 128, 1);
        wg_commit();
        if (st > 1) { wg_wait<2>(); ring.release(prev2, elect); }
        prev2 = prev; prev = ring.advance();
      }
      if (layer) {
        finish_stats();
#pragma unroll
        for (int j = 0; j < 7; j++) { xs[j][0] = lds32(abuf + slice_off(j, 0)); xs[j][1] = lds32(abuf + slice_off(j, 1)); }
      }
      wg_wait<0>(); reg_fence(acc);
      ring.release(prev2, elect); ring.release(prev, elect);
      STAMP(1 + layer * 12);
      uint32_t f[3][14];
      auto frags = [&](const int p0, const int p1) {
        const float2* cs = reinterpret_cast<const float2*>(sg + OFF_CS) + t;
        const float mr0 = -mean[0] * rstd[0], mr1 = -mean[1] * rstd[1];
#pragma unroll
        for (int p = p0; p < p1; p++)
#pragma unroll
          for (int j = 0; j < 7; j++) {
            const float2 s = cs[p * 32 + j * 4];
            const int b = p * 32 + j * 4;
            f[p][2 * j] = pack(fmaf(acc[b], rstd[0], s.x * mr0), fmaf(acc[b + 1], rstd[0], s.y * mr0));
            f[p][2 * j + 1] = pack(fmaf(acc[b + 2], rstd[1], s.x * mr1), fmaf(acc[b + 3], rstd[1], s.y * mr1));
          }
      };
      frags(1, 2);
      float pk[28]; reg_def(pk);
      const uint64_t dW = mkdesc(sb + OFF_WPHI, 4096, 1024, 1);
      wg_fence();
#pragma unroll
      for (int s = 0; s < 4; s++) {
        mma_rs_56(pk, f[1][4 * s], f[1][4 * s + 1], s < 3 ? f[1][(4 * s + 2) % 14] : 0u, s < 3 ? f[1][(4 * s + 3) % 14] : 0u, dW + s * 128, s);
      }
      wg_commit();
      frags(2, 3);
      bar_wg(c);
      const uint32_t srow = abuf + stsm_off, ones = t == 0 ? 0x3F803F80u : 0u;
#pragma unroll
      for (int jp = 0; jp < 4; jp++)
        stsm4(srow + 16384 + (((2 * jp + stsm_hi) ^ (lane & 7)) << 4), f[2][4 * jp], f[2][4 * jp + 1],
              jp < 3 ? f[2][(4 * jp + 2) % 14] : ones, jp < 3 ? f[2][(4 * jp + 3) % 14] : ones);
      wg_wait<0>(); reg_fence(pk);
      {
        dual_softmax(pk, phiq);
#pragma unroll
        for (int e = 0; e < 2; e++)
#pragma unroll
          for (int jp = 0; jp < 4; jp++)
            stsm4(srow + e * 8192 + (((2 * jp + stsm_hi) ^ (lane & 7)) << 4), phiq[e][2 * jp], phiq[2 + e][2 * jp],
                  jp < 3 ? phiq[e][(2 * jp + 1) % 7] : 0u, jp < 3 ? phiq[2 + e][(2 * jp + 1) % 7] : 0u);
        fence_async_smem();
        bar_sync<3, 256>();
        float kv[32], kw[32]; reg_def(kv); reg_def(kw);
        const uint64_t dP = mkdesc(sb + c * 8192, 4096, 1024, 1), dV = mkdesc(sb + 16384, 4096, 1024, 1);
        wg_fence();
#pragma unroll
        for (int s = 0; s < 4; s++) { mma_ss_64t(kv, dP + s * 128, dV + s * 128, s); mma_ss_64t(kw, dP + ABYTES / 16 + s * 128, dV + ABYTES / 16 + s * 128, s); }
        wg_commit();
        if (layer == 0) mbar_wait(barCS, 0);
        wg_wait<0>(); reg_fence(kv); reg_fence(kw);
#pragma unroll
        for (int i = 0; i < 32; i++) kv[i] += kw[i];
        float4* kvg = gKV + ((layer * 8 + r) * 2 + c) * 640 + (tid & 127);
#pragma unroll
        for (int i = 0; i < 5; i++) {
          float v0, v1, v2, v3;
          if (i == 4) { v0 = kv[28]; v1 = kv[29]; v2 = kv[30]; v3 = kv[31]; }
          else { v0 = c ? kv[12 + 4 * i] : kv[4 * i]; v1 = c ? kv[13 + 4 * i] : kv[1 + 4 * i]; v2 = c ? kv[14 + 4 * i] : kv[2 + 4 * i]; v3 = c ? kv[15 + 4 * i] : kv[3 + 4 * i]; }
          const bool use = i == 4 ? t == 0 : (i == 0 ? (c == 0 || t >= 2) : (i == 3 ? (c == 1 || t < 2) : true));
          if (use) asm volatile("red.relaxed.gpu.global.add.v4.f32 [%0], {%1,%2,%3,%4};" ::"l"(kvg + i * 128), "f"(v0), "f"(v1), "f"(v2), "f"(v3) : "memory");
        }
        asm volatile("bar.arrive 4, 288;" ::: "memory");
        STAMP(2 + layer * 12);
      }
      frags(0, 1);
      float pq[28]; reg_def(pq);
      wg_fence();
#pragma unroll
      for (int s = 0; s < 4; s++)
        mma_rs_56(pq, f[0][4 * s], f[0][4 * s + 1], s < 3 ? f[0][(4 * s + 2) % 14] : 0u, s < 3 ? f[0][(4 * s + 3) % 14] : 0u, dW + s * 128, s);
      wg_commit();
      wg_wait<0>(); reg_fence(pq);
      dual_softmax(pq, phiq);
    }
    {
      mbar_wait(barX + 16, layer);
      STAMP(3 + layer * 12);
      const float4* kvg = gKV + (layer * 8 + r) * 1280 + c * 640 + (tid & 127);
      uint4 kk[5];
#pragma unroll
      for (int i = 0; i < 5; i++) kk[i] = ldcg4(kvg + i * 128);
      uint32_t f[5][2];
#pragma unroll
      for (int i = 0; i < 5; i++) { f[i][0] = pack(__uint_as_float(kk[i].x), __uint_as_float(kk[i].y)); f[i][1] = pack(__uint_as_float(kk[i].z), __uint_as_float(kk[i].w)); }
      const uint32_t zm = c ? 0xFFFF0000u : 0xFFFFu;
      const uint32_t srow = abuf + 24576 + stsm_off;
#pragma unroll
      for (int jp = 0; jp < 4; jp++) {
        uint32_t v[2][2];
#pragma unroll
        for (int u = 0; u < 2; u++) {
          const int j = 2 * jp + u;
#pragma unroll
          for (int hh = 0; hh < 2; hh++) v[u][hh] = j == 7 ? f[4][hh] & zm : (c ? (j >= 3 ? f[(j + 2) % 5][hh] : 0u) : (j < 4 ? f[j % 5][hh] : 0u));
        }
        stsm4(srow + (((2 * jp + stsm_hi) ^ (lane & 7)) << 4), v[0][0], v[0][1], v[1][0], v[1][1]);
      }
      fence_async_smem();
      bar_sync<3, 256>();
      float num[32], nub[32]; reg_def(num); reg_def(nub);
      const uint64_t dK = mkdesc(sb + 24576, 4096, 1024, 1);
      wg_fence();
#pragma unroll
      for (int s = 0; s < 4; s++) {
        mma_rs_64(num, phiq[0][2 * s], phiq[2][2 * s], s < 3 ? phiq[0][(2 * s + 1) % 7] : 0u, s < 3 ? phiq[2][(2 * s + 1) % 7] : 0u, dK + s * 128, s);
        mma_rs_64(nub, phiq[1][2 * s], phiq[3][2 * s], s < 3 ? phiq[1][(2 * s + 1) % 7] : 0u, s < 3 ? phiq[3][(2 * s + 1) % 7] : 0u, dK + ABYTES / 16 + s * 128, s);
      }
      wg_commit();
      wg_wait<0>(); reg_fence(num); reg_fence(nub);
      bar_sync<3, 256>();
#pragma unroll
      for (int i = 12; i < 32; i++) num[i] += nub[i];
      float rd[4];
#pragma unroll
      for (int i = 0; i < 4; i++) rd[i] = __fdividef(1.f, __shfl_sync(~0u, num[28 + i], lane & ~3) + 1e-6f);
      unsigned char* img = gImg + (size_t)(G * 2 + c) * ABYTES;
#pragma unroll
      for (int j = 0; j < 7; j++) {
        const bool hb = j > 3 || (j == 3 && t >= 2);
        const float r0 = hb ? rd[1] : rd[0], r1 = hb ? rd[3] : rd[2];
        *reinterpret_cast<uint32_t*>(img + slice_off(j, 0)) = pack(num[4 * j] * r0, num[4 * j + 1] * r0);
        *reinterpret_cast<uint32_t*>(img + slice_off(j, 1)) = pack(num[4 * j + 2] * r1, num[4 * j + 3] * r1);
      }
      STAMP(4 + layer * 12);
      gather(fl, img);
      STAMP(5 + layer * 12);
    }
    {
      float acc[28], acc2[28]; reg_def(acc); reg_def(acc2); reg_fence(acc); reg_fence(acc2);
      int sl[4];
      ring.uniform();
#pragma unroll
      for (int st = 0; st < 4; st++) {
        const uint64_t db = mkdesc(ring.acquire(), 4096, 1024, 1);
        sl[st] = ring.advance();
#pragma unroll
        for (int s = 0; s < 7; s++) {
          const int ks = st * 7 + s;
          if (!(ks & 3)) mbar_wait(barAc + (ks >> 2) * 8, apar);
          if (!(ks & 3) || !s) wg_fence();
          if (ks & 1) mma_ss_56(acc2, dA + ks * 128, db + s * 128, ks > 1); else mma_ss_56(acc, dA + ks * 128, db + s * 128, ks > 1);
        }
        wg_commit();
      }
      wg_wait<0>(); reg_fence(acc); reg_fence(acc2);
      unsigned char* img = gImg + (size_t)(32 + G * 2 + c) * ABYTES;
#pragma unroll
      for (int hh = 0; hh < 2; hh++) {
        float s = 0.f, q = 0.f;
#pragma unroll
        for (int j = 0; j < 7; j++) {
          xs[j][hh] = pack(lo(xs[j][hh]) + (acc[4 * j + 2 * hh] + acc2[4 * j + 2 * hh]), hi(xs[j][hh]) + (acc[4 * j + 2 * hh + 1] + acc2[4 * j + 2 * hh + 1]));
          *reinterpret_cast<uint32_t*>(img + slice_off(j, hh)) = xs[j][hh];
          s += lo(xs[j][hh]) + hi(xs[j][hh]);
        }
        s += __shfl_xor_sync(~0u, s, 1); s += __shfl_xor_sync(~0u, s, 2);
        s *= 1.f / 56.f;
#pragma unroll
        for (int j = 0; j < 7; j++) { const float a = lo(xs[j][hh]) - s, b = hi(xs[j][hh]) - s; q = fmaf(a, a, q); q = fmaf(b, b, q); }
        q += __shfl_xor_sync(~0u, q, 1); q += __shfl_xor_sync(~0u, q, 2);
        if (t == 0) gStat[(size_t)row0 * 8 + r * 64 + w * 16 + hh * 8 + g] = make_float2(s, q);
      }
#pragma unroll
      for (int j = 0; j < 7; j++) xs[j][0] = xs[j][1] = 0u;
      STAMP(6 + layer * 12);
      gather(fl + 32, img);
#pragma unroll
      for (int st = 0; st < 4; st++) ring.release(sl[st], elect);
      STAMP(7 + layer * 12);
    }
    {
      uint32_t hf[28][2];
      {
        float acc[112]; reg_def(acc);
        int prev = 0, prev2 = 0;
        load_stats(gStat);
        ring.uniform();
#pragma unroll UNR
        for (int st = 0; st < 14; st++) {
          if (!(st & 1)) mbar_wait(barAc + (st >> 1) * 8, apar);
          const uint64_t da = dA + st * 256, db = mkdesc(ring.acquire(), 2048, 512, 2);
          wg_fence();
          mma_ss_224(acc, da, db, 1);
          mma_ss_224(acc, da + 128, db + 64, 1);
          wg_commit();
          if (st > 1) { wg_wait<2>(); ring.release(prev2, elect); }
          prev2 = prev; prev = ring.advance();
        }
        finish_stats();
        if (layer == 0) mbar_wait(barCS + 8, 0);
        wg_wait<0>(); reg_fence(acc);
        ring.release(prev2, elect); ring.release(prev, elect);
        STAMP(8 + layer * 12);
        const float4* bs = reinterpret_cast<const float4*>(sg + OFF_B1) + t;
        const float mr0 = -mean[0] * rstd[0], mr1 = -mean[1] * rstd[1];
#pragma unroll
        for (int j = 0; j < 28; j++) {
          const float4 b = bs[4 * j];
          const float2 s = make_float2(b.z, b.w);
          hf[j][0] = relu_sq(fmaf(acc[4 * j], rstd[0], fmaf(s.x, mr0, b.x)), fmaf(acc[4 * j + 1], rstd[0], fmaf(s.y, mr0, b.y)));
          hf[j][1] = relu_sq(fmaf(acc[4 * j + 2], rstd[1], fmaf(s.x, mr1, b.x)), fmaf(acc[4 * j + 3], rstd[1], fmaf(s.y, mr1, b.y)));
        }
      }
      unsigned char* pd[2]; int pstr[2];
#pragma unroll
      for (int hh = 0; hh < 2; hh++) {
        const bool own = 2 * w + hh == r;
        pd[hh] = own ? sg + c * ABYTES + (lane >> 4) * 1024 + (r ^ 1) * 128 + (lane & 15) * 8
                     : gP + (size_t)(((G * 2 + c) * 8 + 2 * w + hh) * 8 + r) * 7168 + lane * 8;
        pstr[hh] = own ? 2048 : 256;
      }
      uint2 pk[8] = {};
      ring.uniform();
#pragma unroll 1
      for (int ch = 0; ch < 7; ch++) {
        float acc[32], acc2[32]; reg_def(acc); reg_def(acc2);
        const uint64_t db0 = mkdesc(ring.acquire(), 4096, 1024, 1);
        const int sl0 = ring.advance();
        const uint64_t db1 = mkdesc(ring.acquire(), 4096, 1024, 1);
        const int sl1 = ring.advance();
        wg_fence();
#pragma unroll
        for (int s = 0; s < 7; s++) {
          mma_rs_64(acc, hf[2 * s][0], hf[2 * s][1], hf[2 * s + 1][0], hf[2 * s + 1][1], db0 + s * 128, s);
          mma_rs_64(acc2, hf[14 + 2 * s][0], hf[14 + 2 * s][1], hf[15 + 2 * s][0], hf[15 + 2 * s][1], db1 + s * 128, s);
        }
        wg_commit();
        if (ch > 0) {
#pragma unroll
          for (int i = 0; i < 8; i++) { *reinterpret_cast<uint2*>(pd[i & 1]) = pk[i]; pd[i & 1] += pstr[i & 1]; }
        }
        wg_wait<0>(); reg_fence(acc); reg_fence(acc2); ring.release(sl0, elect && ch < 6); ring.release(sl1, elect && ch < 6);
#pragma unroll
        for (int i = 0; i < 8; i++) {
          const int b = (i >> 1) * 8 + (i & 1) * 2;
          pk[i] = make_uint2((pack(acc[b] + acc2[b], acc[b + 1] + acc2[b + 1]) & ~1u) | (layer ^ 1), pack(acc[b + 4] + acc2[b + 4], acc[b + 5] + acc2[b + 5]));
        }
      }
#pragma unroll
      for (int i = 0; i < 8; i++) { *reinterpret_cast<uint2*>(pd[i & 1]) = pk[i]; pd[i & 1] += pstr[i & 1]; }
      STAMP(9 + layer * 12);
    }
    {
      uint32_t bx[14];
#pragma unroll
      for (int j = 0; j < 14; j++) bx[j] = __ldg(reinterpret_cast<const uint32_t*>(b2 + (j >> 1) * 64 + w * 16 + (j & 1) * 8 + 2 * t));
      const unsigned char* psrc = gP + (size_t)(((G * 2 + c) * 8 + r) * 8) * 7168 + w * 256 + lane * 8;
      unsigned char* img = gImg + (size_t)(64 + G * 2 + c) * ABYTES;
      uint2 pv[7][7];
      const unsigned char* ps[7];
#pragma unroll
      for (int s = 0; s < 7; s++) ps[s] = psrc + ((r + 1 + s) & 7) * 7168;
#pragma unroll
      for (int i = 0; i < 5; i++)
#pragma unroll
        for (int s = 0; s < 7; s++) pv[s][i] = ldcg2(ps[s] + i * 1024);
      bar_wg(c);
      const uint32_t off = w * 2048 + r * 128 + lane * 4;
      unsigned char* dst = layer ? reinterpret_cast<unsigned char*>(out + (size_t)(row0 + r * 8 + g) * DM + w * 16 + 4 * t) : img + off;
      float sm = 0.f, q = 0.f;
#pragma unroll
      for (int i = 0; i < 7; i++) {
        const uint2 own = *reinterpret_cast<const uint2*>(sg + c * ABYTES + i * 8192 + w * 2048 + (lane >> 4) * 1024 + (r ^ 1) * 128 + (lane & 15) * 8);
#pragma unroll 1
        for (int n = 0; n < (1 << 16); n++) {
          const uint32_t all = pv[0][i].x & pv[1][i].x & pv[2][i].x & pv[3][i].x & pv[4][i].x & pv[5][i].x & pv[6][i].x;
          const uint32_t any = pv[0][i].x | pv[1][i].x | pv[2][i].x | pv[3][i].x | pv[4][i].x | pv[5][i].x | pv[6][i].x;
          if (!__any_sync(~0u, (layer ? any : ~all) & 1u)) break;
#pragma unroll
          for (int s = 0; s < 7; s++) pv[s][i] = ldcg2(ps[s] + i * 1024);
        }
        if (i < 2) {
#pragma unroll
          for (int s = 0; s < 7; s++) pv[s][5 + (i & 1)] = ldcg2(ps[s] + (5 + i) * 1024);
        }
#pragma unroll
        for (int jj = 0; jj < 2; jj++) {
          const int j = 2 * i + jj;
          const uint32_t xo = lds32(abuf + off + i * 8192 + jj * 1024), uo = jj ? own.y : own.x;
          float y0 = lo(bx[j]) + lo(xo) + lo(uo), y1 = hi(bx[j]) + hi(xo) + hi(uo);
#pragma unroll
          for (int s = 0; s < 7; s++) { const uint32_t u = jj ? pv[s][i].y : pv[s][i].x; y0 += lo(u); y1 += hi(u); }
          bx[j] = pack(y0, y1);
          if (!layer) *reinterpret_cast<uint32_t*>(dst + (i * 8 + jj) * 1024) = bx[j];
          sm += lo(bx[j]) + hi(bx[j]);
        }
        if (layer) {
          const int sl = (lane & ~3) | ((t & 1) << 1);
          const uint32_t a0 = __shfl_sync(~0u, bx[2 * i], sl), a1 = __shfl_sync(~0u, bx[2 * i], sl + 1);
          const uint32_t b0 = __shfl_sync(~0u, bx[2 * i + 1], sl), b1v = __shfl_sync(~0u, bx[2 * i + 1], sl + 1);
          *reinterpret_cast<uint2*>(dst + i * 128) = t < 2 ? make_uint2(a0, a1) : make_uint2(b0, b1v);
        }
      }
      if (layer) break;
      sm += __shfl_xor_sync(~0u, sm, 1); sm += __shfl_xor_sync(~0u, sm, 2);
      sm *= 1.f / 112.f;
#pragma unroll
      for (int j = 0; j < 14; j++) { const float a = lo(bx[j]) - sm, b = hi(bx[j]) - sm; q = fmaf(a, a, q); q = fmaf(b, b, q); }
      q += __shfl_xor_sync(~0u, q, 1); q += __shfl_xor_sync(~0u, q, 2);
      if (t < 2) gStat[(size_t)(2048 + row0) * 8 + (2 * w + t) * 64 + r * 8 + g] = make_float2(sm, q * 0.5f);
      STAMP(11);
      gather(fl + 64, img);
#pragma unroll
      for (int i = 5; i < 7; i++) ring.release((ring.slot + i) % NSLOT, elect);
      STAMP(12);
    }
  }
  STAMP(30);
  if (tid == 0) asm volatile("red.relaxed.gpu.global.add.u32 [%0], 1;" ::"l"(gFlag + FL_DONE * 32) : "memory");
  }
}

typedef CUresult (*EncFn)(CUtensorMap*, CUtensorMapDataType, cuuint32_t, void*, const cuuint64_t*, const cuuint64_t*,
                          const cuuint32_t*, const cuuint32_t*, CUtensorMapInterleave, CUtensorMapSwizzle,
                          CUtensorMapL2promotion, CUtensorMapFloatOOBfill);

void make_map(EncFn enc, CUtensorMap* m, void* p, int rank, uint64_t d0, uint64_t d1, uint64_t d2, uint64_t s1, uint64_t s2,
              uint32_t b0, uint32_t b1, uint32_t b2, CUtensorMapSwizzle sw) {
  cuuint64_t dims[3] = {d0, d1, d2}, strides[2] = {s1, s2};
  cuuint32_t box[3] = {b0, b1, b2}, es[3] = {1, 1, 1};
  enc(m, CU_TENSOR_MAP_DATA_TYPE_BFLOAT16, rank, p, dims, strides, box, es, CU_TENSOR_MAP_INTERLEAVE_NONE, sw,
      CU_TENSOR_MAP_L2_PROMOTION_L2_128B, CU_TENSOR_MAP_FLOAT_OOB_FILL_NONE);
}

}

extern "C" void kernel_launch(void* const* d_in, const int* in_sizes, int n_in, void* d_out, int out_size) {
  static EncFn enc = nullptr;
  if (!enc) {
    cudaDriverEntryPointQueryResult st;
    void* fn = nullptr;
    cudaGetDriverEntryPoint("cuTensorMapEncodeTiled", &fn, cudaEnableDefault, &st);
    enc = (EncFn)fn;
    cudaFuncSetAttribute(fused_kernel, cudaFuncAttributeMaxDynamicSharedMemorySize, SMEM_BYTES);
  }
  CUtensorMap mQKV, mWO, mW1, mW2, mX;
  make_map(enc, &mX, d_in[0], 2, 448, 2048, 1, 896, 0, 64, 64, 1, CU_TENSOR_MAP_SWIZZLE_128B);
  make_map(enc, &mQKV, d_in[1], 3, 448, 448, 3, 2688, 896, 64, 32, 3, CU_TENSOR_MAP_SWIZZLE_128B);
  make_map(enc, &mWO, d_in[3], 2, 448, 448, 1, 896, 0, 64, 112, 1, CU_TENSOR_MAP_SWIZZLE_128B);
  make_map(enc, &mW1, d_in[5], 3, 32, 448, 56, 3584, 64, 32, 32, 7, CU_TENSOR_MAP_SWIZZLE_64B);
  make_map(enc, &mW2, d_in[7], 2, 448, 1792, 1, 896, 0, 64, 112, 1, CU_TENSOR_MAP_SWIZZLE_128B);
  fused_kernel<<<NCTA, 384, SMEM_BYTES, cudaStreamPerThread>>>(
      mQKV, mWO, mW1, mW2, mX, (const __nv_bfloat16*)d_in[2], (const __nv_bfloat16*)d_in[6],
      (const __nv_bfloat16*)d_in[8], (const __nv_bfloat16*)d_in[1], (const __nv_bfloat16*)d_in[3], (const __nv_bfloat16*)d_in[5],
      (const __nv_bfloat16*)d_in[7], (__nv_bfloat16*)d_out);
}
```
